```python
import torch

def _softmax(x, axis=-1):
    return torch.softmax(x, dim=axis)

def _gelu(x):
    return torch.nn.functional.gelu(x, approximate='tanh')

def _silu(x):
    return torch.nn.functional.silu(x)

def _sigmoid(x):
    return torch.sigmoid(x)

def _layernorm(x, axis=-1, eps=1e-05):
    m = x.mean(dim=axis, keepdim=True)
    v = x.var(dim=axis, keepdim=True, unbiased=False)
    return (x - m) / torch.sqrt(v + eps)

def _scatter_add(tgt, idx, src, axis=0):
    return tgt.clone().index_add_(axis, idx, src)

def _segment_sum(src, seg, n):
    out = torch.zeros((n,) + src.shape[1:], dtype=src.dtype)
    return out.index_add_(0, seg, src)

def _pad(x, pw):
    flat = tuple((v for pair in reversed(pw) for v in pair))
    return torch.nn.functional.pad(x, flat)
kernel_name = 'adaLN_cond__memory_aug_recurrent_mem_tr__glu_gated_swiglu__prompt'

def setup_inputs():

    _w = lambda a: (lambda t: t.to(torch.bfloat16) if t.is_floating_point() else t)(torch.as_tensor(a))

    def _A_setup():
        B, S, Dm = (1, 2048, 1024)
        H, Dh = (32, 128)
        M, seg = (8, 32)
        seg = min(seg, S)
        S = S // seg * seg
        return {'x': _w((lambda *s: torch.randn(*s, dtype=torch.bfloat16) * 0.05)(B, S, Dm)), 'mem0': _w((lambda *s: torch.randn(*s, dtype=torch.bfloat16) * 0.8)(B, M, Dm)), 'Wq': _w((lambda *s: torch.randn(*s, dtype=torch.bfloat16) * 0.8)(Dm, H, Dh) * Dm ** (-0.5)), 'Wk': _w((lambda *s: torch.randn(*s, dtype=torch.bfloat16) * 0.8)(Dm, H, Dh) * Dm ** (-0.5)), 'Wv': _w((lambda *s: torch.randn(*s, dtype=torch.bfloat16) * 0.8)(Dm, H, Dh) * Dm ** (-0.5)), 'Wo': _w((lambda *s: torch.randn(*s, dtype=torch.bfloat16) * 0.8)(H, Dh, Dm) * (H * Dh) ** (-0.5)), 'seg_len': seg}
    _A_in = _A_setup()

    def _B_setup():
        B, S, D, F = (1, 2048, 1024, 3584)
        return {'x': _w((lambda *s: torch.randn(*s, dtype=torch.bfloat16) * 0.05)(B, S, D)), 'w1': _w((lambda *s: torch.randn(*s, dtype=torch.bfloat16) * 0.4)(D, F) * (2.0 / D) ** 0.5), 'w3': _w((lambda *s: torch.randn(*s, dtype=torch.bfloat16) * 0.4)(D, F) * (2.0 / D) ** 0.5), 'w2': _w((lambda *s: torch.randn(*s, dtype=torch.bfloat16) * 0.4)(F, D) * (2.0 / F) ** 0.5)}
    _B_in = _B_setup()
    return {'A_x': _A_in['x'], 'A_mem0': _A_in['mem0'], 'A_Wq': _A_in['Wq'], 'A_Wk': _A_in['Wk'], 'A_Wv': _A_in['Wv'], 'A_Wo': _A_in['Wo'], 'A_seg_len': _A_in['seg_len'], 'B_x': _B_in['x'], 'B_w1': _B_in['w1'], 'B_w3': _B_in['w3'], 'B_w2': _B_in['w2'], 'c': _w((lambda *s: torch.randn(*s, dtype=torch.bfloat16) * 0.1)(1, 1024) * 8.0), 'w_mod': _w((lambda *s: torch.randn(*s, dtype=torch.bfloat16) * 0.1)(1024, 6 * 1024) * 1024 ** (-0.5) * 8.0)}

def reference(A_x, A_mem0, A_Wq, A_Wk, A_Wv, A_Wo, A_seg_len, B_x, B_w1, B_w3, B_w2, c, w_mod):

    def _A_ref(x, mem0, Wq, Wk, Wv, Wo, seg_len):
        B, S, Dm = x.shape
        H, Dh = (Wq.shape[1], Wq.shape[2])
        M = mem0.shape[1]
        scale = Dh ** (-0.5)
        n_seg = S // seg_len
        L = M + seg_len
        idx = torch.arange(L)
        mask = (idx[:, None] < M) | (idx[:, None] >= idx[None, :])
        mem = mem0
        outs = []
        for s in range(n_seg):
            xs = x[:, s * seg_len:(s + 1) * seg_len, :].clone()
            h = torch.concatenate([mem, xs], axis=1)
            q = torch.einsum('btd,dhe->bhte', h, Wq)
            k = torch.einsum('btd,dhe->bhte', h, Wk)
            v = torch.einsum('btd,dhe->bhte', h, Wv)
            scores = torch.einsum('bhqe,bhke->bhqk', q, k) * scale
            scores = torch.where(mask[None, None], scores, -1000000000.0)
            p = _softmax(scores, axis=-1)
            o = torch.einsum('bhqk,bhke->bhqe', p, v)
            o = torch.einsum('bhte,hed->btd', o, Wo)
            mem = o[:, :M, :].clone()
            outs.append(o[:, M:, :])
        return torch.concatenate(outs, axis=1)

    def _B_ref(x, w1, w3, w2):
        gate = torch.einsum('bsd,df->bsf', x, w1)
        up = torch.einsum('bsd,df->bsf', x, w3)
        h = _silu(gate) * up
        out = torch.einsum('bsf,fd->bsd', h, w2)
        return out
    x = A_x
    mod = (_silu(c) @ w_mod).reshape(c.shape[0], 6, 1, -1)
    sa, ca, ga, sb, cb, gb = (mod[:, 0].clone(), mod[:, 1].clone(), mod[:, 2].clone(), mod[:, 3].clone(), mod[:, 4].clone(), mod[:, 5].clone())
    h = _layernorm(x, axis=-1) * (1 + ca) + sa
    x = x + ga * _A_ref(h, A_mem0, A_Wq, A_Wk, A_Wv, A_Wo, A_seg_len)
    h = _layernorm(x, axis=-1) * (1 + cb) + sb
    x = x + gb * _B_ref(h, B_w1, B_w3, B_w2)
    return x
```

```cpp
#include <cuda_runtime.h>
#include <cuda_bf16.h>
#include <cuda.h>
#include <stdint.h>
#include <type_traits>

namespace {

constexpr int S_ = 2048, D_ = 1024, NSEG = 64, F_ = 3584;

__device__ __align__(1024) uint8_t g_h[S_ * D_ * 2];
__device__ __align__(1024) uint8_t g_att[S_ * 4096 * 2];
__device__ __align__(1024) uint8_t g_x1[S_ * D_ * 2];
__device__ __align__(1024) uint8_t g_h2[S_ * D_ * 2];
__device__ __align__(1024) uint8_t g_act[S_ * F_ * 2];
__device__ __align__(1024) float g_ws[2 * 4 * 16 * 4 * 8192];
__device__ __align__(1024) float g_stat[S_ * 2];
__device__ __align__(1024) float g_uv[F_ * 4];
__device__ __align__(1024) float g_slot[4 * 3 * 8 * 4 * 32 * 4];
__device__ __align__(128) __nv_bfloat16 g_mod[6 * D_];
__device__ __align__(128) float g_modp[3 * 2 * D_];
__device__ __align__(128) uint32_t g_flags[1024];
constexpr int FL_S1 = 0, FL_S2 = 32, FL_MOD = 64, FL_HEAD = 96, FL_EXIT = 128, FL_UV = 160, FL_GO = 192, FL_ATT = 256, FL_XT = 384, FL_OUT = 512, FL_F1 = 640, FL_SPL = 768;

__device__ __forceinline__ uint32_t smem_u32(const void* p) { return (uint32_t)__cvta_generic_to_shared(p); }
__device__ __forceinline__ uint32_t mapa(uint32_t a, uint32_t r) { uint32_t o; asm("mapa.shared::cluster.u32 %0, %1, %2;" : "=r"(o) : "r"(a), "r"(r)); return o; }
__device__ __forceinline__ uint32_t pack2(float a, float b) { uint32_t r; asm("cvt.rn.bf16x2.f32 %0, %1, %2;" : "=r"(r) : "f"(b), "f"(a)); return r; }
__device__ __forceinline__ float bf_lo(uint32_t w) { return __uint_as_float(w << 16); }
__device__ __forceinline__ float bf_hi(uint32_t w) { return __uint_as_float(w & 0xffff0000u); }
__device__ __forceinline__ float ex2(float x) { float y; asm("ex2.approx.ftz.f32 %0, %1;" : "=f"(y) : "f"(x)); return y; }
__device__ __forceinline__ float rcp(float x) { float y; asm("rcp.approx.ftz.f32 %0, %1;" : "=f"(y) : "f"(x)); return y; }
__device__ __forceinline__ uint32_t clk32() { uint64_t c; asm volatile("mov.u64 %0, %%clock64;" : "=l"(c) :: "memory"); return (uint32_t)c; }

__device__ __forceinline__ void mbar_init(uint32_t b, uint32_t n) { asm volatile("mbarrier.init.shared::cta.b64 [%0], %1;" :: "r"(b), "r"(n) : "memory"); }
__device__ __forceinline__ void mbar_arrive(uint32_t b) { asm volatile("mbarrier.arrive.shared::cta.b64 _, [%0];" :: "r"(b) : "memory"); }
__device__ __forceinline__ void mbar_expect(uint32_t b, uint32_t n) { asm volatile("mbarrier.arrive.expect_tx.shared::cta.b64 _, [%0], %1;" :: "r"(b), "r"(n) : "memory"); }
__device__ __forceinline__ uint32_t mbar_try(uint32_t b, uint32_t par) {
  uint32_t ok;
  asm volatile("{\n.reg .pred p;\nmbarrier.try_wait.parity.shared::cta.b64 p, [%1], %2;\nselp.u32 %0, 1, 0, p;\n}" : "=r"(ok) : "r"(b), "r"(par) : "memory");
  return ok;
}
__device__ __forceinline__ void mbar_wait(uint32_t b, uint32_t par) {
  asm volatile("{\n.reg .pred p;\n"
               "LOOP:\n"
               "mbarrier.try_wait.parity.shared::cta.b64 p, [%0], %1;\n"
               "@!p bra.uni LOOP;\n}" :: "r"(b), "r"(par) : "memory");
}
__device__ __forceinline__ void mbar_wait_safe(uint32_t b, uint32_t par) {
  uint32_t c = 0;
  while (!mbar_try(b, par)) { if (++c > 4000000u) __trap(); }
}
__device__ __forceinline__ bool elect_one() {
  uint32_t p;
  asm volatile("{\n.reg .pred p;\nelect.sync _|p, 0xffffffff;\nselp.u32 %0, 1, 0, p;\n}" : "=r"(p));
  return p;
}
__device__ __forceinline__ void sched_fence(uint32_t x, uint32_t y) { asm volatile("{\n.reg .pred p;\nsetp.eq.u32 p, %0, %1;\n@p trap;\n}" :: "r"(x), "r"(y) : "memory"); }
template <class T> __device__ __forceinline__ T opaque32(T x) { asm volatile("" : "+r"(x)); return x; }
template <class T> __device__ __forceinline__ T opaque64(T x) { asm volatile("" : "+l"(x)); return x; }
template <int ID, int N> __device__ __forceinline__ void bar_sync() { asm volatile("bar.sync %0, %1;" :: "n"(ID), "n"(N) : "memory"); }
template <int ID, int N> __device__ __forceinline__ void bar_arrive() { asm volatile("bar.arrive %0, %1;" :: "n"(ID), "n"(N) : "memory"); }
__device__ __forceinline__ void fence_async_smem() { asm volatile("fence.proxy.async.shared::cta;" ::: "memory"); }
__device__ __forceinline__ void fence_async_all() { asm volatile("fence.proxy.async;" ::: "memory"); }
__device__ __forceinline__ void fence_gpu() { asm volatile("fence.acq_rel.gpu;" ::: "memory"); }
__device__ __forceinline__ void red_add_u32(uint32_t* p, uint32_t v) { asm volatile("red.relaxed.gpu.global.add.u32 [%0], %1;" :: "l"(p), "r"(v) : "memory"); }
__device__ __forceinline__ uint32_t ld_acquire(const uint32_t* p) { uint32_t v; asm volatile("ld.acquire.gpu.global.u32 %0, [%1];" : "=r"(v) : "l"(p) : "memory"); return v; }
__device__ __forceinline__ void wait_flag(const uint32_t* p, uint32_t target) {
  uint32_t c = 0;
  while (ld_acquire(p) < target) { if (++c > 20000000u) __trap(); __nanosleep(20); }
}

__device__ __forceinline__ void tma2d(uint32_t dst, const CUtensorMap* m, int c0, int c1, uint32_t bar) {
  asm volatile("cp.async.bulk.tensor.2d.shared::cluster.global.mbarrier::complete_tx::bytes [%0], [%1, {%3, %4}], [%2];"
               :: "r"(dst), "l"(m), "r"(bar), "r"(c0), "r"(c1) : "memory");
}
__device__ __forceinline__ void tma5d(uint32_t dst, const CUtensorMap* m, int n0, int kb, uint32_t bar) {
  asm volatile("cp.async.bulk.tensor.5d.shared::cluster.global.mbarrier::complete_tx::bytes [%0], [%1, {%3, %5, %5, %5, %4}], [%2];"
               :: "r"(dst), "l"(m), "r"(bar), "r"(n0), "r"(2 * kb), "r"(0) : "memory");
}
__device__ __forceinline__ void tma2d_prefetch(const CUtensorMap* m, int c0, int c1) {
  asm volatile("cp.async.bulk.prefetch.tensor.2d.L2.global [%0, {%1, %2}];" :: "l"(m), "r"(c0), "r"(c1) : "memory");
}
__device__ __forceinline__ void bulk_g2s(uint32_t dst, const void* src, uint32_t bytes, uint32_t bar) {
  asm volatile("cp.async.bulk.shared::cluster.global.mbarrier::complete_tx::bytes [%0], [%1], %2, [%3];"
               :: "r"(dst), "l"(src), "r"(bytes), "r"(bar) : "memory");
}
__device__ __forceinline__ void bulk_s2s(uint32_t dst, uint32_t src, uint32_t bytes, uint32_t bar) {
  asm volatile("cp.async.bulk.shared::cluster.shared::cta.mbarrier::complete_tx::bytes [%0], [%1], %2, [%3];"
               :: "r"(dst), "r"(src), "r"(bytes), "r"(bar) : "memory");
}
__device__ __forceinline__ void st_async1(uint32_t dst, uint32_t a, uint32_t bar) {
  asm volatile("st.async.shared::cluster.mbarrier::complete_tx::bytes.b32 [%0], %1, [%2];" :: "r"(dst), "r"(a), "r"(bar) : "memory");
}
__device__ __forceinline__ void st_async2(uint32_t dst, uint32_t a, uint32_t b, uint32_t bar) {
  asm volatile("st.async.shared::cluster.mbarrier::complete_tx::bytes.v2.b32 [%0], {%1, %2}, [%3];" :: "r"(dst), "r"(a), "r"(b), "r"(bar) : "memory");
}
__device__ __forceinline__ void st_async4(uint32_t dst, const uint32_t* r, uint32_t bar) {
  asm volatile("st.async.shared::cluster.mbarrier::complete_tx::bytes.v4.b32 [%0], {%1, %2, %3, %4}, [%5];"
               :: "r"(dst), "r"(r[0]), "r"(r[1]), "r"(r[2]), "r"(r[3]), "r"(bar) : "memory");
}
__device__ __forceinline__ void sts32(uint32_t a, uint32_t v) { asm volatile("st.shared.b32 [%0], %1;" :: "r"(a), "r"(v) : "memory"); }
__device__ __forceinline__ void sts64(uint32_t a, uint32_t x, uint32_t y) { asm volatile("st.shared.v2.b32 [%0], {%1, %2};" :: "r"(a), "r"(x), "r"(y) : "memory"); }
__device__ __forceinline__ void sts128(uint32_t a, uint32_t x, uint32_t y, uint32_t z, uint32_t w) {
  asm volatile("st.shared.v4.b32 [%0], {%1, %2, %3, %4};" :: "r"(a), "r"(x), "r"(y), "r"(z), "r"(w) : "memory");
}
__device__ __forceinline__ void lds128(uint32_t* r, uint32_t a) {
  asm volatile("ld.shared.v4.b32 {%0, %1, %2, %3}, [%4];" : "=r"(r[0]), "=r"(r[1]), "=r"(r[2]), "=r"(r[3]) : "r"(a) : "memory");
}
__device__ __forceinline__ uint32_t lds32(uint32_t a) { uint32_t r; asm volatile("ld.shared.b32 %0, [%1];" : "=r"(r) : "r"(a) : "memory"); return r; }
__device__ __forceinline__ void lds64(uint32_t* r, uint32_t a) {
  asm volatile("ld.shared.v2.b32 {%0, %1}, [%2];" : "=r"(r[0]), "=r"(r[1]) : "r"(a) : "memory");
}
__device__ __forceinline__ void lds128f(float* r, uint32_t a) {
  asm volatile("ld.shared.v4.f32 {%0, %1, %2, %3}, [%4];" : "=f"(r[0]), "=f"(r[1]), "=f"(r[2]), "=f"(r[3]) : "r"(a) : "memory");
}
__device__ __forceinline__ void lds64f(float* r, uint32_t a) {
  asm volatile("ld.shared.v2.f32 {%0, %1}, [%2];" : "=f"(r[0]), "=f"(r[1]) : "r"(a) : "memory");
}
__device__ __forceinline__ void ldsm4(uint32_t* r, uint32_t a) {
  asm volatile("ldmatrix.sync.aligned.m8n8.x4.shared.b16 {%0, %1, %2, %3}, [%4];" : "=r"(r[0]), "=r"(r[1]), "=r"(r[2]), "=r"(r[3]) : "r"(a) : "memory");
}
__device__ __forceinline__ void ldsm4t(uint32_t* r, uint32_t a) {
  asm volatile("ldmatrix.sync.aligned.m8n8.x4.trans.shared.b16 {%0, %1, %2, %3}, [%4];" : "=r"(r[0]), "=r"(r[1]), "=r"(r[2]), "=r"(r[3]) : "r"(a) : "memory");
}
__device__ __forceinline__ void ldsm2(uint32_t* r, uint32_t a) {
  asm volatile("ldmatrix.sync.aligned.m8n8.x2.shared.b16 {%0, %1}, [%2];" : "=r"(r[0]), "=r"(r[1]) : "r"(a) : "memory");
}
__device__ __forceinline__ void stsm4(uint32_t a, const uint32_t* r) {
  asm volatile("stmatrix.sync.aligned.m8n8.x4.shared.b16 [%0], {%1, %2, %3, %4};" :: "r"(a), "r"(r[0]), "r"(r[1]), "r"(r[2]), "r"(r[3]) : "memory");
}
__device__ __forceinline__ uint32_t hadd2(uint32_t a, uint32_t b) { uint32_t t; asm("add.rn.bf16x2 %0, %1, %2;" : "=r"(t) : "r"(a), "r"(b)); return t; }
__device__ __forceinline__ uint32_t hmax2(uint32_t a, uint32_t b) { uint32_t t; asm("max.bf16x2 %0, %1, %2;" : "=r"(t) : "r"(a), "r"(b)); return t; }
__device__ __forceinline__ void ldsm2t(uint32_t* r, uint32_t a) {
  asm volatile("ldmatrix.sync.aligned.m8n8.x2.trans.shared.b16 {%0, %1}, [%2];" : "=r"(r[0]), "=r"(r[1]) : "r"(a) : "memory");
}
__device__ __forceinline__ uint32_t movm(uint32_t x) { uint32_t y; asm volatile("movmatrix.sync.aligned.m8n8.trans.b16 %0, %1;" : "=r"(y) : "r"(x)); return y; }
__device__ __forceinline__ void hmma(float* d, uint32_t a0, uint32_t a1, uint32_t a2, uint32_t a3, uint32_t b0, uint32_t b1) {
  asm volatile("mma.sync.aligned.m16n8k16.row.col.f32.bf16.bf16.f32 {%0,%1,%2,%3}, {%4,%5,%6,%7}, {%8,%9}, {%0,%1,%2,%3};"
               : "+f"(d[0]), "+f"(d[1]), "+f"(d[2]), "+f"(d[3]) : "r"(a0), "r"(a1), "r"(a2), "r"(a3), "r"(b0), "r"(b1));
}
__device__ __forceinline__ void hmma0(float* d, uint32_t a0, uint32_t a1, uint32_t a2, uint32_t a3, uint32_t b0, uint32_t b1) {
  asm volatile("mma.sync.aligned.m16n8k16.row.col.f32.bf16.bf16.f32 {%0,%1,%2,%3}, {%4,%5,%6,%7}, {%8,%9}, {%10,%10,%10,%10};"
               : "=f"(d[0]), "=f"(d[1]), "=f"(d[2]), "=f"(d[3]) : "r"(a0), "r"(a1), "r"(a2), "r"(a3), "r"(b0), "r"(b1), "f"(0.f));
}
__device__ __forceinline__ void hmma_k8(float* d, uint32_t a0, uint32_t a1, uint32_t b0) {
  asm volatile("mma.sync.aligned.m16n8k8.row.col.f32.bf16.bf16.f32 {%0,%1,%2,%3}, {%4,%5}, {%6}, {%0,%1,%2,%3};"
               : "+f"(d[0]), "+f"(d[1]), "+f"(d[2]), "+f"(d[3]) : "r"(a0), "r"(a1), "r"(b0));
}
__host__ __device__ constexpr uint64_t mkdesc(uint32_t addr, uint32_t lbo, uint32_t sbo, uint32_t sw) {
  return (uint64_t)((addr & 0x3FFFF) >> 4) | ((uint64_t)(lbo >> 4) << 16) | ((uint64_t)(sbo >> 4) << 32) | ((uint64_t)sw << 62);
}
#define WG_FENCE() asm volatile("wgmma.fence.sync.aligned;" ::: "memory")
#define WG_COMMIT() asm volatile("wgmma.commit_group.sync.aligned;" ::: "memory")
#define WG_WAIT(n) asm volatile("wgmma.wait_group.sync.aligned " #n ";" ::: "memory")
template <int N> __device__ __forceinline__ void reg_fence(float* d) {
#pragma unroll
  for (int i = 0; i < N; i++) asm volatile("" : "+f"(d[i]) :: "memory");
}
template <int N> __device__ __forceinline__ void zero_regs(float* d) {
#pragma unroll
  for (int i = 0; i < N; i++) asm volatile("mov.b32 %0, 0;" : "=f"(d[i]));
}
template <int SD>
__device__ __forceinline__ void wg_rs32(float* d, uint32_t a0, uint32_t a1, uint32_t a2, uint32_t a3, uint64_t b) {
  asm volatile("wgmma.mma_async.sync.aligned.m64n32k16.f32.bf16.bf16 {%0,%1,%2,%3,%4,%5,%6,%7,%8,%9,%10,%11,%12,%13,%14,%15}, {%16,%17,%18,%19}, %20, %21, 1, 1, 0;"
               : "+f"(d[0]), "+f"(d[1]), "+f"(d[2]), "+f"(d[3]), "+f"(d[4]), "+f"(d[5]), "+f"(d[6]), "+f"(d[7]),
                 "+f"(d[8]), "+f"(d[9]), "+f"(d[10]), "+f"(d[11]), "+f"(d[12]), "+f"(d[13]), "+f"(d[14]), "+f"(d[15])
               : "r"(a0), "r"(a1), "r"(a2), "r"(a3), "l"(b), "n"(SD));
}
template <int TB>
__device__ __forceinline__ void wg_ss40(float* d, uint64_t a, uint64_t b) {
  asm volatile("wgmma.mma_async.sync.aligned.m64n40k16.f32.bf16.bf16 {%0,%1,%2,%3,%4,%5,%6,%7,%8,%9,%10,%11,%12,%13,%14,%15,%16,%17,%18,%19}, %20, %21, 1, 1, 1, 1, %22;"
               : "+f"(d[0]), "+f"(d[1]), "+f"(d[2]), "+f"(d[3]), "+f"(d[4]), "+f"(d[5]), "+f"(d[6]), "+f"(d[7]),
                 "+f"(d[8]), "+f"(d[9]), "+f"(d[10]), "+f"(d[11]), "+f"(d[12]), "+f"(d[13]), "+f"(d[14]), "+f"(d[15]),
                 "+f"(d[16]), "+f"(d[17]), "+f"(d[18]), "+f"(d[19])
               : "l"(a), "l"(b), "n"(TB));
}
template <int T>
__device__ __forceinline__ void wg_ss32(float* d, uint64_t a, uint64_t b) {
  asm volatile("wgmma.mma_async.sync.aligned.m64n32k16.f32.bf16.bf16 {%0,%1,%2,%3,%4,%5,%6,%7,%8,%9,%10,%11,%12,%13,%14,%15}, %16, %17, 1, 1, 1, %18, %18;"
               : "+f"(d[0]), "+f"(d[1]), "+f"(d[2]), "+f"(d[3]), "+f"(d[4]), "+f"(d[5]), "+f"(d[6]), "+f"(d[7]),
                 "+f"(d[8]), "+f"(d[9]), "+f"(d[10]), "+f"(d[11]), "+f"(d[12]), "+f"(d[13]), "+f"(d[14]), "+f"(d[15])
               : "l"(a), "l"(b), "n"(T));
}

constexpr int R_TAIL = 0;
constexpr int R_WO = 65536;
constexpr int R_QK = R_WO + 86016;
constexpr int R_P = R_QK + 10240;
constexpr int R_GA = R_P + 6400;
constexpr int R_M2 = R_GA + 16384;
constexpr int R_M1 = R_M2 + 7168;
constexpr int R_GB = R_M1 + 9216;
constexpr int R_VT = R_GB + 16384;
constexpr int R_VM = R_VT + 8192;
constexpr int R_XS = R_VM + 2048;
constexpr int R_OX = R_XS + 1280;
constexpr int R_BAR = R_OX + 2048;
constexpr int R_TRC = R_BAR + 256;
constexpr int R_SMEM = R_TRC + 1024;
constexpr int B_MB = 0, B_XS = 32, B_VM = 40, B_VT = 48, B_TS = 56, B_FA = 64, B_FB = 72, B_TAIL = 80, B_WO = 88, B_STG = 96, B_WM = 128, B_X = 136;
constexpr int NB_A = 1, NB_B = 2, NB_X = 3, NB_C = 4, NB_D = 5, NB_E = 6, NB_F = 7, NB_G = 8, NB_H = 9, NB_S = 10, NB_E2 = 11, NB_P = 12, NB_W0 = 13;

#define POLL_DELAY 750
#define POLL_DELAY1 700
#define POLL_STAG 150
#define POLL_K0 20
#define PF1 2
#define PF2 2
#define PF3 2
#define PF4 0
#define RF_FIRST 1
#define BX_I 5
#define NCH 4
#define TOP2 0
#define CX_I 13
#define ATT_LATE 0
#define V_FENCE 1
#define SELF_STAS 1
#define Q_FENCE 1
#define ND_K 3
#define TRACE(i)
#define TS(i)

__device__ __forceinline__ int rot_chunk(int c, int rank) {
  int G = c;
  if (c < 9) { G = c + 3 * rank; if (G >= 9) G -= 9; }
  return G;
}
__device__ __forceinline__ int wo_tile(int i, int rank) {
  if (i < 12) return 12 * rank + i;
  const int r = i - 12 + 9 * rank;
  return r < 16 ? 48 + r : 20 + r;
}
__device__ __forceinline__ void load_chunk(uint32_t dst, int seg, int G, uint32_t bar) {
  mbar_expect(bar, 4096);
  bulk_g2s(dst, g_h + (size_t)(seg * 16 + G) * 4096, 4096, bar);
}
__device__ __forceinline__ void load_red(uint32_t* v, const float* p) {
#pragma unroll
  for (int j = 0; j < 2; j++)
    asm volatile("ld.relaxed.gpu.global.v4.u32 {%0, %1, %2, %3}, [%4];"
                 : "=r"(v[4 * j]), "=r"(v[4 * j + 1]), "=r"(v[4 * j + 2]), "=r"(v[4 * j + 3]) : "l"(p + j * 256) : "memory");
}
__device__ __forceinline__ bool red_done(const uint32_t* v) { return __all_sync(0xffffffffu, (v[3] & v[7]) == 0x42000000u); }
__device__ __forceinline__ uint32_t finish_red(uint32_t* v, const float* p) {
  uint32_t tries = 0;
  if (__builtin_expect(!red_done(v), 0)) {
    do { if (++tries > 20000000u) __trap(); load_red(v, p); } while (!red_done(v));
  }
  return tries;
}
__device__ __forceinline__ void exp10(float* sv, const uint32_t* x) {
  constexpr float SC = 0.08838834764831845f * 1.4426950408889634f;
  uint32_t m2 = hmax2(hmax2(hmax2(x[0], x[1]), hmax2(x[2], x[3])), x[4]);
  m2 = hmax2(m2, __shfl_xor_sync(0xffffffffu, m2, 1));
  m2 = hmax2(m2, __shfl_xor_sync(0xffffffffu, m2, 2));
  const float nm = -fmaxf(bf_lo(m2), bf_hi(m2)) * SC;
#pragma unroll
  for (int j = 0; j < 5; j++) { sv[2 * j] = ex2(fmaf(bf_lo(x[j]), SC, nm)); sv[2 * j + 1] = ex2(fmaf(bf_hi(x[j]), SC, nm)); }
}

__device__ __forceinline__ uint32_t arm_size(int w, bool isC) {
  return w == 0 ? (isC ? 1280 : 640) : w == 1 ? (isC ? 0 : 2048) : w == 2 ? (isC ? 0 : 8192) : (isC ? 0 : 1792);
}
struct RDesc { uint64_t tok[32], tail_b[16], tail_a[32]; };

template <int WG>
__device__ __forceinline__ void r_main(const uint32_t (&W)[48][4], const RDesc& dsc, int head, uint32_t rank, int lane_, int w) {
  const uint32_t sb = (rank << 24) + 0x400, bars = sb + R_BAR;
  const uint32_t to1 = rank == 0 ? 2u << 24 : 0u - (1u << 24), to2 = rank == 2 ? 0u - (2u << 24) : 1u << 24;
  const bool isC = rank == 2;
  const int lane = opaque32(lane_), warp = WG * 4 + w;
  const int gl = rot_chunk(4 * (lane & 3) + w, rank);
  const int g0 = __shfl_sync(0xffffffffu, gl, 0), g1 = __shfl_sync(0xffffffffu, gl, 1), g2 = __shfl_sync(0xffffffffu, gl, 2);
  const uint32_t arm_bytes = arm_size(w, isC);

#define L16 opaque32(sb + opaque32(lane) * 16)
#define L8 opaque32(sb + opaque32(lane) * 8)
#define L4 opaque32(sb + opaque32(lane) * 4)
#define LV opaque32(sb + R_VT + ((opaque32(lane) >> 3) & 1) * 512 + (opaque32(lane) >> 4) * 128 + (opaque32(lane) & 7) * 16)
#define SLOT(st) opaque64(slot0 + ((st) & 3) * 12288 + ((st) & 4) * 32)
  float* const slot0 = opaque64(g_slot + (rank * 1024 + warp * 128 + lane) * 4);
  const uint32_t woa = opaque32(sb + R_WO + warp * 12288 + ((lane >> 4) * 8 + (lane & 7)) * 32 + ((((lane >> 3) ^ (lane >> 2)) & 1) << 4));
  const bool has_wo = WG == 0 || isC || w < 3;
  float acc[20];
  uint32_t pk[8] = {0u, 0u, 0u, 0u, 0u, 0u, 0u, 0u};

  auto forward = [&](auto rd, const uint32_t* v, int st, uint32_t tries) {
    constexpr int RD = decltype(rd)::value;
    uint32_t u[6];
#pragma unroll
    for (int j = 0; j < 6; j++) u[j] = movm(v[4 * (j / 3) + j % 3]);
    const bool all3 = RD == 0 || w < 3;
    if (RD == 0) {
      const uint32_t a = L16 + R_M1 + w * 768, a2 = L8 + R_M1 + 512 + w * 768;
      st_async4(a + to1 + 3072, u, bars + to1 + B_MB + 8); st_async2(a2 + to1 + 3072, u[4], u[5], bars + to1 + B_MB + 8);
      sts128(a, u[0], u[1], u[2], u[3]); sts64(a2, u[4], u[5]);
      __syncwarp();
      if (elect_one()) mbar_arrive(bars + B_MB);
      st_async4(a + to2 + 6144, u, bars + to2 + B_MB + 16); st_async2(a2 + to2 + 6144, u[4], u[5], bars + to2 + B_MB + 16);
    } else {
      const uint32_t a = L4 + R_M2 + rank * 2304 + w * 768;
#pragma unroll
      for (int j = 0; j < 6; j++) if (j < 2 || all3) st_async1(a + to1 + j * 128, u[j], bars + to1 + B_MB + 24);
#pragma unroll
      for (int j = 0; j < 6; j++) if (j < 2 || all3) st_async1(a + to2 + j * 128, u[j], bars + to2 + B_MB + 24);
      if (SELF_STAS) {
#pragma unroll
        for (int j = 0; j < 6; j++) if (j < 2 || all3) st_async1(a + j * 128, u[j], bars + B_MB + 24);
      } else {
#pragma unroll
        for (int j = 0; j < 6; j++) if (j < 2 || all3) sts32(a + j * 128, u[j]);
        __syncwarp();
        if (elect_one()) mbar_arrive(bars + B_MB + 24);
      }
    }
  };

  auto send_vt = [&]() {
    if (elect_one()) {
      const uint32_t src = sb + R_VT + warp * 1024;
      bulk_s2s(src + to1, src, 1024, bars + to1 + B_VT);
      bulk_s2s(src + to2, src, 1024, bars + to2 + B_VT);
    }
  };
  auto store_att = [&](int sg) {
    uint32_t* op = reinterpret_cast<uint32_t*>(g_att + (size_t)((sg >> 2) * 64 + head * 2 + rank) * 16384 + (2 * w * 16 + (sg & 3) * 4) * 128) + opaque32(lane);
#pragma unroll
    for (int j = 0; j < 8; j++) op[(j & 1) * 512 + (j >> 1) * 32] = pk[j];
  };

  if (WG == 0) bar_arrive<NB_G, 256>();
#pragma unroll 1
  for (int s = -1; s < NSEG; s++) {
    const uint32_t par = (s + 1) & 1;
    const uint32_t last = s == NSEG - 1;
    TRACE(0);
    {
      float c[NCH][4];
      uint32_t b[3][6];
      const uint32_t ma = L16, m8 = L8;
#pragma unroll
      for (int i = 0; i < 18; i++) {
        if (i < 16) {
          if (i % 4 == 0 && !(i == 4 && TOP2)) mbar_wait(bars + B_MB + (i / 4) * 8, par ^ 1);
          if (i == 0 && TOP2) mbar_wait(bars + B_MB + 8, par ^ 1);
          if (i % 4 == 0) TRACE(1 + i / 4);
          if (i < 12) { lds128(b[i % 3], ma + R_M1 + i * 768); lds64(b[i % 3] + 4, m8 + R_M1 + 512 + i * 768); }
          else { ldsm4(b[i % 3], ma + R_M2 + 4096 + (i - 12) * 768); ldsm2(b[i % 3] + 4, ma + R_M2 + 4096 + 512 + (i - 12) * 768); }
          if (WG == 1 && i == BX_I) {
            bar_sync<NB_G, 256>();
            if (!last && elect_one()) load_chunk(sb + R_GB + w * 4096, s + 1, g0, bars + B_FB);
          }
          if (i == CX_I) {
            if (isC && s >= 0) send_vt();
            if (WG == 1 && ATT_LATE && !isC && s > 0) store_att(s - 1);
          }
          __syncwarp();
        }
        if (i >= 2) {
          const int j = i - 2;
#pragma unroll
          for (int q = 0; q < 3; q++) {
            const uint32_t* f = W[3 * j + q];
            if (3 * j + q < NCH) hmma0(c[3 * j + q], f[0], f[1], f[2], f[3], b[j % 3][2 * q], b[j % 3][2 * q + 1]);
            else hmma(c[(3 * j + q) % NCH], f[0], f[1], f[2], f[3], b[j % 3][2 * q], b[j % 3][2 * q + 1]);
          }
        }
        if (i == 14) zero_regs<16>(acc);
        if (i == 16) mbar_wait(bars + B_FA, last);
      }
#pragma unroll
      for (int j = 0; j < 4; j++) acc[16 + j] = NCH == 3 ? (c[0][j] + c[1][j]) + c[2][j] : (c[0][j] + c[1][j]) + (c[2][j] + c[NCH - 1][j]);
    }
    TRACE(5);
    bar_sync<NB_H, 256>();
    WG_FENCE();
#pragma unroll
    for (int k = 0; k < 16; k++) wg_ss40<0>(acc, dsc.tail_a[WG * 16 + k], dsc.tail_b[k]);
    WG_COMMIT();
    uint32_t vt[4][4];
    {
      const uint32_t a = opaque32(L4 + w * 256 + (isC ? WG * 1024 + R_VM : R_QK + 4096 + WG * 5120));
      const uint32_t qa = L16 + R_QK, xa = opaque32(LV + w * 2048 + (WG == 0 ? 0 : (opaque32(lane) & 8) * 64 + R_QK + 5120 - R_VT));
      const uint32_t d = opaque32(L4 + R_XS + rank * 640 + w * 256);
      if (s == 0) {
        mbar_wait_safe(bars + B_WO, 0);
        TS(10);
        if (WG == 1 && head == 0 && rank == 0 && w == 0 && elect_one()) red_add_u32(&g_flags[FL_GO], 1);
      }
      mbar_wait(bars + B_FB, last);
      if (WG == 0) mbar_wait(bars + B_VT, par);
      WG_WAIT(0);
      reg_fence<20>(acc);
      TRACE(6);
      const uint32_t p0 = pack2(acc[16], acc[17]), p1 = pack2(acc[18], acc[19]);
      sts32(a, p0); sts32(a + 128, p1);
      if (isC) {
        st_async1(a + to1, p0, bars + B_VM + to1); st_async1(a + to1 + 128, p1, bars + B_VM + to1);
        st_async1(a + to2, p0, bars + B_VM + to2); st_async1(a + to2 + 128, p1, bars + B_VM + to2);
      }
      if (WG == 0) {
        bar_arrive<NB_A, 256>();
        if (Q_FENCE && !isC) fence_async_smem();
#pragma unroll
        for (int i = 0; i < 4; i++) ldsm4(vt[i], xa + (i >> 1) * 1024 + (i & 1) * 256);
        bar_sync<NB_S, 256>();
      } else {
        bar_sync<NB_A, 256>();
        if (!isC) {
          if (w < 3) {
            uint32_t q[8], k[4][4];
            ldsm4t(q, qa + 4096); ldsm4t(k[0], xa); ldsm4t(k[1], xa + 256);
            ldsm4t(q + 4, qa + 4096 + 512); ldsm4t(k[2], xa + 512); ldsm4t(k[3], xa + 768);
            float x[4], y[4];
            hmma0(x, k[0][0], k[0][1], k[0][2], k[0][3], q[0], q[1]); hmma0(y, k[1][0], k[1][1], k[1][2], k[1][3], q[2], q[3]);
            hmma(x, k[2][0], k[2][1], k[2][2], k[2][3], q[4], q[5]); hmma(y, k[3][0], k[3][1], k[3][2], k[3][3], q[6], q[7]);
            const uint32_t s0 = pack2(x[0] + y[0], x[1] + y[1]), s1 = pack2(x[2] + y[2], x[3] + y[3]);
            st_async1(d + to1, s0, bars + B_XS + to1);
            st_async1(d + to2, s0, bars + B_XS + to2);
            if (w < 2) { st_async1(d + to1 + 128, s1, bars + B_XS + to1); st_async1(d + to2 + 128, s1, bars + B_XS + to2); sts32(d + 128, s1); }
            sts32(d, s0);
          }
        }
        bar_arrive<NB_S, 256>();
      }
    }
    if (WG == 1) {
      if (!last && elect_one()) load_chunk(sb + R_GA + w * 4096, s + 1, g1, bars + B_FA);
      {
        if (w > 0 && elect_one()) mbar_expect(bars + B_MB + 8 * w, w < 3 ? 3072 : SELF_STAS ? 28 * 256 : isC ? 18 * 256 : 19 * 256);
      }
      fence_async_smem();
      bar_sync<NB_B, 256>();
    }
    TRACE(7);
    WG_FENCE();
#pragma unroll
    for (int k = 0; k < 16; k++) wg_rs32<1>(acc, W[k][0], W[k][1], W[k][2], W[k][3], dsc.tok[16 + k]);
    WG_COMMIT();
    uint32_t wa[3][4];
    const uint32_t oxa = L16 + R_OX;
    if (WG == 0) {
      const uint32_t vma = oxa - (R_OX - R_VM) + w * 512, oa = opaque32(L4 + w * 512 + R_OX);
      TRACE(8);
      mbar_wait(bars + B_XS, par);
      TRACE(9);
      float sv[10];
      {
        uint32_t x[10];
        ldsm4t(x, oxa - (R_OX - R_XS)); ldsm4t(x + 4, oxa - (R_OX - R_XS) + 512); ldsm2t(x + 8, oxa - (R_OX - R_XS) + 1024);
        bar_arrive<NB_B, 256>();
#pragma unroll
        for (int j = 0; j < 5; j++) x[j] = hadd2(x[j], x[j + 5]);
        exp10(sv, x);
      }
      WG_WAIT(0);
      bar_arrive<NB_X, 256>();
      mbar_wait(bars + B_VM, par);
      uint32_t vm[4];
      ldsm4(vm, vma);
      uint32_t pb[5];
#pragma unroll
      for (int j = 0; j < 5; j++) pb[j] = pack2(sv[2 * j], sv[2 * j + 1]);
      TRACE(10);
      float o0[4], o1[4], sm[4];
      const uint32_t ONE = 0x3f803f80u;
      hmma0(o0, vt[0][0], vt[0][1], vt[0][2], vt[0][3], pb[0], pb[1]);
      hmma0(o1, vt[2][0], vt[2][1], vt[2][2], vt[2][3], pb[0], pb[1]);
      hmma0(sm, ONE, ONE, ONE, ONE, pb[0], pb[1]);
      hmma(sm, ONE, ONE, ONE, ONE, pb[2], pb[3]);
      hmma(o0, vt[1][0], vt[1][1], vt[1][2], vt[1][3], pb[2], pb[3]);
      hmma(o1, vt[3][0], vt[3][1], vt[3][2], vt[3][3], pb[2], pb[3]);
      hmma_k8(sm, ONE, ONE, pb[4]);
      hmma_k8(o0, vm[0], vm[1], pb[4]);
      hmma_k8(o1, vm[2], vm[3], pb[4]);
#pragma unroll
      for (int i = 0; i < 3; i++) ldsm4t(wa[i], woa + i * 4096);
      __syncwarp();
      const float i0 = rcp(sm[0]), i1 = rcp(sm[1]);
      sts32(oa, pack2(o0[0] * i0, o0[1] * i1)); sts32(oa + 128, pack2(o0[2] * i0, o0[3] * i1));
      sts32(oa + 256, pack2(o1[0] * i0, o1[1] * i1)); sts32(oa + 384, pack2(o1[2] * i0, o1[3] * i1));
      TRACE(11);
      bar_sync<NB_C, 128>();
    } else {
      if (!isC) {
        constexpr uint64_t dQ = mkdesc(0x400 + R_QK, 128, 1024, 0), dK = mkdesc(0x400 + R_QK + 5120, 128, 1024, 0);
        float sc[16];
        zero_regs<16>(sc);
        WG_FENCE();
#pragma unroll
        for (int k = 0; k < 4; k++) wg_ss32<1>(sc, dK + k * 16, dQ + k * 16);
        WG_COMMIT();
        const uint32_t top = rank == 0 ? to2 : to1, e = L4 + R_P + w * 256;
        WG_WAIT(0);
        bar_sync<NB_X, 256>();
        if (!last && elect_one()) load_chunk(sb + R_GB + w * 4096, s + 1, g2, bars + B_FB);
        reg_fence<16>(sc);
        if (w < 3) {
#pragma unroll
          for (int j = 0; j < 8; j++) {
            if ((j & 1) ? (j > 1 && (w == 0 || (w == 1 && j == 7))) : (j >= 4 || w != 1)) {
              const uint32_t t = pack2(sc[2 * j], sc[2 * j + 1]), o = (j >> 1) * 768 + (j & 1) * 128;
              st_async1(e + top + 3072 + o, t, bars + top + B_TS);
              sts32(e + o, t);
            }
          }
          __syncwarp();
          if (elect_one()) mbar_arrive(bars + B_TS);
        }
      } else {
        WG_WAIT(0);
        bar_sync<NB_X, 256>();
        if (!last && elect_one()) load_chunk(sb + R_GB + w * 4096, s + 1, g2, bars + B_FB);
      }
      TRACE(8);
      mbar_wait(bars + B_FA, 1);
      TRACE(11);
    }
    if (has_wo) {
      float* rslot = SLOT(s);
      uint32_t ob[4][4];
      float c[3][4];
      if (WG == 1) {
#pragma unroll
        for (int i = 0; i < 3; i++) ldsm4t(wa[i], woa + i * 4096);
        bar_sync<NB_D, 256>();
      }
      ldsm4t(ob[0], oxa);
      __syncwarp();
#pragma unroll
      for (int k = 0; k < 8; k++) {
        uint32_t nx[3][4];
        if ((k & 1) == 0 && k < 6) { ldsm4t(ob[(k >> 1) + 1], oxa + ((k >> 1) + 1) * 512); __syncwarp(); }
#pragma unroll
        for (int i = 0; i < 3; i++) {
          const uint32_t* o = ob[k >> 1] + (k & 1) * 2;
          if (k < 7) { ldsm4t(nx[i], woa + i * 4096 + (k + 1) * 512); if (i == 2) __syncwarp(); }
          if (k == 0) hmma0(c[i], wa[i][0], wa[i][1], wa[i][2], wa[i][3], o[0], o[1]);
          else hmma(c[i], wa[i][0], wa[i][1], wa[i][2], wa[i][3], o[0], o[1]);
#pragma unroll
          for (int q = 0; q < 4; q++) if (k < 7) wa[i][q] = nx[i][q];
        }
        if (k == ND_K && WG == 0) bar_arrive<NB_D, 256>();
      }
      const float* cv = &c[0][0];
      uint32_t r[6];
#pragma unroll
      for (int j = 0; j < 6; j++) r[j] = pack2(cv[2 * j], cv[2 * j + 1]);
      asm volatile("{\n.reg .pred p;\nsetp.lt.s32 p, %8, 0;\n@p bra.uni SKIP;\n"
                   "red.relaxed.gpu.global.add.noftz.v4.bf16x2 [%0], {%1, %2, %3, %7};\n"
                   "red.relaxed.gpu.global.add.noftz.v4.bf16x2 [%0+1024], {%4, %5, %6, %7};\nSKIP:\n}"
                   :: "l"(rslot), "r"(r[0]), "r"(r[1]), "r"(r[2]), "r"(r[3]), "r"(r[4]), "r"(r[5]), "r"(0x3f800000), "r"(s) : "memory");
    } else {
      bar_arrive<NB_D, 256>();
      if ((s & 3) == 0) {
        fence_gpu();
        if (s > 0 && elect_one()) red_add_u32(&g_flags[FL_ATT + 2 * (s - 4)], 1);
      }
      if (rank == 0 || head < 16)
        reinterpret_cast<uint4*>(g_slot)[((s + 2) & 3) * 3072 + ((s - 2) & 4) * 8 + rank * 2048 + head * 64 + opaque32(lane)] = make_uint4(0, 0, 0, 0);
    }
    const uint32_t t_red = clk32();
    uint32_t v[8];
    const float* slot = SLOT(s);
    TRACE(13);
    if (WG == 0) {
      if (!isC) {
        const int ln = opaque32(lane), kg = w - (ln >> 3);
        const uint32_t r16 = sb + R_P + w * 768 + (ln & 7) * 16;
        const uint32_t ta = r16 + (kg >= 0 ? kg * 128 : 640);
        const int dg = (ln >> 2) - 2 * (ln & 3);
        const uint32_t keep = dg > 0 ? 0xffffffffu : dg == 0 ? 0x0000ffffu : 0u;
        mbar_wait(bars + B_TS, par);
        uint32_t x[6], y[4];
        ldsm4t(x, ta); ldsm4t(y, ta + 3072); ldsm2t(x + 4, r16 + 512 + ((ln >> 3) & 1) * 3072);
#pragma unroll
        for (int j = 0; j < 5; j++) x[j] = hadd2(x[j], j < 4 ? y[j] : x[5]);
        x[0] = (x[0] & keep) | (0xff80ff80u & ~keep);
        float sv[10];
        exp10(sv, x);
        float sum = (((sv[0] + sv[1]) + (sv[2] + sv[3])) + ((sv[4] + sv[5]) + (sv[6] + sv[7]))) + (sv[8] + sv[9]);
        sum += __shfl_xor_sync(0xffffffffu, sum, 1);
        sum += __shfl_xor_sync(0xffffffffu, sum, 2);
        const float inv = rcp(sum);
#pragma unroll
        for (int j = 0; j < 5; j++) x[j] = pack2(sv[2 * j] * inv, sv[2 * j + 1] * inv);
        stsm4(r16 + (kg & 3) * 128, x);
        sts32(sb + ln * 4 + w * 768 + R_P + 512, x[4]);
        fence_async_smem();
        bar_arrive<NB_P, 256>();
      }
      while (clk32() - t_red < POLL_DELAY) {}
      load_red(v, slot);
      bar_sync<NB_E, 256>();
    } else {
      mbar_wait(bars + B_FB, 1);
    }
    TRACE(14);
    float ao[16];
    if (WG == 1) zero_regs<16>(ao);
    WG_FENCE();
#pragma unroll
    for (int k = 0; k < 32; k++) {
      if (WG == 0 && k == 16) WG_COMMIT();
      wg_rs32<1>(acc, W[16 + k][0], W[16 + k][1], W[16 + k][2], W[16 + k][3], dsc.tok[k]);
    }
    WG_COMMIT();
    TRACE(12);
    if (WG == 1) {
      if (!isC) {
        constexpr uint64_t dP = mkdesc(0x400 + R_P, 128, 768, 0);
        const uint64_t dV = mkdesc(0x400 + R_VT, 128, 512, 0) + rank * 256, dM = mkdesc(0x400 + R_VM, 0, 128, 0) + rank * 64;
        bar_sync<NB_P, 256>();
        WG_FENCE();
        wg_ss32<0>(ao, dV, dP); wg_ss32<0>(ao, dV + 16, dP + 16); wg_ss32<0>(ao, dM, dP + 32);
        WG_COMMIT();
      }
      bar_arrive<NB_E, 256>();
      if (elect_one()) mbar_expect(bars + B_XS + 8 * w, arm_bytes);
      while (clk32() - t_red < POLL_DELAY1) {}
      load_red(v, slot);
      bar_arrive<NB_W0, 128>();
    } else {
      WG_WAIT(1);
      bar_arrive<NB_F, 256>();
      sched_fence(head, 100);
      v[3] = opaque32(v[3]);
      const uint32_t tries = finish_red(v, slot);
      forward(std::integral_constant<int, 0>(), v, s, tries);
      TRACE(16);
    }
    WG_WAIT(0);
    reg_fence<16>(acc);
    if (WG == 0) bar_arrive<NB_G, 256>();
    TRACE(15);
    {
      uint32_t pq[8];
#pragma unroll
      for (int j = 0; j < 8; j++) pq[j] = pack2(acc[2 * j], acc[2 * j + 1]);
      if (WG == 1) {
        reg_fence<16>(ao);
#pragma unroll
        for (int j = 0; j < 8; j++) pk[j] = pack2(ao[2 * j], ao[2 * j + 1]);
      }
      if (!isC) {
        const uint32_t q = L4 + w * 256 + R_QK + WG * 5120;
#pragma unroll
        for (int j = 0; j < 8; j++) sts32(q + (j >> 1) * 1024 + (j & 1) * 128, pq[j]);
        if (WG == 1 && !ATT_LATE && s >= 0) store_att(s);
      } else {
        const uint32_t a = LV + warp * 1024;
        stsm4(a, pq); stsm4(a + 256, pq + 4);
      }
    }
    TRACE(17);
    if (WG == 1) {
      auto refill = [&]() {
        bar_sync<NB_F, 256>();
        if (s < NSEG - 2 && elect_one()) load_chunk(sb + R_GA + w * 4096, s + 2, 12 + w, bars + B_FA);
      };
      if (RF_FIRST) refill();
      if (has_wo) { v[3] = opaque32(v[3]); const uint32_t tries = finish_red(v, slot); forward(std::integral_constant<int, 1>(), v, s, tries); }
      if (!RF_FIRST) refill();
      TRACE(16);
    }
    if (isC && V_FENCE) { fence_async_smem(); __syncwarp(); }
    TRACE(18);
  }
  if (WG == 1 && ATT_LATE && !isC) store_att(NSEG - 1);
  if (WG == 1) bar_sync<NB_G, 256>();
  mbar_wait_safe(bars + B_MB + 8, 0); mbar_wait_safe(bars + B_MB + 16, 0); mbar_wait_safe(bars + B_MB + 24, 0);
#undef L16
#undef L8
#undef L4
#undef SLOT
#undef LV
}

__global__ void __cluster_dims__(3, 1, 1) __launch_bounds__(256, 1)
kernel_R(const __grid_constant__ CUtensorMap tmq, const __grid_constant__ CUtensorMap tmk, const __grid_constant__ CUtensorMap tmv,
         const __grid_constant__ CUtensorMap tmo, const __grid_constant__ CUtensorMap tmm, const __nv_bfloat16* __restrict__ x,
         const __nv_bfloat16* __restrict__ mem0, const __nv_bfloat16* __restrict__ cvec, const __grid_constant__ RDesc dsc) {
  extern __shared__ __align__(1024) uint8_t smem[];
  const uint32_t sb = smem_u32(smem);
  uint32_t rank; asm("mov.u32 %0, %%cluster_ctarank;" : "=r"(rank));
  rank = __shfl_sync(0xffffffffu, rank, 0);
  const int cta = blockIdx.x, head = __shfl_sync(0xffffffffu, cta / 3, 0);
  const int tid = threadIdx.x, lane = tid & 31;
  const int warp = __shfl_sync(0xffffffffu, tid >> 5, 0);
  const int wg = warp >> 2, w = warp & 3;
  const uint32_t bars = sb + R_BAR;
  const CUtensorMap* tmw = rank == 2 ? &tmv : (wg == 0 ? &tmq : &tmk);
  const int fcol = head * 128 + (rank == 2 ? wg * 64 : (int)rank * 64);

  asm volatile("griddepcontrol.launch_dependents;");
  uint32_t W[48][4];
  {
    if (sb != (rank << 24) + 0x400) __trap();
    if (tid == 0) {
      sts64(bars + 248, rank, head);
      mbar_init(bars + B_MB, 4); mbar_init(bars + B_MB + 8, 1); mbar_init(bars + B_MB + 16, 1); mbar_init(bars + B_MB + 24, SELF_STAS ? 1 : rank == 2 ? 5 : 4);
      for (int i = B_XS; i <= B_X; i += 8) mbar_init(bars + i, i == B_FA || i == B_FB || (i == B_TS && rank < 2) ? 4 : 1);
      asm volatile("fence.mbarrier_init.release.cluster;" ::: "memory");
      fence_async_smem();
    }
    __syncthreads();
    asm volatile("barrier.cluster.arrive.relaxed.aligned;" ::: "memory");
    TS(0);
    const int nwm = rank == 0 ? 6 : 5, wm0 = rank == 0 ? 0 : 5 * rank + 1, nrg = cta < 64 ? 3 : 2;
    if (elect_one()) {
      if (warp == 0) { mbar_expect(bars + B_WM, nwm * 8192); mbar_expect(bars + B_X, nrg * 16384); }
      if (warp < nwm) tma2d(sb + R_GA + warp * 8192, &tmm, head * 64, (wm0 + warp) * 64, bars + B_WM);
#pragma unroll 1
      for (int r = 0; r < nrg; r++) bulk_g2s(sb + R_TAIL + (r * 8 + warp) * 2064, x + (size_t)((cta + 96 * r) * 8 + warp) * D_, 2048, bars + B_X);
      if (w == 0) mbar_expect(bars + B_STG + wg * 16, 49152);
      if (w < 2) tma2d(sb + R_WO + wg * 49152 + w * 8192, tmw, fcol, rot_chunk(w, rank) * 64, bars + B_STG + wg * 16);
    }
    float* scr = reinterpret_cast<float*>(smem + R_VT);
#pragma unroll 1
    for (int i = tid; i < nwm * 64; i += 256) {
      const float c = __bfloat162float(cvec[wm0 * 64 + i]);
      scr[i] = __bfloat162float(__float2bfloat16(c / (1.f + __expf(-c))));
    }
    if (tid < 128) {
      uint32_t e[4] = {0u, 0u, 0u, 0u};
      if (cta >= 72 && (tid & 32)) {
        const uint16_t* mp = reinterpret_cast<const uint16_t*>(mem0) + 2 * (lane & 3) * D_ + (lane >> 2);
#pragma unroll
        for (int q = 0; q < 3; q++) {
          const int n = 3 * (tid >> 6) + q, col = wo_tile(3 * (cta & 7) + (n >> 1), (cta - 72) >> 3) * 16 + 8 * (n & 1);
          e[q] = mp[col] | (uint32_t)mp[col + D_] << 16;
        }
        e[3] = 0x42000000u;
      }
      reinterpret_cast<uint4*>(g_slot)[cta * 128 + tid] = make_uint4(e[0], e[1], e[2], e[3]);
    }
    __syncthreads();
    TS(1);
    mbar_wait_safe(bars + B_WM, 0);
    if (elect_one()) tma2d(sb + R_WO + wg * 49152 + (2 + w) * 8192, tmw, fcol, rot_chunk(2 + w, rank) * 64, bars + B_STG + wg * 16);
    {
      float a[8];
#pragma unroll
      for (int j = 0; j < 8; j++) a[j] = 0.f;
#pragma unroll 2
      for (int i = 0; i < 2 * nwm; i++) {
        uint32_t u[4];
        lds128(u, sb + R_GA + i * 4096 + tid * 16);
        const float sc = scr[i * 32 + (tid >> 3)];
#pragma unroll
        for (int j = 0; j < 4; j++) { a[2 * j] += sc * bf_lo(u[j]); a[2 * j + 1] += sc * bf_hi(u[j]); }
      }
#pragma unroll
      for (int j = 0; j < 8; j++) { a[j] += __shfl_xor_sync(0xffffffffu, a[j], 8); a[j] += __shfl_xor_sync(0xffffffffu, a[j], 16); }
      if (lane < 8) {
        sts128(sb + R_VT + 1536 + warp * 256 + lane * 32, __float_as_uint(a[0]), __float_as_uint(a[1]), __float_as_uint(a[2]), __float_as_uint(a[3]));
        sts128(sb + R_VT + 1552 + warp * 256 + lane * 32, __float_as_uint(a[4]), __float_as_uint(a[5]), __float_as_uint(a[6]), __float_as_uint(a[7]));
      }
    }
    __syncthreads();
    TS(2);
    if (warp == 7) {
      float t0 = 0.f, t1 = 0.f;
#pragma unroll
      for (int i = 0; i < 8; i++) { float t[2]; lds64f(t, sb + R_VT + 1536 + i * 256 + lane * 8); t0 += t[0]; t1 += t[1]; }
      reinterpret_cast<float2*>(g_modp + rank * 2048 + head * 64)[lane] = make_float2(t0, t1);
      fence_gpu();
      __syncwarp();
      if (lane == 0) red_add_u32(&g_flags[FL_S1], 1);
      __syncwarp();
    }
    mbar_wait_safe(bars + B_X, 0);
#pragma unroll 1
    for (int r = 0; r < nrg; r++) {
      float f[32];
#pragma unroll
      for (int i = 0; i < 4; i++) {
        uint32_t u[4];
        lds128(u, sb + R_TAIL + (r * 8 + warp) * 2064 + i * 512 + lane * 16);
#pragma unroll
        for (int j = 0; j < 4; j++) { f[8 * i + 2 * j] = bf_lo(u[j]); f[8 * i + 2 * j + 1] = bf_hi(u[j]); }
      }
      float t = 0.f;
#pragma unroll
      for (int i = 0; i < 32; i++) t += f[i];
#pragma unroll
      for (int o = 1; o < 32; o <<= 1) t += __shfl_xor_sync(0xffffffffu, t, o);
      const float mean = t * (1.f / D_);
      t = 0.f;
#pragma unroll
      for (int i = 0; i < 32; i++) t = fmaf(f[i] - mean, f[i] - mean, t);
#pragma unroll
      for (int o = 1; o < 32; o <<= 1) t += __shfl_xor_sync(0xffffffffu, t, o);
      const float rstd = rsqrtf(t * (1.f / D_) + 1e-5f);
      if (lane == 0) sts64(sb + R_VT + 3584 + (r * 8 + warp) * 8, __float_as_uint(rstd), __float_as_uint(-mean * rstd));
    }
    TS(3);
    if (w < PF1 && elect_one()) tma2d_prefetch(tmw, fcol, rot_chunk(6 + w, rank) * 64);
    if (tid == 0) wait_flag(&g_flags[FL_S1], 96);
    __syncthreads();
    TS(4);
    {
      float4 p[6];
#pragma unroll
      for (int i = 0; i < 6; i++) p[i] = __ldcg(reinterpret_cast<const float4*>(g_modp + (i >> 1) * 2048) + 2 * tid + (i & 1));
      if (w < PF2 && elect_one()) tma2d_prefetch(tmw, fcol, (9 + w) * 64);
      sts128(sb + R_VT + 5120 + tid * 16, pack2(p[0].x + p[2].x + p[4].x, p[0].y + p[2].y + p[4].y), pack2(p[0].z + p[2].z + p[4].z, p[0].w + p[2].w + p[4].w),
             pack2(p[1].x + p[3].x + p[5].x, p[1].y + p[3].y + p[5].y), pack2(p[1].z + p[3].z + p[5].z, p[1].w + p[3].w + p[5].w));
    }
    __syncthreads();
#pragma unroll 2
    for (int it = 0; it < 4 * nrg; it++) {
      const int r = it >> 2, rg = cta + 96 * r, c = 16 * warp + (lane >> 3) + 4 * (it & 3);
      uint32_t a[4], b[4], u[4], o[4];
      float t[2];
      lds128(u, sb + R_TAIL + (r * 8 + (lane & 7)) * 2064 + c * 16);
      lds128(a, sb + R_VT + 5120 + c * 16); lds128(b, sb + R_VT + 7168 + c * 16);
      lds64f(t, sb + R_VT + 3584 + (r * 8 + (lane & 7)) * 8);
#pragma unroll
      for (int j = 0; j < 4; j++)
        o[j] = pack2(fmaf(fmaf(bf_lo(u[j]), t[0], t[1]), 1.f + bf_lo(b[j]), bf_lo(a[j])), fmaf(fmaf(bf_hi(u[j]), t[0], t[1]), 1.f + bf_hi(b[j]), bf_hi(a[j])));
      *reinterpret_cast<uint4*>(g_h + (size_t)(rg >> 2) * 65536 + (lane & 7) * 16 + (c & 7) * 128 +
                                (c < 96 ? (c >> 3) * 4096 + (rg & 3) * 1024 : 49152 + (rg & 3) * 4096 + ((c >> 3) - 12) * 1024)) =
          make_uint4(o[0], o[1], o[2], o[3]);
    }
    TS(5);
    __syncthreads();
    TS(6);
    if (w < PF3 && elect_one()) tma2d(sb + R_TAIL + warp * 8192, tmw, fcol, 768 + w * 64, bars + B_TAIL);
    if (warp == 3 && lane == 0) { fence_gpu(); red_add_u32(&g_flags[FL_S2], 1); }
    __syncwarp();

    const uint32_t a0 = opaque32(sb + R_WO + wg * 49152 + ((lane >> 4) * 8 + (lane & 7)) * 128 + (((2 * w + ((lane >> 3) & 1)) ^ (lane & 7)) << 4));
    mbar_wait_safe(bars + B_STG + wg * 16, 0);
    TS(7);
#pragma unroll
    for (int i = 0; i < 24; i++) ldsm4t(W[i], a0 + i * 2048);
    if (tid == 0) wait_flag(&g_flags[FL_S2], 96);
    __syncthreads();
    asm volatile("fence.proxy.async.global;" ::: "memory");
    if (elect_one()) {
      if (wg == 0) load_chunk(sb + R_GA + w * 4096, 0, 12 + w, bars + B_FA);
      if (w == 0) mbar_expect(bars + B_STG + wg * 16 + 8, 49152);
#pragma unroll 1
      for (int c = w; c < 6; c += 4) tma2d(sb + R_WO + wg * 49152 + c * 8192, tmw, fcol, rot_chunk(6 + c, rank) * 64, bars + B_STG + wg * 16 + 8);
      if (warp == 0) mbar_expect(bars + B_TAIL, 65536);
      if (w >= PF3) tma2d(sb + R_TAIL + warp * 8192, tmw, fcol, 768 + w * 64, bars + B_TAIL);
      if (wg == 1) mbar_expect(bars + B_XS + 8 * w, w == 2 ? 0 : arm_size(w, rank == 2));
#pragma unroll 1
      for (int i = warp; i < PF4; i += 8) tma2d_prefetch(&tmo, 16 * wo_tile(i, rank), head * 128);
    }
    TS(8);
    mbar_wait_safe(bars + B_STG + wg * 16 + 8, 0);
    TS(9);
#pragma unroll
    for (int i = 0; i < 24; i++) ldsm4t(W[24 + i], a0 + i * 2048);
    __syncthreads();
    if (elect_one()) {
      const int n = rank == 2 ? 22 : 21;
      if (warp == 0) mbar_expect(bars + B_WO, n * 4096);
#pragma unroll 1
      for (int i = warp; i < n; i += 8) tma2d(sb + R_WO + i * 4096, &tmo, 16 * wo_tile(i, rank), head * 128, bars + B_WO);
    }
    sts32(sb + R_P + warp * 768 + 640 + lane * 4, wg == 0 ? 0u : 0xff80ff80u);
    mbar_wait_safe(bars + B_TAIL, 0);
    asm volatile("barrier.cluster.wait.aligned;\nbarrier.cluster.arrive.relaxed.aligned;\nbarrier.cluster.wait.aligned;" ::: "memory");
  }
  uint32_t rh[2];
  lds64(rh, bars + 248);
  rh[0] = __shfl_sync(0xffffffffu, rh[0], 0); rh[1] = __shfl_sync(0xffffffffu, rh[1], 0);
  if (wg == 0) r_main<0>(W, dsc, rh[1], rh[0], lane, w);
  else r_main<1>(W, dsc, rh[1], rh[0], lane, w);
  __syncthreads();
  if (rank < 2 && threadIdx.x == 0) { fence_gpu(); red_add_u32(&g_flags[FL_ATT + 8 * 15], 1); }
  asm volatile("barrier.cluster.arrive.release.aligned;\nbarrier.cluster.wait.acquire.aligned;" ::: "memory");
}

template <int TA> __device__ __forceinline__ void wg_ss256(float* d, uint64_t a, uint64_t b) {
  asm volatile("wgmma.mma_async.sync.aligned.m64n256k16.f32.bf16.bf16 {%0,%1,%2,%3,%4,%5,%6,%7,%8,%9,%10,%11,%12,%13,%14,%15,%16,%17,%18,%19,%20,%21,%22,%23,%24,%25,%26,%27,%28,%29,%30,%31,%32,%33,%34,%35,%36,%37,%38,%39,%40,%41,%42,%43,%44,%45,%46,%47,%48,%49,%50,%51,%52,%53,%54,%55,%56,%57,%58,%59,%60,%61,%62,%63,%64,%65,%66,%67,%68,%69,%70,%71,%72,%73,%74,%75,%76,%77,%78,%79,%80,%81,%82,%83,%84,%85,%86,%87,%88,%89,%90,%91,%92,%93,%94,%95,%96,%97,%98,%99,%100,%101,%102,%103,%104,%105,%106,%107,%108,%109,%110,%111,%112,%113,%114,%115,%116,%117,%118,%119,%120,%121,%122,%123,%124,%125,%126,%127}, %128, %129, 1, 1, 1, %130, 1;"
               : "+f"(d[0]), "+f"(d[1]), "+f"(d[2]), "+f"(d[3]), "+f"(d[4]), "+f"(d[5]), "+f"(d[6]), "+f"(d[7]),
                 "+f"(d[8]), "+f"(d[9]), "+f"(d[10]), "+f"(d[11]), "+f"(d[12]), "+f"(d[13]), "+f"(d[14]), "+f"(d[15]),
                 "+f"(d[16]), "+f"(d[17]), "+f"(d[18]), "+f"(d[19]), "+f"(d[20]), "+f"(d[21]), "+f"(d[22]), "+f"(d[23]),
                 "+f"(d[24]), "+f"(d[25]), "+f"(d[26]), "+f"(d[27]), "+f"(d[28]), "+f"(d[29]), "+f"(d[30]), "+f"(d[31]),
                 "+f"(d[32]), "+f"(d[33]), "+f"(d[34]), "+f"(d[35]), "+f"(d[36]), "+f"(d[37]), "+f"(d[38]), "+f"(d[39]),
                 "+f"(d[40]), "+f"(d[41]), "+f"(d[42]), "+f"(d[43]), "+f"(d[44]), "+f"(d[45]), "+f"(d[46]), "+f"(d[47]),
                 "+f"(d[48]), "+f"(d[49]), "+f"(d[50]), "+f"(d[51]), "+f"(d[52]), "+f"(d[53]), "+f"(d[54]), "+f"(d[55]),
                 "+f"(d[56]), "+f"(d[57]), "+f"(d[58]), "+f"(d[59]), "+f"(d[60]), "+f"(d[61]), "+f"(d[62]), "+f"(d[63]),
                 "+f"(d[64]), "+f"(d[65]), "+f"(d[66]), "+f"(d[67]), "+f"(d[68]), "+f"(d[69]), "+f"(d[70]), "+f"(d[71]),
                 "+f"(d[72]), "+f"(d[73]), "+f"(d[74]), "+f"(d[75]), "+f"(d[76]), "+f"(d[77]), "+f"(d[78]), "+f"(d[79]),
                 "+f"(d[80]), "+f"(d[81]), "+f"(d[82]), "+f"(d[83]), "+f"(d[84]), "+f"(d[85]), "+f"(d[86]), "+f"(d[87]),
                 "+f"(d[88]), "+f"(d[89]), "+f"(d[90]), "+f"(d[91]), "+f"(d[92]), "+f"(d[93]), "+f"(d[94]), "+f"(d[95]),
                 "+f"(d[96]), "+f"(d[97]), "+f"(d[98]), "+f"(d[99]), "+f"(d[100]), "+f"(d[101]), "+f"(d[102]), "+f"(d[103]),
                 "+f"(d[104]), "+f"(d[105]), "+f"(d[106]), "+f"(d[107]), "+f"(d[108]), "+f"(d[109]), "+f"(d[110]), "+f"(d[111]),
                 "+f"(d[112]), "+f"(d[113]), "+f"(d[114]), "+f"(d[115]), "+f"(d[116]), "+f"(d[117]), "+f"(d[118]), "+f"(d[119]),
                 "+f"(d[120]), "+f"(d[121]), "+f"(d[122]), "+f"(d[123]), "+f"(d[124]), "+f"(d[125]), "+f"(d[126]), "+f"(d[127])
               : "l"(a), "l"(b), "n"(TA));
}
template <int TA> __device__ __forceinline__ void wg_ss128(float* d, uint64_t a, uint64_t b) {
  asm volatile("wgmma.mma_async.sync.aligned.m64n128k16.f32.bf16.bf16 {%0,%1,%2,%3,%4,%5,%6,%7,%8,%9,%10,%11,%12,%13,%14,%15,%16,%17,%18,%19,%20,%21,%22,%23,%24,%25,%26,%27,%28,%29,%30,%31,%32,%33,%34,%35,%36,%37,%38,%39,%40,%41,%42,%43,%44,%45,%46,%47,%48,%49,%50,%51,%52,%53,%54,%55,%56,%57,%58,%59,%60,%61,%62,%63}, %64, %65, 1, 1, 1, %66, 1;"
               : "+f"(d[0]), "+f"(d[1]), "+f"(d[2]), "+f"(d[3]), "+f"(d[4]), "+f"(d[5]), "+f"(d[6]), "+f"(d[7]),
                 "+f"(d[8]), "+f"(d[9]), "+f"(d[10]), "+f"(d[11]), "+f"(d[12]), "+f"(d[13]), "+f"(d[14]), "+f"(d[15]),
                 "+f"(d[16]), "+f"(d[17]), "+f"(d[18]), "+f"(d[19]), "+f"(d[20]), "+f"(d[21]), "+f"(d[22]), "+f"(d[23]),
                 "+f"(d[24]), "+f"(d[25]), "+f"(d[26]), "+f"(d[27]), "+f"(d[28]), "+f"(d[29]), "+f"(d[30]), "+f"(d[31]),
                 "+f"(d[32]), "+f"(d[33]), "+f"(d[34]), "+f"(d[35]), "+f"(d[36]), "+f"(d[37]), "+f"(d[38]), "+f"(d[39]),
                 "+f"(d[40]), "+f"(d[41]), "+f"(d[42]), "+f"(d[43]), "+f"(d[44]), "+f"(d[45]), "+f"(d[46]), "+f"(d[47]),
                 "+f"(d[48]), "+f"(d[49]), "+f"(d[50]), "+f"(d[51]), "+f"(d[52]), "+f"(d[53]), "+f"(d[54]), "+f"(d[55]),
                 "+f"(d[56]), "+f"(d[57]), "+f"(d[58]), "+f"(d[59]), "+f"(d[60]), "+f"(d[61]), "+f"(d[62]), "+f"(d[63])
               : "l"(a), "l"(b), "n"(TA));
}
template <int TA> __device__ __forceinline__ void wg_ss64(float* d, uint64_t a, uint64_t b) {
  asm volatile("wgmma.mma_async.sync.aligned.m64n64k16.f32.bf16.bf16 {%0,%1,%2,%3,%4,%5,%6,%7,%8,%9,%10,%11,%12,%13,%14,%15,%16,%17,%18,%19,%20,%21,%22,%23,%24,%25,%26,%27,%28,%29,%30,%31}, %32, %33, 1, 1, 1, %34, 1;"
               : "+f"(d[0]), "+f"(d[1]), "+f"(d[2]), "+f"(d[3]), "+f"(d[4]), "+f"(d[5]), "+f"(d[6]), "+f"(d[7]),
                 "+f"(d[8]), "+f"(d[9]), "+f"(d[10]), "+f"(d[11]), "+f"(d[12]), "+f"(d[13]), "+f"(d[14]), "+f"(d[15]),
                 "+f"(d[16]), "+f"(d[17]), "+f"(d[18]), "+f"(d[19]), "+f"(d[20]), "+f"(d[21]), "+f"(d[22]), "+f"(d[23]),
                 "+f"(d[24]), "+f"(d[25]), "+f"(d[26]), "+f"(d[27]), "+f"(d[28]), "+f"(d[29]), "+f"(d[30]), "+f"(d[31])
               : "l"(a), "l"(b), "n"(TA));
}

constexpr int H_STAGE = 49152, H_NST = 4;
constexpr int H_STG = H_NST * H_STAGE;
constexpr int H_VEC = H_STG + 16384;
constexpr int H_BAR = H_VEC + 6144;
constexpr int H_SMEM = H_BAR + 256;
constexpr int HB_FULL = 0, HB_EMPTY = 32, HB_IFULL = 64, HB_IEMPTY = 80, HB_ITEM = 96, HB_INC = 104;
enum { IT_END = 0, IT_MOD = 1, IT_XT = 2, IT_OUT = 3, IT_UV = 4, IT_F1 = 5, IT_F2 = 6 };
constexpr int MAX_ITEMS = 1400;
struct HList { uint32_t n; uint32_t it[MAX_ITEMS]; };

template <int BN, int TA>
__device__ __forceinline__ void h_mainloop(float* acc, uint32_t sb, int nst, uint32_t& st, uint32_t& ph, int wg, bool leader, bool fixed_a = false) {
  constexpr int KS = BN == 64 ? 8 : 4;
  constexpr uint32_t BOFF = BN == 64 ? 32768 : 16384;
  const uint64_t da0 = fixed_a ? mkdesc(sb + H_STG, 128, 0, 0) : TA ? mkdesc(sb + wg * 1024, 2048, 128, 0) : mkdesc(sb + wg * 8192, 128, 1024, 0);
  const uint64_t db0 = mkdesc(sb + BOFF, 8192, 1024, 1);
  uint32_t prev = 0;
  zero_regs<BN / 2>(acc);
#pragma unroll 1
  for (int i = 0; i < nst; i++) {
    mbar_wait(sb + H_BAR + HB_FULL + st * 8, ph);
    const uint64_t da = da0 + (fixed_a ? i * 64 : st * (H_STAGE >> 4)), db = db0 + st * (H_STAGE >> 4);
    WG_FENCE();
#pragma unroll
    for (int k = 0; k < KS; k++) {
      const uint64_t a = da + (k >> 2) * 1024 + (k & 3) * (TA ? 256 : 16), b = db + k * 128;
      if (BN == 256) wg_ss256<TA>(acc, a, b); else if (BN == 128) wg_ss128<TA>(acc, a, b); else wg_ss64<TA>(acc, a, b);
    }
    WG_COMMIT();
    WG_WAIT(1);
    if (i > 0 && leader) mbar_arrive(sb + H_BAR + HB_EMPTY + prev * 8);
    prev = st;
    if (++st == H_NST) { st = 0; ph ^= 1; }
  }
  WG_WAIT(0);
  reg_fence<BN / 2>(acc);
  if (leader) mbar_arrive(sb + H_BAR + HB_EMPTY + prev * 8);
}

template <int BN, bool FINAL>
__device__ __forceinline__ bool h_residual(uint32_t sb, uint32_t va, int mt, int n0, uint32_t& st, uint32_t& ph, int warp, int lane, __nv_bfloat16* out,
                                           int part = 0, int lgp = 0) {
  const size_t toff = (size_t)(mt * 16 + (n0 >> 6)) * 16384 + warp * 2048 + (lane & 3) * 128 + (lane >> 2) * 16;
  uint4 r[BN / 16];
#pragma unroll
  for (int i = 0; i < BN / 16; i++) r[i] = __ldcg(reinterpret_cast<const uint4*>(g_x1 + toff + (i >> 2) * 16384 + ((i >> 1) & 1) * 512 + (i & 1) * 1024));
  float acc[BN / 2];
  h_mainloop<BN, FINAL ? 0 : 1>(acc, sb, ((FINAL ? 56 : 64) / (BN == 64 ? 2 : 1)) >> lgp, st, ph, warp >> 2, (warp & 3) == 0 && lane == 0);
  if (BN == 64 && lgp > 0) {
    const int tile = (FINAL * 4 + (mt & 3)) * 16 + (n0 >> 6);
    float4* ws = reinterpret_cast<float4*>(g_ws) + (size_t)tile * 8192 + warp * 32 + lane;
#pragma unroll
    for (int i = 0; i < 8; i++) ws[part * 2048 + i * 256] = make_float4(acc[4 * i], acc[4 * i + 1], acc[4 * i + 2], acc[4 * i + 3]);
    bar_sync<1, 256>();
    if (warp == 0 && lane == 0) { fence_gpu(); const uint32_t t = atomicAdd(&g_flags[FL_SPL + tile], 1); fence_gpu(); sts32(sb + H_BAR + HB_INC + 8, t); }
    bar_sync<1, 256>();
    if (lds32(sb + H_BAR + HB_INC + 8) != (1u << lgp) - 1) return false;
#pragma unroll 1
    for (int p = 1; p < (1 << lgp); p++) {
      float4 o[8];
#pragma unroll
      for (int i = 0; i < 8; i++) o[i] = __ldcg(ws + (part ^ p) * 2048 + i * 256);
#pragma unroll
      for (int i = 0; i < 8; i++) { acc[4 * i] += o[i].x; acc[4 * i + 1] += o[i].y; acc[4 * i + 2] += o[i].z; acc[4 * i + 3] += o[i].w; }
    }
  }
  float sm[4] = {0.f, 0.f, 0.f, 0.f};
  const uint32_t stg = sb + H_STG + warp * 2048;
#pragma unroll
  for (int c = 0; c < BN / 32; c++) {
    uint32_t y[2][4] = {{r[2 * c].x, r[2 * c].y, r[2 * c].z, r[2 * c].w}, {r[2 * c + 1].x, r[2 * c + 1].y, r[2 * c + 1].z, r[2 * c + 1].w}}, z[2][4];
#pragma unroll
    for (int j = 0; j < 4; j++) {
      const uint32_t gt = lds32(va + c * 64 + j * 16 + (lane & 3) * 4);
      const uint32_t cb = FINAL ? 0 : lds32(va + 512 + c * 64 + j * 16 + (lane & 3) * 4);
#pragma unroll
      for (int h = 0; h < 2; h++) {
        const float* a = acc + c * 16 + j * 4 + h * 2;
        y[h][j] = pack2(fmaf(bf_lo(gt), a[0], bf_lo(y[h][j])), fmaf(bf_hi(gt), a[1], bf_hi(y[h][j])));
        if (!FINAL) {
          const float p = bf_lo(y[h][j]), q = bf_hi(y[h][j]);
          sm[2 * h] += p + q;
          sm[2 * h + 1] = fmaf(p, p, fmaf(q, q, sm[2 * h + 1]));
          z[h][j] = pack2(fmaf(p, bf_lo(cb), p), fmaf(q, bf_hi(cb), q));
        }
      }
    }
    if (!FINAL) {
#pragma unroll
      for (int h = 0; h < 2; h++) {
        const size_t o = toff + (c >> 1) * 16384 + (c & 1) * 512 + h * 1024;
        *reinterpret_cast<uint4*>(g_x1 + o) = make_uint4(y[h][0], y[h][1], y[h][2], y[h][3]);
        *reinterpret_cast<uint4*>(g_h2 + o) = make_uint4(z[h][0], z[h][1], z[h][2], z[h][3]);
      }
    } else {
#pragma unroll
      for (int h = 0; h < 2; h++) stsm4(stg + (h * 8 + (lane & 7)) * 128 + ((((c & 1) * 4 + (lane >> 3)) ^ (lane & 7)) << 4), y[h]);
      if (c & 1) {
        __syncwarp();
#pragma unroll
        for (int j = 0; j < 4; j++) {
          const int rr = 4 * j + (lane >> 3);
          uint32_t v[4];
          lds128(v, stg + rr * 128 + (((lane & 7) ^ (rr & 7)) << 4));
          *reinterpret_cast<uint4*>(out + (size_t)(mt * 128 + warp * 16 + rr) * D_ + n0 + (c >> 1) * 64 + (lane & 7) * 8) = make_uint4(v[0], v[1], v[2], v[3]);
        }
        __syncwarp();
      }
    }
  }
  if (!FINAL) {
#pragma unroll
    for (int j = 0; j < 4; j++) { sm[j] += __shfl_xor_sync(0xffffffffu, sm[j], 1); sm[j] += __shfl_xor_sync(0xffffffffu, sm[j], 2); }
    const int t = lane & 3;
    atomicAdd(g_stat + (mt * 128 + warp * 16 + (t >> 1) * 8 + (lane >> 2)) * 2 + (t & 1), t == 0 ? sm[0] : t == 1 ? sm[1] : t == 2 ? sm[2] : sm[3]);
  }
  return true;
}

__device__ __forceinline__ float silu_mul(float g, float u) {
  float t; asm("tanh.approx.f32 %0, %1;" : "=f"(t) : "f"(0.5f * g));
  const float h = 0.5f * g * u;
  return fmaf(h, t, h);
}

template <int BN>
__device__ __forceinline__ void h_swiglu(const float* acc, uint32_t va, int mt, int kb0, int warp, int lane) {
  uint8_t* ap = g_act + (size_t)(mt * 56 + kb0) * 16384 + warp * 2048 + (lane & 3) * 128 + (lane >> 2) * 16;
  float rs[2], nm[2];
#pragma unroll
  for (int h = 0; h < 2; h++) {
    float t[2];
    lds64f(t, va + 2048 + (warp * 16 + h * 8 + (lane >> 2)) * 8);
    const float mean = t[0] * (1.f / D_);
    rs[h] = rsqrtf(fmaxf(t[1] * (1.f / D_) - mean * mean, 0.f) + 1e-5f);
    nm[h] = -mean * rs[h];
  }
#pragma unroll
  for (int c = 0; c < BN / 64; c++) {
    uint32_t y[2][4];
#pragma unroll
    for (int j = 0; j < 4; j++) {
      const float* g = acc + 16 * c + 4 * j; const float* u = g + BN / 4;
      float p[4], q[4], o[4];
      lds128f(p, va + (4 * c + j) * 128 + (lane & 3) * 32); lds128f(q, va + (4 * c + j) * 128 + (lane & 3) * 32 + 16);
#pragma unroll
      for (int e = 0; e < 4; e++)
        o[e] = silu_mul(fmaf(rs[e >> 1], g[e], fmaf(nm[e >> 1], p[e & 1], p[2 + (e & 1)])), fmaf(rs[e >> 1], u[e], fmaf(nm[e >> 1], q[e & 1], q[2 + (e & 1)])));
      y[0][j] = pack2(o[0], o[1]); y[1][j] = pack2(o[2], o[3]);
    }
#pragma unroll
    for (int h = 0; h < 2; h++)
      *reinterpret_cast<uint4*>(ap + (c >> 1) * 16384 + (c & 1) * 512 + h * 1024) = make_uint4(y[h][0], y[h][1], y[h][2], y[h][3]);
  }
}

__global__ void __launch_bounds__(384, 1)
kernel_H(const __grid_constant__ CUtensorMap tmo, const __grid_constant__ CUtensorMap tm1, const __grid_constant__ CUtensorMap tm3,
         const __grid_constant__ CUtensorMap tm2, const __grid_constant__ CUtensorMap tmm, const __nv_bfloat16* __restrict__ x,
         const __nv_bfloat16* __restrict__ cvec, __nv_bfloat16* __restrict__ out, const __grid_constant__ HList list) {
  extern __shared__ __align__(1024) uint8_t smem[];
  constexpr uint32_t sb = 0x400, bars = sb + H_BAR;
  const int tid = threadIdx.x, lane = tid & 31;
  const int warp = __shfl_sync(0xffffffffu, tid >> 5, 0);
  if (tid == 0) {
    if (smem_u32(smem) != sb) __trap();
    for (int i = 0; i < H_NST; i++) { mbar_init(bars + HB_FULL + i * 8, 1); mbar_init(bars + HB_EMPTY + i * 8, 2); }
    for (int i = 0; i < 2; i++) { mbar_init(bars + HB_IFULL + i * 8, 1); mbar_init(bars + HB_IEMPTY + i * 8, 1); }
    fence_async_smem();
  }
  __syncthreads();
  if (warp >= 8) {
    asm volatile("setmaxnreg.dec.sync.aligned.u32 40;");
    if (warp == 8) {
      uint32_t st = 0, ph = 1;
#pragma unroll 1
      for (uint32_t n = 0;; n++) {
        uint32_t q = 0;
        if (lane == 0) q = atomicAdd(&g_flags[FL_HEAD], 1);
        q = __shfl_sync(0xffffffffu, q, 0);
        const uint32_t it = q < list.n ? list.it[q] : 0;
        const int type = it & 7, mt = (it >> 3) & 15, idx = (it >> 7) & 63, sz = (it >> 13) & 3, part = (it >> 15) & 3, lgp = (it >> 17) & 3;
        {
          int f = FL_GO; uint32_t target = 0;
          if (type == IT_OUT) { f = lane == 0 ? FL_ATT + 8 * mt : lane == 1 ? FL_XT + 8 * mt : FL_MOD; target = lane == 0 ? 64 : lane == 1 ? 2 : 16; }
          else if (type == IT_F1) { f = lane == 0 ? FL_OUT + 8 * mt : FL_UV; target = lane == 0 ? 16 : 28; }
          else if (type == IT_F2) { f = FL_F1 + 8 * mt; target = 56; }
          else if (type == IT_UV) { f = FL_MOD; target = 16; }
          else if (type != IT_END) target = 1;
          if (lane < 3) wait_flag(&g_flags[f], target);
          __syncwarp();
          asm volatile("fence.proxy.async.global;" ::: "memory");
        }
        mbar_wait(bars + HB_IEMPTY + (n & 1) * 8, ((n >> 1) & 1) ^ 1);
        if (elect_one()) {
          sts32(bars + HB_ITEM + (n & 1) * 4, it | (q << 19));
          mbar_arrive(bars + HB_IFULL + (n & 1) * 8);
        }
        if (type == IT_END) break;
        if (type != IT_XT) {
          const bool ffn1 = type == IT_F1 || type == IT_UV, has_a = type == IT_OUT || type >= IT_F1;
          const uint8_t* ap = type == IT_OUT ? g_att + (size_t)mt * 64 * 16384 : type == IT_F1 ? g_h2 + (size_t)mt * 16 * 16384 : g_act + (size_t)mt * 56 * 16384;
          const int nkb = (type == IT_OUT ? 64 : type == IT_F2 ? 56 : 16) >> lgp;
          const CUtensorMap* tb = type == IT_OUT ? &tmo : ffn1 ? &tm1 : type == IT_F2 ? &tm2 : &tmm;
          const CUtensorMap* tc = ffn1 ? &tm3 : tb;
          const int c0 = ffn1 ? idx * (128 >> sz) : idx * (256 >> sz) + (type == IT_MOD ? 2048 : 0), c2 = ffn1 ? c0 : c0 + 128;
          const CUtensorMap* tb1 = sz == 1 ? tc : tb;
          const uint32_t abytes = has_a ? (sz == 2 ? 32768 : 16384) : 0, bytes = (sz == 0 ? 32768 : 16384) + abytes;
          const uint32_t boff = sz == 2 ? 32768 : 16384;
          const int c1 = sz == 2 || (sz == 1 && ffn1) ? c0 : c0 + 64, dk = sz == 2 ? 1 : 0;
          if (has_a) {
            mbar_wait(bars + HB_EMPTY + st * 8, ph);
            if (elect_one()) {
              const uint32_t v = sb + H_VEC + (n & 1) * 3072, fb = bars + HB_FULL + st * 8;
              const bool f1 = type == IT_F1;
              const uint32_t n0 = (f1 ? 2048 : 512) >> sz, n1 = f1 ? 1024 : n0;
              asm volatile("mbarrier.expect_tx.relaxed.cta.shared::cta.b64 [%0], %1;" :: "r"(fb), "r"(n0 + n1) : "memory");
              bulk_g2s(v, f1 ? (const void*)(g_uv + c0 * 4) : (const void*)(g_mod + (type == IT_OUT ? 2 : 5) * D_ + c0), n0, fb);
              bulk_g2s(v + (f1 ? 2048 : 512), f1 ? (const void*)(g_stat + mt * 256) : (const void*)(g_mod + 4 * D_ + c0), n1, fb);
            }
          }
#pragma unroll 1
          for (int kb = part * nkb; kb < (part + 1) * nkb; kb += 1 + dk) {
            const uint32_t d = sb + st * H_STAGE, fb = bars + HB_FULL + st * 8;
            mbar_wait(bars + HB_EMPTY + st * 8, ph);
            if (elect_one()) {
              mbar_expect(fb, bytes);
              if (has_a) bulk_g2s(d, ap + (size_t)kb * 16384, abytes, fb);
              tma5d(d + boff, tb, c0, kb, fb);
              tma5d(d + boff + 8192, tb1, c1, kb + dk, fb);
              if (sz == 0) { tma5d(d + 32768, tc, c2, kb, fb); tma5d(d + 40960, tc, c2 + 64, kb, fb); }
            }
            if (++st == H_NST) { st = 0; ph ^= 1; }
          }
        }
      }
    } else if (warp == 9) {
#pragma unroll 1
      for (uint32_t n = 0;; n++) {
        mbar_wait(bars + HB_IFULL + (n & 1) * 8, (n >> 1) & 1);
        const uint32_t itq = lds32(bars + HB_ITEM + (n & 1) * 4);
        const int type = itq & 7, mt = (itq >> 3) & 15;
        if (type == IT_END) break;
        if (n & 1) bar_sync<3, 288>(); else bar_sync<2, 288>();
        if (lane == 0) {
          const uint32_t inc = lds32(bars + HB_INC + (n & 1) * 4);
          mbar_arrive(bars + HB_IEMPTY + (n & 1) * 8);
          if (inc) {
            fence_gpu();
            red_add_u32(&g_flags[type == IT_MOD ? FL_MOD : type == IT_UV ? FL_UV : (type == IT_XT ? FL_XT : type == IT_OUT ? FL_OUT : FL_F1) + 8 * mt], inc);
          }
        }
        __syncwarp();
      }
      asm volatile("griddepcontrol.wait;" ::: "memory");
      uint32_t k = 0;
      if (lane == 0) { fence_gpu(); k = atomicAdd(&g_flags[FL_EXIT], 1); }
      k = __shfl_sync(0xffffffffu, k, 0);
      if (k == gridDim.x - 1) {
        fence_gpu();
        for (int i = lane; i < 1024; i += 32) g_flags[i] = 0;
      }
    }
  } else {
    asm volatile("setmaxnreg.inc.sync.aligned.u32 232;");
    const int wg = warp >> 2;
    const bool leader = (tid & 127) == 0;
    uint32_t st = 0, ph = 0;
#pragma unroll 1
    for (uint32_t n = 0;; n++) {
      mbar_wait(bars + HB_IFULL + (n & 1) * 8, (n >> 1) & 1);
      const uint32_t itq = __shfl_sync(0xffffffffu, lds32(bars + HB_ITEM + (n & 1) * 4), 0);
      const int type = itq & 7, mt = (itq >> 3) & 15, idx = (itq >> 7) & 63, sz = (itq >> 13) & 3, part = (itq >> 15) & 3, lgp = (itq >> 17) & 3;
      uint32_t inc = type == IT_OUT ? 4 >> sz : type == IT_F1 ? 2 >> sz : type != IT_F2;
      if (type == IT_END) break;
      const uint32_t va = sb + H_VEC + (n & 1) * 3072;
      if (type == IT_OUT) {
        if (sz == 0) h_residual<256, false>(sb, va, mt, idx * 256, st, ph, warp, lane, out);
        else if (sz == 1) h_residual<128, false>(sb, va, mt, idx * 128, st, ph, warp, lane, out);
        else inc = h_residual<64, false>(sb, va, mt, idx * 64, st, ph, warp, lane, out, part, lgp);
      } else if (type == IT_F2) {
        if (sz == 0) h_residual<256, true>(sb, va, mt, idx * 256, st, ph, warp, lane, out);
        else if (sz == 1) h_residual<128, true>(sb, va, mt, idx * 128, st, ph, warp, lane, out);
        else h_residual<64, true>(sb, va, mt, idx * 64, st, ph, warp, lane, out, part, lgp);
      } else if (type == IT_XT) {
        const int rg = idx * 8 + warp;
        const uint32_t* xp = reinterpret_cast<const uint32_t*>(x + (size_t)(mt * 128 + rg * 8 + (lane >> 2)) * D_) + (lane & 3);
        uint8_t* tp = g_x1 + (size_t)mt * 262144 + rg * 1024 + (lane & 3) * 128 + (lane >> 2) * 16;
        if (lane < 16) g_stat[(mt * 128 + rg * 8) * 2 + lane] = 0.f;
#pragma unroll 1
        for (int b = 0; b < 2; b++) {
          uint32_t v[64];
#pragma unroll
          for (int i = 0; i < 64; i++) v[i] = __ldg(xp + 256 * b + 4 * i);
#pragma unroll
          for (int i = 0; i < 16; i++)
            *reinterpret_cast<uint4*>(tp + (8 * b + (i >> 1)) * 16384 + (i & 1) * 512) = make_uint4(v[4 * i], v[4 * i + 1], v[4 * i + 2], v[4 * i + 3]);
        }
      } else if (sz == 1) {
        float acc[64];
        h_mainloop<128, 0>(acc, sb, 16, st, ph, wg, leader);
        h_swiglu<128>(acc, va, mt, idx, warp, lane);
      } else {
        if (type != IT_F1) {
          bar_sync<1, 256>();
          for (int i = tid; i < D_; i += 256) {
            __nv_bfloat16* p = reinterpret_cast<__nv_bfloat16*>(smem + H_STG + (i >> 5) * 512 + ((i >> 1) & 3) * 128) + ((i >> 3) & 3) * 2 + (i & 1);
            if (type == IT_UV) { p[0] = __float2bfloat16(1.f); p[8] = __ldcg(g_mod + 4 * D_ + i); p[16] = __ldcg(g_mod + 3 * D_ + i); }
            else { const float c = __bfloat162float(cvec[i]); p[0] = __float2bfloat16(c / (1.f + __expf(-c))); }
          }
          fence_async_smem();
          bar_sync<1, 256>();
        }
        float acc[128];
        h_mainloop<256, 0>(acc, sb, 16, st, ph, wg, leader, type != IT_F1);
        if (type == IT_F1) {
          h_swiglu<256>(acc, va, mt, idx * 2, warp, lane);
        } else if (warp == 0) {
#pragma unroll
          for (int j = 0; j < 32; j++) {
            if (type == IT_MOD) {
              if (lane < 4) reinterpret_cast<uint32_t*>(g_mod + 2048 + idx * 256)[j * 4 + lane] = pack2(acc[4 * j], acc[4 * j + 1]);
            } else {
              const float a = acc[4 * j] + __shfl_down_sync(0xffffffffu, acc[4 * j], 4), b = acc[4 * j + 1] + __shfl_down_sync(0xffffffffu, acc[4 * j + 1], 4);
              float2* up = reinterpret_cast<float2*>(g_uv + idx * 512 + ((j & 15) * 4 + (lane & 3)) * 8 + (j >> 4) * 4);
              if (lane < 4) up[0] = make_float2(a, b);
              else if ((lane >> 2) == 2) up[1] = make_float2(acc[4 * j], acc[4 * j + 1]);
            }
          }
        }
      }
      if (tid == 0) sts32(bars + HB_INC + (n & 1) * 4, inc);
      if (n & 1) bar_arrive<3, 288>(); else bar_arrive<2, 288>();
    }
  }
}

#define T_FIRST 35.f
#define T_UV 14.f
#define T_SLACK 2.f
#define T_PERIOD 13.4f
#define G_OUT "1111111111111124"
#define G_F1 "0000000000000001"
#define G_F2 "0000000011112233"
#define F2_LEAD 20.f
void build_list(HList& l) {
  int n = 0;
  auto add = [&](int type, int mt, int idx, int g) {
    const int sz = g > 2 ? 2 : g, lgp = g - sz;
    l.it[n++] = type | mt << 3 | (idx >> lgp) << 7 | sz << 13 | (idx & ((1 << lgp) - 1)) << 15 | lgp << 17;
  };
  for (int i = 0; i < 16; i++) add(IT_MOD, 0, i, 0);
  for (int i = 0; i < 32; i++) add(IT_XT, i >> 1, i & 1, 0);
  for (int i = 0; i < 28; i++) add(IT_UV, 0, i, 0);
  const char* gran[3] = {G_OUT, G_F1, G_F2};
  const float dur[3][5] = {{42.f, 22.f, 13.f, 9.f, 7.f}, {11.2f, 7.f, 0.f, 0.f, 0.f}, {37.f, 21.f, 11.5f, 8.f, 6.f}};
  const float t_end = T_FIRST + 15 * T_PERIOD - 1.5f;
  float fr[132];
  for (int i = 0; i < 132; i++) fr[i] = i < 8 ? T_FIRST : i < 36 ? T_FIRST + T_UV : t_end + 1.2f;
  float rdy[3][16];
  int mt[3] = {0, 0, 0}, ix[3] = {0, 0, 0};
  for (int m = 0; m < 16; m++) { rdy[0][m] = m < 15 ? T_FIRST + m * T_PERIOD : t_end; rdy[1][m] = rdy[2][m] = 0.f; }
  while (mt[2] < 16) {
    int w = 0;
    for (int i = 1; i < 132; i++) if (fr[i] < fr[w]) w = i;
    const float t = fr[w];
    int best = -1;
    float tb = 1e9f;
    const bool f2_first = gran[2][mt[2]] == '0' && t > t_end - F2_LEAD;
    const int order[3] = {0, f2_first ? 2 : 1, f2_first ? 1 : 2};
    for (int k = 0; k < 3; k++) {
      const int q = order[k];
      if (mt[q] >= 16 || (q > 0 && mt[q] >= mt[q - 1])) continue;
      const float ts = rdy[q][mt[q]] > t ? rdy[q][mt[q]] : t;
      if (ts < tb - T_SLACK) { tb = ts; best = q; }
    }
    const int m = mt[best], g = gran[best][m] - '0';
    add(best == 0 ? IT_OUT : best == 1 ? IT_F1 : IT_F2, m, ix[best], g);
    fr[w] = tb + dur[best][g];
    if (best < 2 && fr[w] + 0.5f > rdy[best + 1][m]) rdy[best + 1][m] = fr[w] + 0.5f;
    if (++ix[best] == (best == 1 ? 28 : 4) << g) { ix[best] = 0; mt[best]++; }
  }
  l.n = n;
}

typedef CUresult (*EncodeFn)(CUtensorMap*, CUtensorMapDataType, cuuint32_t, void*, const cuuint64_t*, const cuuint64_t*,
                             const cuuint32_t*, const cuuint32_t*, CUtensorMapInterleave, CUtensorMapSwizzle,
                             CUtensorMapL2promotion, CUtensorMapFloatOOBfill);

void make_map(EncodeFn fn, CUtensorMap* m, const void* p, uint64_t cols, uint64_t rows, uint32_t bc, uint32_t br, CUtensorMapSwizzle sw) {
  cuuint64_t dims[2] = {cols, rows};
  cuuint64_t strides[1] = {cols * 2};
  cuuint32_t box[2] = {bc, br};
  cuuint32_t es[2] = {1, 1};
  fn(m, CU_TENSOR_MAP_DATA_TYPE_BFLOAT16, 2, const_cast<void*>(p), dims, strides, box, es, CU_TENSOR_MAP_INTERLEAVE_NONE, sw,
     CU_TENSOR_MAP_L2_PROMOTION_L2_128B, CU_TENSOR_MAP_FLOAT_OOB_FILL_NONE);
}

void make_map_perm(EncodeFn fn, CUtensorMap* m, const void* p, uint64_t cols, uint64_t rows, bool perm) {
  cuuint64_t dims[5] = {cols, 2, 4, 4, rows / 32};
  cuuint64_t strides[4] = {cols * 2, cols * 2 * (perm ? 8 : 2), cols * 2 * (perm ? 2 : 8), cols * 2 * 32};
  cuuint32_t box[5] = {64, 2, 4, 4, 2};
  cuuint32_t es[5] = {1, 1, 1, 1, 1};
  fn(m, CU_TENSOR_MAP_DATA_TYPE_BFLOAT16, 5, const_cast<void*>(p), dims, strides, box, es, CU_TENSOR_MAP_INTERLEAVE_NONE,
     CU_TENSOR_MAP_SWIZZLE_128B, CU_TENSOR_MAP_L2_PROMOTION_L2_128B, CU_TENSOR_MAP_FLOAT_OOB_FILL_NONE);
}

}

extern "C" void kernel_launch(void* const* d_in, const int* in_sizes, int n_in, void* d_out, int out_size) {
  const __nv_bfloat16* x = (const __nv_bfloat16*)d_in[0];
  const __nv_bfloat16* mem0 = (const __nv_bfloat16*)d_in[1];
  const __nv_bfloat16* cvec = (const __nv_bfloat16*)d_in[11];
  static EncodeFn enc = nullptr;
  if (!enc) {
    cudaDriverEntryPointQueryResult qr;
    void* fp = nullptr;
    cudaGetDriverEntryPoint("cuTensorMapEncodeTiled", &fp, cudaEnableDefault, &qr);
    enc = (EncodeFn)fp;
    cudaFuncSetAttribute(kernel_R, cudaFuncAttributeMaxDynamicSharedMemorySize, R_SMEM);
    cudaFuncSetAttribute(kernel_H, cudaFuncAttributeMaxDynamicSharedMemorySize, H_SMEM);
  }
  CUtensorMap tmq, tmk, tmv, tmo, tmm;
  make_map(enc, &tmm, d_in[12], 6144, 1024, 64, 64, CU_TENSOR_MAP_SWIZZLE_NONE);
  make_map(enc, &tmq, d_in[2], 4096, 1024, 64, 64, CU_TENSOR_MAP_SWIZZLE_128B);
  make_map(enc, &tmk, d_in[3], 4096, 1024, 64, 64, CU_TENSOR_MAP_SWIZZLE_128B);
  make_map(enc, &tmv, d_in[4], 4096, 1024, 64, 64, CU_TENSOR_MAP_SWIZZLE_128B);
  make_map(enc, &tmo, d_in[5], 1024, 4096, 16, 128, CU_TENSOR_MAP_SWIZZLE_32B);
  RDesc dsc;
  for (int k = 0; k < 32; k++) {
    dsc.tok[k] = mkdesc(0x400 + (k < 16 ? R_GA : R_GB) + ((k & 15) >> 2) * 4096 + (k & 3) * 256, 128, 1024, 0);
    dsc.tail_a[k] = mkdesc(0x400 + R_TAIL + k * 2048, 1024, 1024, 1);
    if (k < 16) dsc.tail_b[k] = mkdesc(0x400 + R_GA + k * 256, 128, 4096, 0);
  }
  kernel_R<<<96, 256, R_SMEM, cudaStreamPerThread>>>(tmq, tmk, tmv, tmo, tmm, x, mem0, cvec, dsc);

  CUtensorMap ho, h1, h3, h2, hm;
  make_map_perm(enc, &ho, d_in[5], 1024, 4096, false);
  make_map_perm(enc, &h1, d_in[8], F_, 1024, true);
  make_map_perm(enc, &h3, d_in[9], F_, 1024, true);
  make_map_perm(enc, &h2, d_in[10], 1024, F_, true);
  make_map_perm(enc, &hm, d_in[12], 6144, 1024, true);
  HList list;
  build_list(list);
  cudaLaunchConfig_t cfg = {};
  cfg.gridDim = dim3(132); cfg.blockDim = dim3(384); cfg.dynamicSmemBytes = H_SMEM; cfg.stream = cudaStreamPerThread;
  cudaLaunchAttribute at[1];
  at[0].id = cudaLaunchAttributeProgrammaticStreamSerialization;
  at[0].val.programmaticStreamSerializationAllowed = 1;
  cfg.attrs = at;
  cfg.numAttrs = 1;
  cudaLaunchKernelEx(&cfg, kernel_H, ho, h1, h3, h2, hm, x, cvec, (__nv_bfloat16*)d_out, list);
}
```

```cpp
#include <cuda_runtime.h>
#include <cuda_bf16.h>
#include <cuda.h>
#include <stdint.h>
#include <type_traits>

namespace {

constexpr int S_ = 2048, D_ = 1024, NSEG = 64, F_ = 3584;

__device__ __align__(1024) uint8_t g_h[S_ * D_ * 2];
__device__ __align__(1024) uint8_t g_att[S_ * 4096 * 2];
__device__ __align__(1024) uint8_t g_x1[S_ * D_ * 2];
__device__ __align__(1024) uint8_t g_h2[S_ * D_ * 2];
__device__ __align__(1024) uint8_t g_act[S_ * F_ * 2];
__device__ __align__(1024) float g_ws[2 * 4 * 16 * 4 * 8192];
__device__ __align__(1024) float g_stat[S_ * 2];
__device__ __align__(1024) float g_uv[F_ * 4];
__device__ __align__(1024) float g_slot[4 * 3 * 8 * 4 * 32 * 4];
__device__ __align__(128) __nv_bfloat16 g_mod[6 * D_];
__device__ __align__(128) float g_modp[3 * 2 * D_];
__device__ __align__(128) uint32_t g_flags[1024];
constexpr int FL_S1 = 0, FL_S2 = 32, FL_MOD = 64, FL_HEAD = 96, FL_EXIT = 128, FL_UV = 160, FL_GO = 192, FL_ATT = 256, FL_XT = 384, FL_OUT = 512, FL_F1 = 640, FL_SPL = 768;

__device__ __forceinline__ uint32_t smem_u32(const void* p) { return (uint32_t)__cvta_generic_to_shared(p); }
__device__ __forceinline__ uint32_t mapa(uint32_t a, uint32_t r) { uint32_t o; asm("mapa.shared::cluster.u32 %0, %1, %2;" : "=r"(o) : "r"(a), "r"(r)); return o; }
__device__ __forceinline__ uint32_t pack2(float a, float b) { uint32_t r; asm("cvt.rn.bf16x2.f32 %0, %1, %2;" : "=r"(r) : "f"(b), "f"(a)); return r; }
__device__ __forceinline__ float bf_lo(uint32_t w) { return __uint_as_float(w << 16); }
__device__ __forceinline__ float bf_hi(uint32_t w) { return __uint_as_float(w & 0xffff0000u); }
__device__ __forceinline__ float ex2(float x) { float y; asm("ex2.approx.ftz.f32 %0, %1;" : "=f"(y) : "f"(x)); return y; }
__device__ __forceinline__ float rcp(float x) { float y; asm("rcp.approx.ftz.f32 %0, %1;" : "=f"(y) : "f"(x)); return y; }
__device__ __forceinline__ uint32_t clk32() { uint64_t c; asm volatile("mov.u64 %0, %%clock64;" : "=l"(c) :: "memory"); return (uint32_t)c; }

__device__ __forceinline__ void mbar_init(uint32_t b, uint32_t n) { asm volatile("mbarrier.init.shared::cta.b64 [%0], %1;" :: "r"(b), "r"(n) : "memory"); }
__device__ __forceinline__ void mbar_arrive(uint32_t b) { asm volatile("mbarrier.arrive.shared::cta.b64 _, [%0];" :: "r"(b) : "memory"); }
__device__ __forceinline__ void mbar_expect(uint32_t b, uint32_t n) { asm volatile("mbarrier.arrive.expect_tx.shared::cta.b64 _, [%0], %1;" :: "r"(b), "r"(n) : "memory"); }
__device__ __forceinline__ uint32_t mbar_try(uint32_t b, uint32_t par) {
  uint32_t ok;
  asm volatile("{\n.reg .pred p;\nmbarrier.try_wait.parity.shared::cta.b64 p, [%1], %2;\nselp.u32 %0, 1, 0, p;\n}" : "=r"(ok) : "r"(b), "r"(par) : "memory");
  return ok;
}
__device__ __forceinline__ void mbar_wait(uint32_t b, uint32_t par) {
  asm volatile("{\n.reg .pred p;\n"
               "LOOP:\n"
               "mbarrier.try_wait.parity.shared::cta.b64 p, [%0], %1;\n"
               "@!p bra.uni LOOP;\n}" :: "r"(b), "r"(par) : "memory");
}
__device__ __forceinline__ void mbar_wait_safe(uint32_t b, uint32_t par) {
  uint32_t c = 0;
  while (!mbar_try(b, par)) { if (++c > 4000000u) __trap(); }
}
__device__ __forceinline__ bool elect_one() {
  uint32_t p;
  asm volatile("{\n.reg .pred p;\nelect.sync _|p, 0xffffffff;\nselp.u32 %0, 1, 0, p;\n}" : "=r"(p));
  return p;
}
__device__ __forceinline__ void sched_fence(uint32_t x, uint32_t y) { asm volatile("{\n.reg .pred p;\nsetp.eq.u32 p, %0, %1;\n@p trap;\n}" :: "r"(x), "r"(y) : "memory"); }
template <class T> __device__ __forceinline__ T opaque32(T x) { asm volatile("" : "+r"(x)); return x; }
template <class T> __device__ __forceinline__ T opaque64(T x) { asm volatile("" : "+l"(x)); return x; }
template <int ID, int N> __device__ __forceinline__ void bar_sync() { asm volatile("bar.sync %0, %1;" :: "n"(ID), "n"(N) : "memory"); }
template <int ID, int N> __device__ __forceinline__ void bar_arrive() { asm volatile("bar.arrive %0, %1;" :: "n"(ID), "n"(N) : "memory"); }
__device__ __forceinline__ void fence_async_smem() { asm volatile("fence.proxy.async.shared::cta;" ::: "memory"); }
__device__ __forceinline__ void fence_async_all() { asm volatile("fence.proxy.async;" ::: "memory"); }
__device__ __forceinline__ void fence_gpu() { asm volatile("fence.acq_rel.gpu;" ::: "memory"); }
__device__ __forceinline__ void red_add_u32(uint32_t* p, uint32_t v) { asm volatile("red.relaxed.gpu.global.add.u32 [%0], %1;" :: "l"(p), "r"(v) : "memory"); }
__device__ __forceinline__ uint32_t ld_acquire(const uint32_t* p) { uint32_t v; asm volatile("ld.acquire.gpu.global.u32 %0, [%1];" : "=r"(v) : "l"(p) : "memory"); return v; }
__device__ __forceinline__ void wait_flag(const uint32_t* p, uint32_t target) {
  uint32_t c = 0;
  while (ld_acquire(p) < target) { if (++c > 20000000u) __trap(); __nanosleep(20); }
}

__device__ __forceinline__ void tma2d(uint32_t dst, const CUtensorMap* m, int c0, int c1, uint32_t bar) {
  asm volatile("cp.async.bulk.tensor.2d.shared::cluster.global.mbarrier::complete_tx::bytes [%0], [%1, {%3, %4}], [%2];"
               :: "r"(dst), "l"(m), "r"(bar), "r"(c0), "r"(c1) : "memory");
}
__device__ __forceinline__ void tma5d(uint32_t dst, const CUtensorMap* m, int n0, int kb, uint32_t bar) {
  asm volatile("cp.async.bulk.tensor.5d.shared::cluster.global.mbarrier::complete_tx::bytes [%0], [%1, {%3, %5, %5, %5, %4}], [%2];"
               :: "r"(dst), "l"(m), "r"(bar), "r"(n0), "r"(2 * kb), "r"(0) : "memory");
}
__device__ __forceinline__ void tma2d_prefetch(const CUtensorMap* m, int c0, int c1) {
  asm volatile("cp.async.bulk.prefetch.tensor.2d.L2.global [%0, {%1, %2}];" :: "l"(m), "r"(c0), "r"(c1) : "memory");
}
__device__ __forceinline__ void bulk_g2s(uint32_t dst, const void* src, uint32_t bytes, uint32_t bar) {
  asm volatile("cp.async.bulk.shared::cluster.global.mbarrier::complete_tx::bytes [%0], [%1], %2, [%3];"
               :: "r"(dst), "l"(src), "r"(bytes), "r"(bar) : "memory");
}
__device__ __forceinline__ void bulk_s2s(uint32_t dst, uint32_t src, uint32_t bytes, uint32_t bar) {
  asm volatile("cp.async.bulk.shared::cluster.shared::cta.mbarrier::complete_tx::bytes [%0], [%1], %2, [%3];"
               :: "r"(dst), "r"(src), "r"(bytes), "r"(bar) : "memory");
}
__device__ __forceinline__ void st_async1(uint32_t dst, uint32_t a, uint32_t bar) {
  asm volatile("st.async.shared::cluster.mbarrier::complete_tx::bytes.b32 [%0], %1, [%2];" :: "r"(dst), "r"(a), "r"(bar) : "memory");
}
__device__ __forceinline__ void st_async2(uint32_t dst, uint32_t a, uint32_t b, uint32_t bar) {
  asm volatile("st.async.shared::cluster.mbarrier::complete_tx::bytes.v2.b32 [%0], {%1, %2}, [%3];" :: "r"(dst), "r"(a), "r"(b), "r"(bar) : "memory");
}
__device__ __forceinline__ void st_async4(uint32_t dst, const uint32_t* r, uint32_t bar) {
  asm volatile("st.async.shared::cluster.mbarrier::complete_tx::bytes.v4.b32 [%0], {%1, %2, %3, %4}, [%5];"
               :: "r"(dst), "r"(r[0]), "r"(r[1]), "r"(r[2]), "r"(r[3]), "r"(bar) : "memory");
}
__device__ __forceinline__ void sts32(uint32_t a, uint32_t v) { asm volatile("st.shared.b32 [%0], %1;" :: "r"(a), "r"(v) : "memory"); }
__device__ __forceinline__ void sts64(uint32_t a, uint32_t x, uint32_t y) { asm volatile("st.shared.v2.b32 [%0], {%1, %2};" :: "r"(a), "r"(x), "r"(y) : "memory"); }
__device__ __forceinline__ void sts128(uint32_t a, uint32_t x, uint32_t y, uint32_t z, uint32_t w) {
  asm volatile("st.shared.v4.b32 [%0], {%1, %2, %3, %4};" :: "r"(a), "r"(x), "r"(y), "r"(z), "r"(w) : "memory");
}
__device__ __forceinline__ void lds128(uint32_t* r, uint32_t a) {
  asm volatile("ld.shared.v4.b32 {%0, %1, %2, %3}, [%4];" : "=r"(r[0]), "=r"(r[1]), "=r"(r[2]), "=r"(r[3]) : "r"(a) : "memory");
}
__device__ __forceinline__ uint32_t lds32(uint32_t a) { uint32_t r; asm volatile("ld.shared.b32 %0, [%1];" : "=r"(r) : "r"(a) : "memory"); return r; }
__device__ __forceinline__ void lds64(uint32_t* r, uint32_t a) {
  asm volatile("ld.shared.v2.b32 {%0, %1}, [%2];" : "=r"(r[0]), "=r"(r[1]) : "r"(a) : "memory");
}
__device__ __forceinline__ void lds128f(float* r, uint32_t a) {
  asm volatile("ld.shared.v4.f32 {%0, %1, %2, %3}, [%4];" : "=f"(r[0]), "=f"(r[1]), "=f"(r[2]), "=f"(r[3]) : "r"(a) : "memory");
}
__device__ __forceinline__ void lds64f(float* r, uint32_t a) {
  asm volatile("ld.shared.v2.f32 {%0, %1}, [%2];" : "=f"(r[0]), "=f"(r[1]) : "r"(a) : "memory");
}
__device__ __forceinline__ void ldsm4(uint32_t* r, uint32_t a) {
  asm volatile("ldmatrix.sync.aligned.m8n8.x4.shared.b16 {%0, %1, %2, %3}, [%4];" : "=r"(r[0]), "=r"(r[1]), "=r"(r[2]), "=r"(r[3]) : "r"(a) : "memory");
}
__device__ __forceinline__ void ldsm4t(uint32_t* r, uint32_t a) {
  asm volatile("ldmatrix.sync.aligned.m8n8.x4.trans.shared.b16 {%0, %1, %2, %3}, [%4];" : "=r"(r[0]), "=r"(r[1]), "=r"(r[2]), "=r"(r[3]) : "r"(a) : "memory");
}
__device__ __forceinline__ void ldsm2(uint32_t* r, uint32_t a) {
  asm volatile("ldmatrix.sync.aligned.m8n8.x2.shared.b16 {%0, %1}, [%2];" : "=r"(r[0]), "=r"(r[1]) : "r"(a) : "memory");
}
__device__ __forceinline__ void stsm4(uint32_t a, const uint32_t* r) {
  asm volatile("stmatrix.sync.aligned.m8n8.x4.shared.b16 [%0], {%1, %2, %3, %4};" :: "r"(a), "r"(r[0]), "r"(r[1]), "r"(r[2]), "r"(r[3]) : "memory");
}
__device__ __forceinline__ uint32_t hadd2(uint32_t a, uint32_t b) { uint32_t t; asm("add.rn.bf16x2 %0, %1, %2;" : "=r"(t) : "r"(a), "r"(b)); return t; }
__device__ __forceinline__ uint32_t hmax2(uint32_t a, uint32_t b) { uint32_t t; asm("max.bf16x2 %0, %1, %2;" : "=r"(t) : "r"(a), "r"(b)); return t; }
__device__ __forceinline__ void ldsm2t(uint32_t* r, uint32_t a) {
  asm volatile("ldmatrix.sync.aligned.m8n8.x2.trans.shared.b16 {%0, %1}, [%2];" : "=r"(r[0]), "=r"(r[1]) : "r"(a) : "memory");
}
__device__ __forceinline__ uint32_t movm(uint32_t x) { uint32_t y; asm volatile("movmatrix.sync.aligned.m8n8.trans.b16 %0, %1;" : "=r"(y) : "r"(x)); return y; }
__device__ __forceinline__ void hmma(float* d, uint32_t a0, uint32_t a1, uint32_t a2, uint32_t a3, uint32_t b0, uint32_t b1) {
  asm volatile("mma.sync.aligned.m16n8k16.row.col.f32.bf16.bf16.f32 {%0,%1,%2,%3}, {%4,%5,%6,%7}, {%8,%9}, {%0,%1,%2,%3};"
               : "+f"(d[0]), "+f"(d[1]), "+f"(d[2]), "+f"(d[3]) : "r"(a0), "r"(a1), "r"(a2), "r"(a3), "r"(b0), "r"(b1));
}
__device__ __forceinline__ void hmma0(float* d, uint32_t a0, uint32_t a1, uint32_t a2, uint32_t a3, uint32_t b0, uint32_t b1) {
  asm volatile("mma.sync.aligned.m16n8k16.row.col.f32.bf16.bf16.f32 {%0,%1,%2,%3}, {%4,%5,%6,%7}, {%8,%9}, {%10,%10,%10,%10};"
               : "=f"(d[0]), "=f"(d[1]), "=f"(d[2]), "=f"(d[3]) : "r"(a0), "r"(a1), "r"(a2), "r"(a3), "r"(b0), "r"(b1), "f"(0.f));
}
__device__ __forceinline__ void hmma_k8(float* d, uint32_t a0, uint32_t a1, uint32_t b0) {
  asm volatile("mma.sync.aligned.m16n8k8.row.col.f32.bf16.bf16.f32 {%0,%1,%2,%3}, {%4,%5}, {%6}, {%0,%1,%2,%3};"
               : "+f"(d[0]), "+f"(d[1]), "+f"(d[2]), "+f"(d[3]) : "r"(a0), "r"(a1), "r"(b0));
}
__host__ __device__ constexpr uint64_t mkdesc(uint32_t addr, uint32_t lbo, uint32_t sbo, uint32_t sw) {
  return (uint64_t)((addr & 0x3FFFF) >> 4) | ((uint64_t)(lbo >> 4) << 16) | ((uint64_t)(sbo >> 4) << 32) | ((uint64_t)sw << 62);
}
#define WG_FENCE() asm volatile("wgmma.fence.sync.aligned;" ::: "memory")
#define WG_COMMIT() asm volatile("wgmma.commit_group.sync.aligned;" ::: "memory")
#define WG_WAIT(n) asm volatile("wgmma.wait_group.sync.aligned " #n ";" ::: "memory")
template <int N> __device__ __forceinline__ void reg_fence(float* d) {
#pragma unroll
  for (int i = 0; i < N; i++) asm volatile("" : "+f"(d[i]) :: "memory");
}
template <int N> __device__ __forceinline__ void zero_regs(float* d) {
#pragma unroll
  for (int i = 0; i < N; i++) asm volatile("mov.b32 %0, 0;" : "=f"(d[i]));
}
template <int SD>
__device__ __forceinline__ void wg_rs32(float* d, uint32_t a0, uint32_t a1, uint32_t a2, uint32_t a3, uint64_t b) {
  asm volatile("wgmma.mma_async.sync.aligned.m64n32k16.f32.bf16.bf16 {%0,%1,%2,%3,%4,%5,%6,%7,%8,%9,%10,%11,%12,%13,%14,%15}, {%16,%17,%18,%19}, %20, %21, 1, 1, 0;"
               : "+f"(d[0]), "+f"(d[1]), "+f"(d[2]), "+f"(d[3]), "+f"(d[4]), "+f"(d[5]), "+f"(d[6]), "+f"(d[7]),
                 "+f"(d[8]), "+f"(d[9]), "+f"(d[10]), "+f"(d[11]), "+f"(d[12]), "+f"(d[13]), "+f"(d[14]), "+f"(d[15])
               : "r"(a0), "r"(a1), "r"(a2), "r"(a3), "l"(b), "n"(SD));
}
template <int TB>
__device__ __forceinline__ void wg_ss40(float* d, uint64_t a, uint64_t b) {
  asm volatile("wgmma.mma_async.sync.aligned.m64n40k16.f32.bf16.bf16 {%0,%1,%2,%3,%4,%5,%6,%7,%8,%9,%10,%11,%12,%13,%14,%15,%16,%17,%18,%19}, %20, %21, 1, 1, 1, 1, %22;"
               : "+f"(d[0]), "+f"(d[1]), "+f"(d[2]), "+f"(d[3]), "+f"(d[4]), "+f"(d[5]), "+f"(d[6]), "+f"(d[7]),
                 "+f"(d[8]), "+f"(d[9]), "+f"(d[10]), "+f"(d[11]), "+f"(d[12]), "+f"(d[13]), "+f"(d[14]), "+f"(d[15]),
                 "+f"(d[16]), "+f"(d[17]), "+f"(d[18]), "+f"(d[19])
               : "l"(a), "l"(b), "n"(TB));
}
template <int T>
__device__ __forceinline__ void wg_ss32(float* d, uint64_t a, uint64_t b) {
  asm volatile("wgmma.mma_async.sync.aligned.m64n32k16.f32.bf16.bf16 {%0,%1,%2,%3,%4,%5,%6,%7,%8,%9,%10,%11,%12,%13,%14,%15}, %16, %17, 1, 1, 1, %18, %18;"
               : "+f"(d[0]), "+f"(d[1]), "+f"(d[2]), "+f"(d[3]), "+f"(d[4]), "+f"(d[5]), "+f"(d[6]), "+f"(d[7]),
                 "+f"(d[8]), "+f"(d[9]), "+f"(d[10]), "+f"(d[11]), "+f"(d[12]), "+f"(d[13]), "+f"(d[14]), "+f"(d[15])
               : "l"(a), "l"(b), "n"(T));
}

constexpr int R_TAIL = 0;
constexpr int R_WO = 65536;
constexpr int R_QK = R_WO + 86016;
constexpr int R_P = R_QK + 10240;
constexpr int R_GA = R_P + 6400;
constexpr int R_M2 = R_GA + 16384;
constexpr int R_M1 = R_M2 + 7168;
constexpr int R_GB = R_M1 + 9216;
constexpr int R_VT = R_GB + 16384;
constexpr int R_VM = R_VT + 8192;
constexpr int R_XS = R_VM + 2048;
constexpr int R_OX = R_XS + 1280;
constexpr int R_BAR = R_OX + 2048;
constexpr int R_TRC = R_BAR + 256;
constexpr int R_SMEM = R_TRC + 1024;
constexpr int B_MB = 0, B_XS = 32, B_VM = 40, B_VT = 48, B_TS = 56, B_FA = 64, B_FB = 72, B_TAIL = 80, B_WO = 88, B_STG = 96, B_WM = 128, B_X = 136;
constexpr int NB_A = 1, NB_B = 2, NB_X = 3, NB_C = 4, NB_D = 5, NB_E = 6, NB_F = 7, NB_G = 8, NB_H = 9, NB_S = 10, NB_E2 = 11, NB_P = 12, NB_W0 = 13;

#define POLL_DELAY 750
#define POLL_DELAY1 700
#define POLL_STAG 150
#define POLL_K0 20
#define PF1 2
#define PF2 2
#define PF3 2
#define PF4 0
#define RF_FIRST 1
#define BX_I 5
#define NCH 4
#define TOP2 0
#define CX_I 13
#define ATT_LATE 0
#define V_FENCE 1
#define SELF_STAS 1
#define Q_FENCE 1
#define ND_K 3
#define TRACE(i)
#define TS(i)

__device__ __forceinline__ int rot_chunk(int c, int rank) {
  int G = c;
  if (c < 9) { G = c + 3 * rank; if (G >= 9) G -= 9; }
  return G;
}
__device__ __forceinline__ int wo_tile(int i, int rank) {
  if (i < 12) return 12 * rank + i;
  const int r = i - 12 + 9 * rank;
  return r < 16 ? 48 + r : 20 + r;
}
__device__ __forceinline__ void load_chunk(uint32_t dst, int seg, int G, uint32_t bar) {
  mbar_expect(bar, 4096);
  bulk_g2s(dst, g_h + (size_t)(seg * 16 + G) * 4096, 4096, bar);
}
__device__ __forceinline__ void load_red(uint32_t* v, const float* p) {
#pragma unroll
  for (int j = 0; j < 2; j++)
    asm volatile("ld.relaxed.gpu.global.v4.u32 {%0, %1, %2, %3}, [%4];"
                 : "=r"(v[4 * j]), "=r"(v[4 * j + 1]), "=r"(v[4 * j + 2]), "=r"(v[4 * j + 3]) : "l"(p + j * 256) : "memory");
}
__device__ __forceinline__ bool red_done(const uint32_t* v) { return __all_sync(0xffffffffu, (v[3] & v[7]) == 0x42000000u); }
__device__ __forceinline__ uint32_t finish_red(uint32_t* v, const float* p) {
  uint32_t tries = 0;
  if (__builtin_expect(!red_done(v), 0)) {
    do { if (++tries > 20000000u) __trap(); load_red(v, p); } while (!red_done(v));
  }
  return tries;
}
__device__ __forceinline__ void exp10(float* sv, const uint32_t* x) {
  constexpr float SC = 0.08838834764831845f * 1.4426950408889634f;
  uint32_t m2 = hmax2(hmax2(hmax2(x[0], x[1]), hmax2(x[2], x[3])), x[4]);
  m2 = hmax2(m2, __shfl_xor_sync(0xffffffffu, m2, 1));
  m2 = hmax2(m2, __shfl_xor_sync(0xffffffffu, m2, 2));
  const float nm = -fmaxf(bf_lo(m2), bf_hi(m2)) * SC;
#pragma unroll
  for (int j = 0; j < 5; j++) { sv[2 * j] = ex2(fmaf(bf_lo(x[j]), SC, nm)); sv[2 * j + 1] = ex2(fmaf(bf_hi(x[j]), SC, nm)); }
}

__device__ __forceinline__ uint32_t arm_size(int w, bool isC) {
  return w == 0 ? (isC ? 1280 : 640) : w == 1 ? (isC ? 0 : 2048) : w == 2 ? (isC ? 0 : 8192) : (isC ? 0 : 1792);
}
struct RDesc { uint64_t tok[32], tail_b[16], tail_a[32]; };

template <int WG>
__device__ __forceinline__ void r_main(const uint32_t (&W)[48][4], const RDesc& dsc, int head, uint32_t rank, int lane_, int w) {
  const uint32_t sb = (rank << 24) + 0x400, bars = sb + R_BAR;
  const uint32_t to1 = rank == 0 ? 2u << 24 : 0u - (1u << 24), to2 = rank == 2 ? 0u - (2u << 24) : 1u << 24;
  const bool isC = rank == 2;
  const int lane = opaque32(lane_), warp = WG * 4 + w;
  const int gl = rot_chunk(4 * (lane & 3) + w, rank);
  const int g0 = __shfl_sync(0xffffffffu, gl, 0), g1 = __shfl_sync(0xffffffffu, gl, 1), g2 = __shfl_sync(0xffffffffu, gl, 2);
  const uint32_t arm_bytes = arm_size(w, isC);

#define L16 opaque32(sb + opaque32(lane) * 16)
#define L8 opaque32(sb + opaque32(lane) * 8)
#define L4 opaque32(sb + opaque32(lane) * 4)
#define LV opaque32(sb + R_VT + ((opaque32(lane) >> 3) & 1) * 512 + (opaque32(lane) >> 4) * 128 + (opaque32(lane) & 7) * 16)
#define SLOT(st) opaque64(slot0 + ((st) & 3) * 12288 + ((st) & 4) * 32)
  float* const slot0 = opaque64(g_slot + (rank * 1024 + warp * 128 + lane) * 4);
  const uint32_t woa = opaque32(sb + R_WO + warp * 12288 + ((lane >> 4) * 8 + (lane & 7)) * 32 + ((((lane >> 3) ^ (lane >> 2)) & 1) << 4));
  const bool has_wo = WG == 0 || isC || w < 3;
  float acc[20];
  uint32_t pk[8] = {0u, 0u, 0u, 0u, 0u, 0u, 0u, 0u};

  auto forward = [&](auto rd, const uint32_t* v, int st, uint32_t tries) {
    constexpr int RD = decltype(rd)::value;
    uint32_t u[6];
#pragma unroll
    for (int j = 0; j < 6; j++) u[j] = movm(v[4 * (j / 3) + j % 3]);
    const bool all3 = RD == 0 || w < 3;
    if (RD == 0) {
      const uint32_t a = L16 + R_M1 + w * 768, a2 = L8 + R_M1 + 512 + w * 768;
      st_async4(a + to1 + 3072, u, bars + to1 + B_MB + 8); st_async2(a2 + to1 + 3072, u[4], u[5], bars + to1 + B_MB + 8);
      sts128(a, u[0], u[1], u[2], u[3]); sts64(a2, u[4], u[5]);
      __syncwarp();
      if (elect_one()) mbar_arrive(bars + B_MB);
      st_async4(a + to2 + 6144, u, bars + to2 + B_MB + 16); st_async2(a2 + to2 + 6144, u[4], u[5], bars + to2 + B_MB + 16);
    } else {
      const uint32_t a = L4 + R_M2 + rank * 2304 + w * 768;
#pragma unroll
      for (int j = 0; j < 6; j++) if (j < 2 || all3) st_async1(a + to1 + j * 128, u[j], bars + to1 + B_MB + 24);
#pragma unroll
      for (int j = 0; j < 6; j++) if (j < 2 || all3) st_async1(a + to2 + j * 128, u[j], bars + to2 + B_MB + 24);
      if (SELF_STAS) {
#pragma unroll
        for (int j = 0; j < 6; j++) if (j < 2 || all3) st_async1(a + j * 128, u[j], bars + B_MB + 24);
      } else {
#pragma unroll
        for (int j = 0; j < 6; j++) if (j < 2 || all3) sts32(a + j * 128, u[j]);
        __syncwarp();
        if (elect_one()) mbar_arrive(bars + B_MB + 24);
      }
    }
  };

  auto send_vt = [&]() {
    if (elect_one()) {
      const uint32_t src = sb + R_VT + warp * 1024;
      bulk_s2s(src + to1, src, 1024, bars + to1 + B_VT);
      bulk_s2s(src + to2, src, 1024, bars + to2 + B_VT);
    }
  };
  auto store_att = [&](int sg) {
    uint32_t* op = reinterpret_cast<uint32_t*>(g_att + (size_t)((sg >> 2) * 64 + head * 2 + rank) * 16384 + (2 * w * 16 + (sg & 3) * 4) * 128) + opaque32(lane);
#pragma unroll
    for (int j = 0; j < 8; j++) op[(j & 1) * 512 + (j >> 1) * 32] = pk[j];
  };

  if (WG == 0) bar_arrive<NB_G, 256>();
#pragma unroll 1
  for (int s = -1; s < NSEG; s++) {
    const uint32_t par = (s + 1) & 1;
    const uint32_t last = s == NSEG - 1;
    TRACE(0);
    {
      float c[NCH][4];
      uint32_t b[3][6];
      const uint32_t ma = L16, m8 = L8;
#pragma unroll
      for (int i = 0; i < 18; i++) {
        if (i < 16) {
          if (i % 4 == 0 && !(i == 4 && TOP2)) mbar_wait(bars + B_MB + (i / 4) * 8, par ^ 1);
          if (i == 0 && TOP2) mbar_wait(bars + B_MB + 8, par ^ 1);
          if (i % 4 == 0) TRACE(1 + i / 4);
          if (i < 12) { lds128(b[i % 3], ma + R_M1 + i * 768); lds64(b[i % 3] + 4, m8 + R_M1 + 512 + i * 768); }
          else { ldsm4(b[i % 3], ma + R_M2 + 4096 + (i - 12) * 768); ldsm2(b[i % 3] + 4, ma + R_M2 + 4096 + 512 + (i - 12) * 768); }
          if (WG == 1 && i == BX_I) {
            bar_sync<NB_G, 256>();
            if (!last && elect_one()) load_chunk(sb + R_GB + w * 4096, s + 1, g0, bars + B_FB);
          }
          if (i == CX_I) {
            if (isC && s >= 0) send_vt();
            if (WG == 1 && ATT_LATE && !isC && s > 0) store_att(s - 1);
          }
          __syncwarp();
        }
        if (i >= 2) {
          const int j = i - 2;
#pragma unroll
          for (int q = 0; q < 3; q++) {
            const uint32_t* f = W[3 * j + q];
            if (3 * j + q < NCH) hmma0(c[3 * j + q], f[0], f[1], f[2], f[3], b[j % 3][2 * q], b[j % 3][2 * q + 1]);
            else hmma(c[(3 * j + q) % NCH], f[0], f[1], f[2], f[3], b[j % 3][2 * q], b[j % 3][2 * q + 1]);
          }
        }
        if (i == 14) zero_regs<16>(acc);
        if (i == 16) mbar_wait(bars + B_FA, last);
      }
#pragma unroll
      for (int j = 0; j < 4; j++) acc[16 + j] = NCH == 3 ? (c[0][j] + c[1][j]) + c[2][j] : (c[0][j] + c[1][j]) + (c[2][j] + c[NCH - 1][j]);
    }
    TRACE(5);
    bar_sync<NB_H, 256>();
    WG_FENCE();
#pragma unroll
    for (int k = 0; k < 16; k++) wg_ss40<0>(acc, dsc.tail_a[WG * 16 + k], dsc.tail_b[k]);
    WG_COMMIT();
    uint32_t vt[4][4];
    {
      const uint32_t a = opaque32(L4 + w * 256 + (isC ? WG * 1024 + R_VM : R_QK + 4096 + WG * 5120));
      const uint32_t qa = L16 + R_QK, xa = opaque32(LV + w * 2048 + (WG == 0 ? 0 : (opaque32(lane) & 8) * 64 + R_QK + 5120 - R_VT));
      const uint32_t d = opaque32(L4 + R_XS + rank * 640 + w * 256);
      if (s == 0) {
        mbar_wait_safe(bars + B_WO, 0);
        TS(10);
        if (WG == 1 && head == 0 && rank == 0 && w == 0 && elect_one()) red_add_u32(&g_flags[FL_GO], 1);
      }
      mbar_wait(bars + B_FB, last);
      if (WG == 0) mbar_wait(bars + B_VT, par);
      WG_WAIT(0);
      reg_fence<20>(acc);
      TRACE(6);
      const uint32_t p0 = pack2(acc[16], acc[17]), p1 = pack2(acc[18], acc[19]);
      sts32(a, p0); sts32(a + 128, p1);
      if (isC) {
        st_async1(a + to1, p0, bars + B_VM + to1); st_async1(a + to1 + 128, p1, bars + B_VM + to1);
        st_async1(a + to2, p0, bars + B_VM + to2); st_async1(a + to2 + 128, p1, bars + B_VM + to2);
      }
      if (WG == 0) {
        bar_arrive<NB_A, 256>();
        if (Q_FENCE && !isC) fence_async_smem();
#pragma unroll
        for (int i = 0; i < 4; i++) ldsm4(vt[i], xa + (i >> 1) * 1024 + (i & 1) * 256);
        bar_sync<NB_S, 256>();
      } else {
        bar_sync<NB_A, 256>();
        if (!isC) {
          if (w < 3) {
            uint32_t q[8], k[4][4];
            ldsm4t(q, qa + 4096); ldsm4t(k[0], xa); ldsm4t(k[1], xa + 256);
            ldsm4t(q + 4, qa + 4096 + 512); ldsm4t(k[2], xa + 512); ldsm4t(k[3], xa + 768);
            float x[4], y[4];
            hmma0(x, k[0][0], k[0][1], k[0][2], k[0][3], q[0], q[1]); hmma0(y, k[1][0], k[1][1], k[1][2], k[1][3], q[2], q[3]);
            hmma(x, k[2][0], k[2][1], k[2][2], k[2][3], q[4], q[5]); hmma(y, k[3][0], k[3][1], k[3][2], k[3][3], q[6], q[7]);
            const uint32_t s0 = pack2(x[0] + y[0], x[1] + y[1]), s1 = pack2(x[2] + y[2], x[3] + y[3]);
            st_async1(d + to1, s0, bars + B_XS + to1);
            st_async1(d + to2, s0, bars + B_XS + to2);
            if (w < 2) { st_async1(d + to1 + 128, s1, bars + B_XS + to1); st_async1(d + to2 + 128, s1, bars + B_XS + to2); sts32(d + 128, s1); }
            sts32(d, s0);
          }
        }
        bar_arrive<NB_S, 256>();
      }
    }
    if (WG == 1) {
      if (!last && elect_one()) load_chunk(sb + R_GA + w * 4096, s + 1, g1, bars + B_FA);
      {
        if (w > 0 && elect_one()) mbar_expect(bars + B_MB + 8 * w, w < 3 ? 3072 : SELF_STAS ? 28 * 256 : isC ? 18 * 256 : 19 * 256);
      }
      fence_async_smem();
      bar_sync<NB_B, 256>();
    }
    TRACE(7);
    WG_FENCE();
#pragma unroll
    for (int k = 0; k < 16; k++) wg_rs32<1>(acc, W[k][0], W[k][1], W[k][2], W[k][3], dsc.tok[16 + k]);
    WG_COMMIT();
    uint32_t wa[3][4];
    const uint32_t oxa = L16 + R_OX;
    if (WG == 0) {
      const uint32_t vma = oxa - (R_OX - R_VM) + w * 512, oa = opaque32(L4 + w * 512 + R_OX);
      TRACE(8);
      mbar_wait(bars + B_XS, par);
      TRACE(9);
      float sv[10];
      {
        uint32_t x[10];
        ldsm4t(x, oxa - (R_OX - R_XS)); ldsm4t(x + 4, oxa - (R_OX - R_XS) + 512); ldsm2t(x + 8, oxa - (R_OX - R_XS) + 1024);
        bar_arrive<NB_B, 256>();
#pragma unroll
        for (int j = 0; j < 5; j++) x[j] = hadd2(x[j], x[j + 5]);
        exp10(sv, x);
      }
      WG_WAIT(0);
      bar_arrive<NB_X, 256>();
      mbar_wait(bars + B_VM, par);
      uint32_t vm[4];
      ldsm4(vm, vma);
      uint32_t pb[5];
#pragma unroll
      for (int j = 0; j < 5; j++) pb[j] = pack2(sv[2 * j], sv[2 * j + 1]);
      TRACE(10);
      float o0[4], o1[4], sm[4];
      const uint32_t ONE = 0x3f803f80u;
      hmma0(o0, vt[0][0], vt[0][1], vt[0][2], vt[0][3], pb[0], pb[1]);
      hmma0(o1, vt[2][0], vt[2][1], vt[2][2], vt[2][3], pb[0], pb[1]);
      hmma0(sm, ONE, ONE, ONE, ONE, pb[0], pb[1]);
      hmma(sm, ONE, ONE, ONE, ONE, pb[2], pb[3]);
      hmma(o0, vt[1][0], vt[1][1], vt[1][2], vt[1][3], pb[2], pb[3]);
      hmma(o1, vt[3][0], vt[3][1], vt[3][2], vt[3][3], pb[2], pb[3]);
      hmma_k8(sm, ONE, ONE, pb[4]);
      hmma_k8(o0, vm[0], vm[1], pb[4]);
      hmma_k8(o1, vm[2], vm[3], pb[4]);
#pragma unroll
      for (int i = 0; i < 3; i++) ldsm4t(wa[i], woa + i * 4096);
      __syncwarp();
      const float i0 = rcp(sm[0]), i1 = rcp(sm[1]);
      sts32(oa, pack2(o0[0] * i0, o0[1] * i1)); sts32(oa + 128, pack2(o0[2] * i0, o0[3] * i1));
      sts32(oa + 256, pack2(o1[0] * i0, o1[1] * i1)); sts32(oa + 384, pack2(o1[2] * i0, o1[3] * i1));
      TRACE(11);
      bar_sync<NB_C, 128>();
    } else {
      if (!isC) {
        constexpr uint64_t dQ = mkdesc(0x400 + R_QK, 128, 1024, 0), dK = mkdesc(0x400 + R_QK + 5120, 128, 1024, 0);
        float sc[16];
        zero_regs<16>(sc);
        WG_FENCE();
#pragma unroll
        for (int k = 0; k < 4; k++) wg_ss32<1>(sc, dK + k * 16, dQ + k * 16);
        WG_COMMIT();
        const uint32_t top = rank == 0 ? to2 : to1, e = L4 + R_P + w * 256;
        WG_WAIT(0);
        bar_sync<NB_X, 256>();
        if (!last && elect_one()) load_chunk(sb + R_GB + w * 4096, s + 1, g2, bars + B_FB);
        reg_fence<16>(sc);
        if (w < 3) {
#pragma unroll
          for (int j = 0; j < 8; j++) {
            if ((j & 1) ? (j > 1 && (w == 0 || (w == 1 && j == 7))) : (j >= 4 || w != 1)) {
              const uint32_t t = pack2(sc[2 * j], sc[2 * j + 1]), o = (j >> 1) * 768 + (j & 1) * 128;
              st_async1(e + top + 3072 + o, t, bars + top + B_TS);
              sts32(e + o, t);
            }
          }
          __syncwarp();
          if (elect_one()) mbar_arrive(bars + B_TS);
        }
      } else {
        WG_WAIT(0);
        bar_sync<NB_X, 256>();
        if (!last && elect_one()) load_chunk(sb + R_GB + w * 4096, s + 1, g2, bars + B_FB);
      }
      TRACE(8);
      mbar_wait(bars + B_FA, 1);
      TRACE(11);
    }
    if (has_wo) {
      float* rslot = SLOT(s);
      uint32_t ob[4][4];
      float c[3][4];
      if (WG == 1) {
#pragma unroll
        for (int i = 0; i < 3; i++) ldsm4t(wa[i], woa + i * 4096);
        bar_sync<NB_D, 256>();
      }
      ldsm4t(ob[0], oxa);
      __syncwarp();
#pragma unroll
      for (int k = 0; k < 8; k++) {
        uint32_t nx[3][4];
        if ((k & 1) == 0 && k < 6) { ldsm4t(ob[(k >> 1) + 1], oxa + ((k >> 1) + 1) * 512); __syncwarp(); }
#pragma unroll
        for (int i = 0; i < 3; i++) {
          const uint32_t* o = ob[k >> 1] + (k & 1) * 2;
          if (k < 7) { ldsm4t(nx[i], woa + i * 4096 + (k + 1) * 512); if (i == 2) __syncwarp(); }
          if (k == 0) hmma0(c[i], wa[i][0], wa[i][1], wa[i][2], wa[i][3], o[0], o[1]);
          else hmma(c[i], wa[i][0], wa[i][1], wa[i][2], wa[i][3], o[0], o[1]);
#pragma unroll
          for (int q = 0; q < 4; q++) if (k < 7) wa[i][q] = nx[i][q];
        }
        if (k == ND_K && WG == 0) bar_arrive<NB_D, 256>();
      }
      const float* cv = &c[0][0];
      uint32_t r[6];
#pragma unroll
      for (int j = 0; j < 6; j++) r[j] = pack2(cv[2 * j], cv[2 * j + 1]);
      asm volatile("{\n.reg .pred p;\nsetp.lt.s32 p, %8, 0;\n@p bra.uni SKIP;\n"
                   "red.relaxed.gpu.global.add.noftz.v4.bf16x2 [%0], {%1, %2, %3, %7};\n"
                   "red.relaxed.gpu.global.add.noftz.v4.bf16x2 [%0+1024], {%4, %5, %6, %7};\nSKIP:\n}"
                   :: "l"(rslot), "r"(r[0]), "r"(r[1]), "r"(r[2]), "r"(r[3]), "r"(r[4]), "r"(r[5]), "r"(0x3f800000), "r"(s) : "memory");
    } else {
      bar_arrive<NB_D, 256>();
      if ((s & 3) == 0) {
        fence_gpu();
        if (s > 0 && elect_one()) red_add_u32(&g_flags[FL_ATT + 2 * (s - 4)], 1);
      }
      if (rank == 0 || head < 16)
        reinterpret_cast<uint4*>(g_slot)[((s + 2) & 3) * 3072 + ((s - 2) & 4) * 8 + rank * 2048 + head * 64 + opaque32(lane)] = make_uint4(0, 0, 0, 0);
    }
    const uint32_t t_red = clk32();
    uint32_t v[8];
    const float* slot = SLOT(s);
    TRACE(13);
    if (WG == 0) {
      if (!isC) {
        const int ln = opaque32(lane), kg = w - (ln >> 3);
        const uint32_t r16 = sb + R_P + w * 768 + (ln & 7) * 16;
        const uint32_t ta = r16 + (kg >= 0 ? kg * 128 : 640);
        const int dg = (ln >> 2) - 2 * (ln & 3);
        const uint32_t keep = dg > 0 ? 0xffffffffu : dg == 0 ? 0x0000ffffu : 0u;
        mbar_wait(bars + B_TS, par);
        uint32_t x[6], y[4];
        ldsm4t(x, ta); ldsm4t(y, ta + 3072); ldsm2t(x + 4, r16 + 512 + ((ln >> 3) & 1) * 3072);
#pragma unroll
        for (int j = 0; j < 5; j++) x[j] = hadd2(x[j], j < 4 ? y[j] : x[5]);
        x[0] = (x[0] & keep) | (0xff80ff80u & ~keep);
        float sv[10];
        exp10(sv, x);
        float sum = (((sv[0] + sv[1]) + (sv[2] + sv[3])) + ((sv[4] + sv[5]) + (sv[6] + sv[7]))) + (sv[8] + sv[9]);
        sum += __shfl_xor_sync(0xffffffffu, sum, 1);
        sum += __shfl_xor_sync(0xffffffffu, sum, 2);
        const float inv = rcp(sum);
#pragma unroll
        for (int j = 0; j < 5; j++) x[j] = pack2(sv[2 * j] * inv, sv[2 * j + 1] * inv);
        stsm4(r16 + (kg & 3) * 128, x);
        sts32(sb + ln * 4 + w * 768 + R_P + 512, x[4]);
        fence_async_smem();
        bar_arrive<NB_P, 256>();
      }
      while (clk32() - t_red < POLL_DELAY) {}
      load_red(v, slot);
      bar_sync<NB_E, 256>();
    } else {
      mbar_wait(bars + B_FB, 1);
    }
    TRACE(14);
    float ao[16];
    if (WG == 1) zero_regs<16>(ao);
    WG_FENCE();
#pragma unroll
    for (int k = 0; k < 32; k++) {
      if (WG == 0 && k == 16) WG_COMMIT();
      wg_rs32<1>(acc, W[16 + k][0], W[16 + k][1], W[16 + k][2], W[16 + k][3], dsc.tok[k]);
    }
    WG_COMMIT();
    TRACE(12);
    if (WG == 1) {
      if (!isC) {
        constexpr uint64_t dP = mkdesc(0x400 + R_P, 128, 768, 0);
        const uint64_t dV = mkdesc(0x400 + R_VT, 128, 512, 0) + rank * 256, dM = mkdesc(0x400 + R_VM, 0, 128, 0) + rank * 64;
        bar_sync<NB_P, 256>();
        WG_FENCE();
        wg_ss32<0>(ao, dV, dP); wg_ss32<0>(ao, dV + 16, dP + 16); wg_ss32<0>(ao, dM, dP + 32);
        WG_COMMIT();
      }
      bar_arrive<NB_E, 256>();
      if (elect_one()) mbar_expect(bars + B_XS + 8 * w, arm_bytes);
      while (clk32() - t_red < POLL_DELAY1) {}
      load_red(v, slot);
      bar_arrive<NB_W0, 128>();
    } else {
      WG_WAIT(1);
      bar_arrive<NB_F, 256>();
      sched_fence(head, 100);
      v[3] = opaque32(v[3]);
      const uint32_t tries = finish_red(v, slot);
      forward(std::integral_constant<int, 0>(), v, s, tries);
      TRACE(16);
    }
    WG_WAIT(0);
    reg_fence<16>(acc);
    if (WG == 0) bar_arrive<NB_G, 256>();
    TRACE(15);
    {
      uint32_t pq[8];
#pragma unroll
      for (int j = 0; j < 8; j++) pq[j] = pack2(acc[2 * j], acc[2 * j + 1]);
      if (WG == 1) {
        reg_fence<16>(ao);
#pragma unroll
        for (int j = 0; j < 8; j++) pk[j] = pack2(ao[2 * j], ao[2 * j + 1]);
      }
      if (!isC) {
        const uint32_t q = L4 + w * 256 + R_QK + WG * 5120;
#pragma unroll
        for (int j = 0; j < 8; j++) sts32(q + (j >> 1) * 1024 + (j & 1) * 128, pq[j]);
        if (WG == 1 && !ATT_LATE && s >= 0) store_att(s);
      } else {
        const uint32_t a = LV + warp * 1024;
        stsm4(a, pq); stsm4(a + 256, pq + 4);
      }
    }
    TRACE(17);
    if (WG == 1) {
      auto refill = [&]() {
        bar_sync<NB_F, 256>();
        if (s < NSEG - 2 && elect_one()) load_chunk(sb + R_GA + w * 4096, s + 2, 12 + w, bars + B_FA);
      };
      if (RF_FIRST) refill();
      if (has_wo) { v[3] = opaque32(v[3]); const uint32_t tries = finish_red(v, slot); forward(std::integral_constant<int, 1>(), v, s, tries); }
      if (!RF_FIRST) refill();
      TRACE(16);
    }
    if (isC && V_FENCE) { fence_async_smem(); __syncwarp(); }
    TRACE(18);
  }
  if (WG == 1 && ATT_LATE && !isC) store_att(NSEG - 1);
  if (WG == 1) bar_sync<NB_G, 256>();
  mbar_wait_safe(bars + B_MB + 8, 0); mbar_wait_safe(bars + B_MB + 16, 0); mbar_wait_safe(bars + B_MB + 24, 0);
#undef L16
#undef L8
#undef L4
#undef SLOT
#undef LV
}

__global__ void __cluster_dims__(3, 1, 1) __launch_bounds__(256, 1)
kernel_R(const __grid_constant__ CUtensorMap tmq, const __grid_constant__ CUtensorMap tmk, const __grid_constant__ CUtensorMap tmv,
         const __grid_constant__ CUtensorMap tmo, const __grid_constant__ CUtensorMap tmm, const __nv_bfloat16* __restrict__ x,
         const __nv_bfloat16* __restrict__ mem0, const __nv_bfloat16* __restrict__ cvec, const __grid_constant__ RDesc dsc) {
  extern __shared__ __align__(1024) uint8_t smem[];
  const uint32_t sb = smem_u32(smem);
  uint32_t rank; asm("mov.u32 %0, %%cluster_ctarank;" : "=r"(rank));
  rank = __shfl_sync(0xffffffffu, rank, 0);
  const int cta = blockIdx.x, head = __shfl_sync(0xffffffffu, cta / 3, 0);
  const int tid = threadIdx.x, lane = tid & 31;
  const int warp = __shfl_sync(0xffffffffu, tid >> 5, 0);
  const int wg = warp >> 2, w = warp & 3;
  const uint32_t bars = sb + R_BAR;
  const CUtensorMap* tmw = rank == 2 ? &tmv : (wg == 0 ? &tmq : &tmk);
  const int fcol = head * 128 + (rank == 2 ? wg * 64 : (int)rank * 64);

  asm volatile("griddepcontrol.launch_dependents;");
  uint32_t W[48][4];
  {
    if (sb != (rank << 24) + 0x400) __trap();
    if (tid == 0) {
      sts64(bars + 248, rank, head);
      mbar_init(bars + B_MB, 4); mbar_init(bars + B_MB + 8, 1); mbar_init(bars + B_MB + 16, 1); mbar_init(bars + B_MB + 24, SELF_STAS ? 1 : rank == 2 ? 5 : 4);
      for (int i = B_XS; i <= B_X; i += 8) mbar_init(bars + i, i == B_FA || i == B_FB || (i == B_TS && rank < 2) ? 4 : 1);
      asm volatile("fence.mbarrier_init.release.cluster;" ::: "memory");
      fence_async_smem();
    }
    __syncthreads();
    asm volatile("barrier.cluster.arrive.relaxed.aligned;" ::: "memory");
    TS(0);
    const int nwm = rank == 0 ? 6 : 5, wm0 = rank == 0 ? 0 : 5 * rank + 1, nrg = cta < 64 ? 3 : 2;
    if (elect_one()) {
      if (warp == 0) { mbar_expect(bars + B_WM, nwm * 8192); mbar_expect(bars + B_X, nrg * 16384); }
      if (warp < nwm) tma2d(sb + R_GA + warp * 8192, &tmm, head * 64, (wm0 + warp) * 64, bars + B_WM);
#pragma unroll 1
      for (int r = 0; r < nrg; r++) bulk_g2s(sb + R_TAIL + (r * 8 + warp) * 2064, x + (size_t)((cta + 96 * r) * 8 + warp) * D_, 2048, bars + B_X);
      if (w == 0) mbar_expect(bars + B_STG + wg * 16, 49152);
      if (w < 2) tma2d(sb + R_WO + wg * 49152 + w * 8192, tmw, fcol, rot_chunk(w, rank) * 64, bars + B_STG + wg * 16);
    }
    float* scr = reinterpret_cast<float*>(smem + R_VT);
#pragma unroll 1
    for (int i = tid; i < nwm * 64; i += 256) {
      const float c = __bfloat162float(cvec[wm0 * 64 + i]);
      scr[i] = __bfloat162float(__float2bfloat16(c / (1.f + __expf(-c))));
    }
    if (tid < 128) {
      uint32_t e[4] = {0u, 0u, 0u, 0u};
      if (cta >= 72 && (tid & 32)) {
        const uint16_t* mp = reinterpret_cast<const uint16_t*>(mem0) + 2 * (lane & 3) * D_ + (lane >> 2);
#pragma unroll
        for (int q = 0; q < 3; q++) {
          const int n = 3 * (tid >> 6) + q, col = wo_tile(3 * (cta & 7) + (n >> 1), (cta - 72) >> 3) * 16 + 8 * (n & 1);
          e[q] = mp[col] | (uint32_t)mp[col + D_] << 16;
        }
        e[3] = 0x42000000u;
      }
      reinterpret_cast<uint4*>(g_slot)[cta * 128 + tid] = make_uint4(e[0], e[1], e[2], e[3]);
    }
    __syncthreads();
    TS(1);
    mbar_wait_safe(bars + B_WM, 0);
    if (elect_one()) tma2d(sb + R_WO + wg * 49152 + (2 + w) * 8192, tmw, fcol, rot_chunk(2 + w, rank) * 64, bars + B_STG + wg * 16);
    {
      float a[8];
#pragma unroll
      for (int j = 0; j < 8; j++) a[j] = 0.f;
#pragma unroll 2
      for (int i = 0; i < 2 * nwm; i++) {
        uint32_t u[4];
        lds128(u, sb + R_GA + i * 4096 + tid * 16);
        const float sc = scr[i * 32 + (tid >> 3)];
#pragma unroll
        for (int j = 0; j < 4; j++) { a[2 * j] += sc * bf_lo(u[j]); a[2 * j + 1] += sc * bf_hi(u[j]); }
      }
#pragma unroll
      for (int j = 0; j < 8; j++) { a[j] += __shfl_xor_sync(0xffffffffu, a[j], 8); a[j] += __shfl_xor_sync(0xffffffffu, a[j], 16); }
      if (lane < 8) {
        sts128(sb + R_VT + 1536 + warp * 256 + lane * 32, __float_as_uint(a[0]), __float_as_uint(a[1]), __float_as_uint(a[2]), __float_as_uint(a[3]));
        sts128(sb + R_VT + 1552 + warp * 256 + lane * 32, __float_as_uint(a[4]), __float_as_uint(a[5]), __float_as_uint(a[6]), __float_as_uint(a[7]));
      }
    }
    __syncthreads();
    TS(2);
    if (warp == 7) {
      float t0 = 0.f, t1 = 0.f;
#pragma unroll
      for (int i = 0; i < 8; i++) { float t[2]; lds64f(t, sb + R_VT + 1536 + i * 256 + lane * 8); t0 += t[0]; t1 += t[1]; }
      reinterpret_cast<float2*>(g_modp + rank * 2048 + head * 64)[lane] = make_float2(t0, t1);
      fence_gpu();
      __syncwarp();
      if (lane == 0) red_add_u32(&g_flags[FL_S1], 1);
      __syncwarp();
    }
    mbar_wait_safe(bars + B_X, 0);
#pragma unroll 1
    for (int r = 0; r < nrg; r++) {
      float f[32];
#pragma unroll
      for (int i = 0; i < 4; i++) {
        uint32_t u[4];
        lds128(u, sb + R_TAIL + (r * 8 + warp) * 2064 + i * 512 + lane * 16);
#pragma unroll
        for (int j = 0; j < 4; j++) { f[8 * i + 2 * j] = bf_lo(u[j]); f[8 * i + 2 * j + 1] = bf_hi(u[j]); }
      }
      float t = 0.f;
#pragma unroll
      for (int i = 0; i < 32; i++) t += f[i];
#pragma unroll
      for (int o = 1; o < 32; o <<= 1) t += __shfl_xor_sync(0xffffffffu, t, o);
      const float mean = t * (1.f / D_);
      t = 0.f;
#pragma unroll
      for (int i = 0; i < 32; i++) t = fmaf(f[i] - mean, f[i] - mean, t);
#pragma unroll
      for (int o = 1; o < 32; o <<= 1) t += __shfl_xor_sync(0xffffffffu, t, o);
      const float rstd = rsqrtf(t * (1.f / D_) + 1e-5f);
      if (lane == 0) sts64(sb + R_VT + 3584 + (r * 8 + warp) * 8, __float_as_uint(rstd), __float_as_uint(-mean * rstd));
    }
    TS(3);
    if (w < PF1 && elect_one()) tma2d_prefetch(tmw, fcol, rot_chunk(6 + w, rank) * 64);
    if (tid == 0) wait_flag(&g_flags[FL_S1], 96);
    __syncthreads();
    TS(4);
    {
      float4 p[6];
#pragma unroll
      for (int i = 0; i < 6; i++) p[i] = __ldcg(reinterpret_cast<const float4*>(g_modp + (i >> 1) * 2048) + 2 * tid + (i & 1));
      if (w < PF2 && elect_one()) tma2d_prefetch(tmw, fcol, (9 + w) * 64);
      sts128(sb + R_VT + 5120 + tid * 16, pack2(p[0].x + p[2].x + p[4].x, p[0].y + p[2].y + p[4].y), pack2(p[0].z + p[2].z + p[4].z, p[0].w + p[2].w + p[4].w),
             pack2(p[1].x + p[3].x + p[5].x, p[1].y + p[3].y + p[5].y), pack2(p[1].z + p[3].z + p[5].z, p[1].w + p[3].w + p[5].w));
    }
    __syncthreads();
#pragma unroll 2
    for (int it = 0; it < 4 * nrg; it++) {
      const int r = it >> 2, rg = cta + 96 * r, c = 16 * warp + (lane >> 3) + 4 * (it & 3);
      uint32_t a[4], b[4], u[4], o[4];
      float t[2];
      lds128(u, sb + R_TAIL + (r * 8 + (lane & 7)) * 2064 + c * 16);
      lds128(a, sb + R_VT + 5120 + c * 16); lds128(b, sb + R_VT + 7168 + c * 16);
      lds64f(t, sb + R_VT + 3584 + (r * 8 + (lane & 7)) * 8);
#pragma unroll
      for (int j = 0; j < 4; j++)
        o[j] = pack2(fmaf(fmaf(bf_lo(u[j]), t[0], t[1]), 1.f + bf_lo(b[j]), bf_lo(a[j])), fmaf(fmaf(bf_hi(u[j]), t[0], t[1]), 1.f + bf_hi(b[j]), bf_hi(a[j])));
      *reinterpret_cast<uint4*>(g_h + (size_t)(rg >> 2) * 65536 + (lane & 7) * 16 + (c & 7) * 128 +
                                (c < 96 ? (c >> 3) * 4096 + (rg & 3) * 1024 : 49152 + (rg & 3) * 4096 + ((c >> 3) - 12) * 1024)) =
          make_uint4(o[0], o[1], o[2], o[3]);
    }
    TS(5);
    __syncthreads();
    TS(6);
    if (w < PF3 && elect_one()) tma2d(sb + R_TAIL + warp * 8192, tmw, fcol, 768 + w * 64, bars + B_TAIL);
    if (warp == 3 && lane == 0) { fence_gpu(); red_add_u32(&g_flags[FL_S2], 1); }
    __syncwarp();

    const uint32_t a0 = opaque32(sb + R_WO + wg * 49152 + ((lane >> 4) * 8 + (lane & 7)) * 128 + (((2 * w + ((lane >> 3) & 1)) ^ (lane & 7)) << 4));
    mbar_wait_safe(bars + B_STG + wg * 16, 0);
    TS(7);
#pragma unroll
    for (int i = 0; i < 24; i++) ldsm4t(W[i], a0 + i * 2048);
    if (tid == 0) wait_flag(&g_flags[FL_S2], 96);
    __syncthreads();
    asm volatile("fence.proxy.async.global;" ::: "memory");
    if (elect_one()) {
      if (wg == 0) load_chunk(sb + R_GA + w * 4096, 0, 12 + w, bars + B_FA);
      if (w == 0) mbar_expect(bars + B_STG + wg * 16 + 8, 49152);
#pragma unroll 1
      for (int c = w; c < 6; c += 4) tma2d(sb + R_WO + wg * 49152 + c * 8192, tmw, fcol, rot_chunk(6 + c, rank) * 64, bars + B_STG + wg * 16 + 8);
      if (warp == 0) mbar_expect(bars + B_TAIL, 65536);
      if (w >= PF3) tma2d(sb + R_TAIL + warp * 8192, tmw, fcol, 768 + w * 64, bars + B_TAIL);
      if (wg == 1) mbar_expect(bars + B_XS + 8 * w, w == 2 ? 0 : arm_size(w, rank == 2));
#pragma unroll 1
      for (int i = warp; i < PF4; i += 8) tma2d_prefetch(&tmo, 16 * wo_tile(i, rank), head * 128);
    }
    TS(8);
    mbar_wait_safe(bars + B_STG + wg * 16 + 8, 0);
    TS(9);
#pragma unroll
    for (int i = 0; i < 24; i++) ldsm4t(W[24 + i], a0 + i * 2048);
    __syncthreads();
    if (elect_one()) {
      const int n = rank == 2 ? 22 : 21;
      if (warp == 0) mbar_expect(bars + B_WO, n * 4096);
#pragma unroll 1
      for (int i = warp; i < n; i += 8) tma2d(sb + R_WO + i * 4096, &tmo, 16 * wo_tile(i, rank), head * 128, bars + B_WO);
    }
    sts32(sb + R_P + warp * 768 + 640 + lane * 4, wg == 0 ? 0u : 0xff80ff80u);
    mbar_wait_safe(bars + B_TAIL, 0);
    asm volatile("barrier.cluster.wait.aligned;\nbarrier.cluster.arrive.relaxed.aligned;\nbarrier.cluster.wait.aligned;" ::: "memory");
  }
  uint32_t rh[2];
  lds64(rh, bars + 248);
  rh[0] = __shfl_sync(0xffffffffu, rh[0], 0); rh[1] = __shfl_sync(0xffffffffu, rh[1], 0);
  if (wg == 0) r_main<0>(W, dsc, rh[1], rh[0], lane, w);
  else r_main<1>(W, dsc, rh[1], rh[0], lane, w);
  __syncthreads();
  if (rank < 2 && threadIdx.x == 0) { fence_gpu(); red_add_u32(&g_flags[FL_ATT + 8 * 15], 1); }
  asm volatile("barrier.cluster.arrive.release.aligned;\nbarrier.cluster.wait.acquire.aligned;" ::: "memory");
}

template <int TA> __device__ __forceinline__ void wg_ss256(float* d, uint64_t a, uint64_t b) {
  asm volatile("wgmma.mma_async.sync.aligned.m64n256k16.f32.bf16.bf16 {%0,%1,%2,%3,%4,%5,%6,%7,%8,%9,%10,%11,%12,%13,%14,%15,%16,%17,%18,%19,%20,%21,%22,%23,%24,%25,%26,%27,%28,%29,%30,%31,%32,%33,%34,%35,%36,%37,%38,%39,%40,%41,%42,%43,%44,%45,%46,%47,%48,%49,%50,%51,%52,%53,%54,%55,%56,%57,%58,%59,%60,%61,%62,%63,%64,%65,%66,%67,%68,%69,%70,%71,%72,%73,%74,%75,%76,%77,%78,%79,%80,%81,%82,%83,%84,%85,%86,%87,%88,%89,%90,%91,%92,%93,%94,%95,%96,%97,%98,%99,%100,%101,%102,%103,%104,%105,%106,%107,%108,%109,%110,%111,%112,%113,%114,%115,%116,%117,%118,%119,%120,%121,%122,%123,%124,%125,%126,%127}, %128, %129, 1, 1, 1, %130, 1;"
               : "+f"(d[0]), "+f"(d[1]), "+f"(d[2]), "+f"(d[3]), "+f"(d[4]), "+f"(d[5]), "+f"(d[6]), "+f"(d[7]),
                 "+f"(d[8]), "+f"(d[9]), "+f"(d[10]), "+f"(d[11]), "+f"(d[12]), "+f"(d[13]), "+f"(d[14]), "+f"(d[15]),
                 "+f"(d[16]), "+f"(d[17]), "+f"(d[18]), "+f"(d[19]), "+f"(d[20]), "+f"(d[21]), "+f"(d[22]), "+f"(d[23]),
                 "+f"(d[24]), "+f"(d[25]), "+f"(d[26]), "+f"(d[27]), "+f"(d[28]), "+f"(d[29]), "+f"(d[30]), "+f"(d[31]),
                 "+f"(d[32]), "+f"(d[33]), "+f"(d[34]), "+f"(d[35]), "+f"(d[36]), "+f"(d[37]), "+f"(d[38]), "+f"(d[39]),
                 "+f"(d[40]), "+f"(d[41]), "+f"(d[42]), "+f"(d[43]), "+f"(d[44]), "+f"(d[45]), "+f"(d[46]), "+f"(d[47]),
                 "+f"(d[48]), "+f"(d[49]), "+f"(d[50]), "+f"(d[51]), "+f"(d[52]), "+f"(d[53]), "+f"(d[54]), "+f"(d[55]),
                 "+f"(d[56]), "+f"(d[57]), "+f"(d[58]), "+f"(d[59]), "+f"(d[60]), "+f"(d[61]), "+f"(d[62]), "+f"(d[63]),
                 "+f"(d[64]), "+f"(d[65]), "+f"(d[66]), "+f"(d[67]), "+f"(d[68]), "+f"(d[69]), "+f"(d[70]), "+f"(d[71]),
                 "+f"(d[72]), "+f"(d[73]), "+f"(d[74]), "+f"(d[75]), "+f"(d[76]), "+f"(d[77]), "+f"(d[78]), "+f"(d[79]),
                 "+f"(d[80]), "+f"(d[81]), "+f"(d[82]), "+f"(d[83]), "+f"(d[84]), "+f"(d[85]), "+f"(d[86]), "+f"(d[87]),
                 "+f"(d[88]), "+f"(d[89]), "+f"(d[90]), "+f"(d[91]), "+f"(d[92]), "+f"(d[93]), "+f"(d[94]), "+f"(d[95]),
                 "+f"(d[96]), "+f"(d[97]), "+f"(d[98]), "+f"(d[99]), "+f"(d[100]), "+f"(d[101]), "+f"(d[102]), "+f"(d[103]),
                 "+f"(d[104]), "+f"(d[105]), "+f"(d[106]), "+f"(d[107]), "+f"(d[108]), "+f"(d[109]), "+f"(d[110]), "+f"(d[111]),
                 "+f"(d[112]), "+f"(d[113]), "+f"(d[114]), "+f"(d[115]), "+f"(d[116]), "+f"(d[117]), "+f"(d[118]), "+f"(d[119]),
                 "+f"(d[120]), "+f"(d[121]), "+f"(d[122]), "+f"(d[123]), "+f"(d[124]), "+f"(d[125]), "+f"(d[126]), "+f"(d[127])
               : "l"(a), "l"(b), "n"(TA));
}
template <int TA> __device__ __forceinline__ void wg_ss128(float* d, uint64_t a, uint64_t b) {
  asm volatile("wgmma.mma_async.sync.aligned.m64n128k16.f32.bf16.bf16 {%0,%1,%2,%3,%4,%5,%6,%7,%8,%9,%10,%11,%12,%13,%14,%15,%16,%17,%18,%19,%20,%21,%22,%23,%24,%25,%26,%27,%28,%29,%30,%31,%32,%33,%34,%35,%36,%37,%38,%39,%40,%41,%42,%43,%44,%45,%46,%47,%48,%49,%50,%51,%52,%53,%54,%55,%56,%57,%58,%59,%60,%61,%62,%63}, %64, %65, 1, 1, 1, %66, 1;"
               : "+f"(d[0]), "+f"(d[1]), "+f"(d[2]), "+f"(d[3]), "+f"(d[4]), "+f"(d[5]), "+f"(d[6]), "+f"(d[7]),
                 "+f"(d[8]), "+f"(d[9]), "+f"(d[10]), "+f"(d[11]), "+f"(d[12]), "+f"(d[13]), "+f"(d[14]), "+f"(d[15]),
                 "+f"(d[16]), "+f"(d[17]), "+f"(d[18]), "+f"(d[19]), "+f"(d[20]), "+f"(d[21]), "+f"(d[22]), "+f"(d[23]),
                 "+f"(d[24]), "+f"(d[25]), "+f"(d[26]), "+f"(d[27]), "+f"(d[28]), "+f"(d[29]), "+f"(d[30]), "+f"(d[31]),
                 "+f"(d[32]), "+f"(d[33]), "+f"(d[34]), "+f"(d[35]), "+f"(d[36]), "+f"(d[37]), "+f"(d[38]), "+f"(d[39]),
                 "+f"(d[40]), "+f"(d[41]), "+f"(d[42]), "+f"(d[43]), "+f"(d[44]), "+f"(d[45]), "+f"(d[46]), "+f"(d[47]),
                 "+f"(d[48]), "+f"(d[49]), "+f"(d[50]), "+f"(d[51]), "+f"(d[52]), "+f"(d[53]), "+f"(d[54]), "+f"(d[55]),
                 "+f"(d[56]), "+f"(d[57]), "+f"(d[58]), "+f"(d[59]), "+f"(d[60]), "+f"(d[61]), "+f"(d[62]), "+f"(d[63])
               : "l"(a), "l"(b), "n"(TA));
}
template <int TA> __device__ __forceinline__ void wg_ss64(float* d, uint64_t a, uint64_t b) {
  asm volatile("wgmma.mma_async.sync.aligned.m64n64k16.f32.bf16.bf16 {%0,%1,%2,%3,%4,%5,%6,%7,%8,%9,%10,%11,%12,%13,%14,%15,%16,%17,%18,%19,%20,%21,%22,%23,%24,%25,%26,%27,%28,%29,%30,%31}, %32, %33, 1, 1, 1, %34, 1;"
               : "+f"(d[0]), "+f"(d[1]), "+f"(d[2]), "+f"(d[3]), "+f"(d[4]), "+f"(d[5]), "+f"(d[6]), "+f"(d[7]),
                 "+f"(d[8]), "+f"(d[9]), "+f"(d[10]), "+f"(d[11]), "+f"(d[12]), "+f"(d[13]), "+f"(d[14]), "+f"(d[15]),
                 "+f"(d[16]), "+f"(d[17]), "+f"(d[18]), "+f"(d[19]), "+f"(d[20]), "+f"(d[21]), "+f"(d[22]), "+f"(d[23]),
                 "+f"(d[24]), "+f"(d[25]), "+f"(d[26]), "+f"(d[27]), "+f"(d[28]), "+f"(d[29]), "+f"(d[30]), "+f"(d[31])
               : "l"(a), "l"(b), "n"(TA));
}

constexpr int H_STAGE = 49152, H_NST = 4;
constexpr int H_STG = H_NST * H_STAGE;
constexpr int H_VEC = H_STG + 16384;
constexpr int H_BAR = H_VEC + 6144;
constexpr int H_SMEM = H_BAR + 256;
constexpr int HB_FULL = 0, HB_EMPTY = 32, HB_IFULL = 64, HB_IEMPTY = 80, HB_ITEM = 96, HB_INC = 104;
enum { IT_END = 0, IT_MOD = 1, IT_XT = 2, IT_OUT = 3, IT_UV = 4, IT_F1 = 5, IT_F2 = 6 };
constexpr int MAX_ITEMS = 1400;
struct HList { uint32_t n; uint32_t it[MAX_ITEMS]; };
#define HT(i)

#define H_LAG 2
template <int BN, int TA>
__device__ __forceinline__ void h_mainloop(float* acc, uint32_t sb, int nst, uint32_t& st, uint32_t& ph, int wg, bool leader, bool fixed_a = false) {
  constexpr int KS = BN == 64 ? 8 : 4;
  constexpr uint32_t BOFF = BN == 64 ? 32768 : 16384;
  const uint64_t da0 = fixed_a ? mkdesc(sb + H_STG, 128, 0, 0) : TA ? mkdesc(sb + wg * 1024, 2048, 128, 0) : mkdesc(sb + wg * 8192, 128, 1024, 0);
  const uint64_t db0 = mkdesc(sb + BOFF, 8192, 1024, 1);
  uint32_t prev = 0;
  zero_regs<BN / 2>(acc);
  if (H_LAG && wg == 1) bar_sync<4, 256>();
#pragma unroll 1
  for (int i = 0; i < nst; i++) {
    mbar_wait(sb + H_BAR + HB_FULL + st * 8, ph);
    const uint64_t da = da0 + (fixed_a ? i * 64 : st * (H_STAGE >> 4)), db = db0 + st * (H_STAGE >> 4);
    WG_FENCE();
#pragma unroll
    for (int k = 0; k < KS; k++) {
      const uint64_t a = da + (k >> 2) * 1024 + (k & 3) * (TA ? 256 : 16), b = db + k * 128;
      if (BN == 256) wg_ss256<TA>(acc, a, b); else if (BN == 128) wg_ss128<TA>(acc, a, b); else wg_ss64<TA>(acc, a, b);
    }
    WG_COMMIT();
    if (H_LAG && wg == 0 && i == H_LAG - 1) bar_arrive<4, 256>();
    WG_WAIT(1);
    if (i > 0 && leader) mbar_arrive(sb + H_BAR + HB_EMPTY + prev * 8);
    prev = st;
    if (++st == H_NST) { st = 0; ph ^= 1; }
  }
  WG_WAIT(0);
  HT(2);
  reg_fence<BN / 2>(acc);
  if (leader) mbar_arrive(sb + H_BAR + HB_EMPTY + prev * 8);
}

template <int BN, bool FINAL>
__device__ __forceinline__ bool h_residual(uint32_t sb, uint32_t va, int mt, int n0, uint32_t& st, uint32_t& ph, int warp, int lane, __nv_bfloat16* out,
                                           int part = 0, int lgp = 0) {
  const size_t toff = (size_t)(mt * 16 + (n0 >> 6)) * 16384 + warp * 2048 + (lane & 3) * 128 + (lane >> 2) * 16;
  uint4 r[BN / 16];
#pragma unroll
  for (int i = 0; i < BN / 16; i++) r[i] = __ldcg(reinterpret_cast<const uint4*>(g_x1 + toff + (i >> 2) * 16384 + ((i >> 1) & 1) * 512 + (i & 1) * 1024));
  float acc[BN / 2];
  h_mainloop<BN, FINAL ? 0 : 1>(acc, sb, ((FINAL ? 56 : 64) / (BN == 64 ? 2 : 1)) >> lgp, st, ph, warp >> 2, (warp & 3) == 0 && lane == 0);
  if (BN == 64 && lgp > 0) {
    const int tile = (FINAL * 4 + (mt & 3)) * 16 + (n0 >> 6);
    float4* ws = reinterpret_cast<float4*>(g_ws) + (size_t)tile * 8192 + warp * 32 + lane;
#pragma unroll
    for (int i = 0; i < 8; i++) ws[part * 2048 + i * 256] = make_float4(acc[4 * i], acc[4 * i + 1], acc[4 * i + 2], acc[4 * i + 3]);
    bar_sync<1, 256>();
    if (warp == 0 && lane == 0) { fence_gpu(); const uint32_t t = atomicAdd(&g_flags[FL_SPL + tile], 1); fence_gpu(); sts32(sb + H_BAR + HB_INC + 8, t); }
    bar_sync<1, 256>();
    if (lds32(sb + H_BAR + HB_INC + 8) != (1u << lgp) - 1) return false;
#pragma unroll 1
    for (int p = 1; p < (1 << lgp); p++) {
      float4 o[8];
#pragma unroll
      for (int i = 0; i < 8; i++) o[i] = __ldcg(ws + (part ^ p) * 2048 + i * 256);
#pragma unroll
      for (int i = 0; i < 8; i++) { acc[4 * i] += o[i].x; acc[4 * i + 1] += o[i].y; acc[4 * i + 2] += o[i].z; acc[4 * i + 3] += o[i].w; }
    }
  }
  float sm[4] = {0.f, 0.f, 0.f, 0.f};
  const uint32_t stg = sb + H_STG + warp * 2048;
#pragma unroll
  for (int c = 0; c < BN / 32; c++) {
    uint32_t y[2][4] = {{r[2 * c].x, r[2 * c].y, r[2 * c].z, r[2 * c].w}, {r[2 * c + 1].x, r[2 * c + 1].y, r[2 * c + 1].z, r[2 * c + 1].w}}, z[2][4];
#pragma unroll
    for (int j = 0; j < 4; j++) {
      const uint32_t gt = lds32(va + c * 64 + j * 16 + (lane & 3) * 4);
      const uint32_t cb = FINAL ? 0 : lds32(va + 512 + c * 64 + j * 16 + (lane & 3) * 4);
#pragma unroll
      for (int h = 0; h < 2; h++) {
        const float* a = acc + c * 16 + j * 4 + h * 2;
        y[h][j] = pack2(fmaf(bf_lo(gt), a[0], bf_lo(y[h][j])), fmaf(bf_hi(gt), a[1], bf_hi(y[h][j])));
        if (!FINAL) {
          const float p = bf_lo(y[h][j]), q = bf_hi(y[h][j]);
          sm[2 * h] += p + q;
          sm[2 * h + 1] = fmaf(p, p, fmaf(q, q, sm[2 * h + 1]));
          z[h][j] = pack2(fmaf(p, bf_lo(cb), p), fmaf(q, bf_hi(cb), q));
        }
      }
    }
    if (!FINAL) {
#pragma unroll
      for (int h = 0; h < 2; h++) {
        const size_t o = toff + (c >> 1) * 16384 + (c & 1) * 512 + h * 1024;
        *reinterpret_cast<uint4*>(g_x1 + o) = make_uint4(y[h][0], y[h][1], y[h][2], y[h][3]);
        *reinterpret_cast<uint4*>(g_h2 + o) = make_uint4(z[h][0], z[h][1], z[h][2], z[h][3]);
      }
    } else {
#pragma unroll
      for (int h = 0; h < 2; h++) stsm4(stg + (h * 8 + (lane & 7)) * 128 + ((((c & 1) * 4 + (lane >> 3)) ^ (lane & 7)) << 4), y[h]);
      if (c & 1) {
        __syncwarp();
#pragma unroll
        for (int j = 0; j < 4; j++) {
          const int rr = 4 * j + (lane >> 3);
          uint32_t v[4];
          lds128(v, stg + rr * 128 + (((lane & 7) ^ (rr & 7)) << 4));
          *reinterpret_cast<uint4*>(out + (size_t)(mt * 128 + warp * 16 + rr) * D_ + n0 + (c >> 1) * 64 + (lane & 7) * 8) = make_uint4(v[0], v[1], v[2], v[3]);
        }
        __syncwarp();
      }
    }
  }
  if (!FINAL) {
#pragma unroll
    for (int j = 0; j < 4; j++) { sm[j] += __shfl_xor_sync(0xffffffffu, sm[j], 1); sm[j] += __shfl_xor_sync(0xffffffffu, sm[j], 2); }
    const int t = lane & 3;
    atomicAdd(g_stat + (mt * 128 + warp * 16 + (t >> 1) * 8 + (lane >> 2)) * 2 + (t & 1), t == 0 ? sm[0] : t == 1 ? sm[1] : t == 2 ? sm[2] : sm[3]);
  }
  return true;
}

__device__ __forceinline__ float silu_mul(float g, float u) {
  float t; asm("tanh.approx.f32 %0, %1;" : "=f"(t) : "f"(0.5f * g));
  const float h = 0.5f * g * u;
  return fmaf(h, t, h);
}

template <int BN>
__device__ __forceinline__ void h_swiglu(const float* acc, uint32_t va, int mt, int kb0, int warp, int lane) {
  uint8_t* ap = g_act + (size_t)(mt * 56 + kb0) * 16384 + warp * 2048 + (lane & 3) * 128 + (lane >> 2) * 16;
  float rs[2], nm[2];
#pragma unroll
  for (int h = 0; h < 2; h++) {
    float t[2];
    lds64f(t, va + 2048 + (warp * 16 + h * 8 + (lane >> 2)) * 8);
    const float mean = t[0] * (1.f / D_);
    rs[h] = rsqrtf(fmaxf(t[1] * (1.f / D_) - mean * mean, 0.f) + 1e-5f);
    nm[h] = -mean * rs[h];
  }
#pragma unroll
  for (int c = 0; c < BN / 64; c++) {
    uint32_t y[2][4];
#pragma unroll
    for (int j = 0; j < 4; j++) {
      const float* g = acc + 16 * c + 4 * j; const float* u = g + BN / 4;
      float p[4], q[4], o[4];
      lds128f(p, va + (4 * c + j) * 128 + (lane & 3) * 32); lds128f(q, va + (4 * c + j) * 128 + (lane & 3) * 32 + 16);
#pragma unroll
      for (int e = 0; e < 4; e++)
        o[e] = silu_mul(fmaf(rs[e >> 1], g[e], fmaf(nm[e >> 1], p[e & 1], p[2 + (e & 1)])), fmaf(rs[e >> 1], u[e], fmaf(nm[e >> 1], q[e & 1], q[2 + (e & 1)])));
      y[0][j] = pack2(o[0], o[1]); y[1][j] = pack2(o[2], o[3]);
    }
#pragma unroll
    for (int h = 0; h < 2; h++)
      *reinterpret_cast<uint4*>(ap + (c >> 1) * 16384 + (c & 1) * 512 + h * 1024) = make_uint4(y[h][0], y[h][1], y[h][2], y[h][3]);
  }
}

__global__ void __launch_bounds__(384, 1)
kernel_H(const __grid_constant__ CUtensorMap tmo, const __grid_constant__ CUtensorMap tm1, const __grid_constant__ CUtensorMap tm3,
         const __grid_constant__ CUtensorMap tm2, const __grid_constant__ CUtensorMap tmm, const __nv_bfloat16* __restrict__ x,
         const __nv_bfloat16* __restrict__ cvec, __nv_bfloat16* __restrict__ out, const __grid_constant__ HList list) {
  extern __shared__ __align__(1024) uint8_t smem[];
  constexpr uint32_t sb = 0x400, bars = sb + H_BAR;
  const int tid = threadIdx.x, lane = tid & 31;
  const int warp = __shfl_sync(0xffffffffu, tid >> 5, 0);
  if (tid == 0) {
    if (smem_u32(smem) != sb) __trap();
    for (int i = 0; i < H_NST; i++) { mbar_init(bars + HB_FULL + i * 8, 1); mbar_init(bars + HB_EMPTY + i * 8, 2); }
    for (int i = 0; i < 2; i++) { mbar_init(bars + HB_IFULL + i * 8, 1); mbar_init(bars + HB_IEMPTY + i * 8, 3); }
    fence_async_smem();
  }
  __syncthreads();
  if (warp >= 8) {
    asm volatile("setmaxnreg.dec.sync.aligned.u32 40;");
    if (warp == 8) {
      uint32_t st = 0, ph = 1;
#pragma unroll 1
      for (uint32_t n = 0;; n++) {
        uint32_t q = 0;
        if (lane == 0) q = atomicAdd(&g_flags[FL_HEAD], 1);
        q = __shfl_sync(0xffffffffu, q, 0);
        const uint32_t it = q < list.n ? list.it[q] : 0;
        const int type = it & 7, mt = (it >> 3) & 15, idx = (it >> 7) & 63, sz = (it >> 13) & 3, part = (it >> 15) & 3, lgp = (it >> 17) & 3;
        {
          int f = FL_GO; uint32_t target = 0;
          if (type == IT_OUT) { f = lane == 0 ? FL_ATT + 8 * mt : lane == 1 ? FL_XT + 8 * mt : FL_MOD; target = lane == 0 ? 64 : lane == 1 ? 2 : 16; }
          else if (type == IT_F1) { f = lane == 0 ? FL_OUT + 8 * mt : FL_UV; target = lane == 0 ? 16 : 28; }
          else if (type == IT_F2) { f = FL_F1 + 8 * mt; target = 56; }
          else if (type == IT_UV) { f = FL_MOD; target = 16; }
          else if (type != IT_END) target = 1;
          if (lane < 3) wait_flag(&g_flags[f], target);
          __syncwarp();
          asm volatile("fence.proxy.async.global;" ::: "memory");
        }
        mbar_wait(bars + HB_IEMPTY + (n & 1) * 8, ((n >> 1) & 1) ^ 1);
        if (elect_one()) {
          sts32(bars + HB_ITEM + (n & 1) * 4, it | (q << 19));
          mbar_arrive(bars + HB_IFULL + (n & 1) * 8);
        }
        if (type == IT_END) break;
        if (type != IT_XT) {
          const bool has_a = type == IT_OUT || type >= IT_F1;
          const uint8_t* ap = type == IT_OUT ? g_att + (size_t)mt * 64 * 16384 : type == IT_F1 ? g_h2 + (size_t)mt * 16 * 16384 : g_act + (size_t)mt * 56 * 16384;
          const int nkb = (type == IT_OUT ? 64 : type == IT_F2 ? 56 : 16) >> lgp;
          const uint32_t abytes = has_a ? (sz == 2 ? 32768 : 16384) : 0, bytes = (sz == 0 ? 32768 : 16384) + abytes;
          const int dk = sz == 2 ? 1 : 0;
          if (has_a) {
            const bool f1 = type == IT_F1;
            const int c0 = f1 ? idx * (128 >> sz) : idx * (256 >> sz);
            mbar_wait(bars + HB_EMPTY + st * 8, ph);
            if (elect_one()) {
              const uint32_t v = sb + H_VEC + (n & 1) * 3072, fb = bars + HB_FULL + st * 8;
              const uint32_t n0 = (f1 ? 2048 : 512) >> sz, n1 = f1 ? 1024 : n0;
              asm volatile("mbarrier.expect_tx.relaxed.cta.shared::cta.b64 [%0], %1;" :: "r"(fb), "r"(n0 + n1) : "memory");
              bulk_g2s(v, f1 ? (const void*)(g_uv + c0 * 4) : (const void*)(g_mod + (type == IT_OUT ? 2 : 5) * D_ + c0), n0, fb);
              bulk_g2s(v + (f1 ? 2048 : 512), f1 ? (const void*)(g_stat + mt * 256) : (const void*)(g_mod + 4 * D_ + c0), n1, fb);
            }
          }
#pragma unroll 1
          for (int kb = part * nkb; kb < (part + 1) * nkb; kb += 1 + dk) {
            const uint32_t d = sb + st * H_STAGE, fb = bars + HB_FULL + st * 8;
            mbar_wait(bars + HB_EMPTY + st * 8, ph);
            if (elect_one()) {
              mbar_expect(fb, bytes);
              if (has_a) bulk_g2s(d, ap + (size_t)kb * 16384, abytes, fb);
            }
            if (++st == H_NST) { st = 0; ph ^= 1; }
          }
        }
      }
    } else if (warp >= 10) {
      const int hb = warp - 10;
      uint32_t st = 0, ph = 1;
#pragma unroll 1
      for (uint32_t n = 0;; n++) {
        mbar_wait(bars + HB_IFULL + (n & 1) * 8, (n >> 1) & 1);
        const uint32_t it = __shfl_sync(0xffffffffu, lds32(bars + HB_ITEM + (n & 1) * 4), 0);
        const int type = it & 7, idx = (it >> 7) & 63, sz = (it >> 13) & 3, part = (it >> 15) & 3, lgp = (it >> 17) & 3;
        if (type == IT_END) break;
        if (elect_one()) mbar_arrive(bars + HB_IEMPTY + (n & 1) * 8);
        if (type == IT_XT) continue;
        const bool ffn1 = type == IT_F1 || type == IT_UV;
        const int nkb = (type == IT_OUT ? 64 : type == IT_F2 ? 56 : 16) >> lgp;
        const CUtensorMap* tb = type == IT_OUT ? &tmo : ffn1 ? &tm1 : type == IT_F2 ? &tm2 : &tmm;
        const CUtensorMap* tc = ffn1 ? &tm3 : tb;
        const int c0 = ffn1 ? idx * (128 >> sz) : idx * (256 >> sz) + (type == IT_MOD ? 2048 : 0), c2 = ffn1 ? c0 : c0 + 128;
        const int dk = sz == 2 ? 1 : 0;
        const CUtensorMap* t0 = hb == 1 && sz == 1 ? tc : tb;
        const int ca = hb == 0 || sz == 2 || (sz == 1 && ffn1) ? c0 : c0 + 64;
        const uint32_t off = (sz == 2 ? 32768 : 16384) + hb * 8192;
#pragma unroll 1
        for (int kb = part * nkb; kb < (part + 1) * nkb; kb += 1 + dk) {
          const uint32_t d = sb + st * H_STAGE + off, fb = bars + HB_FULL + st * 8;
          mbar_wait(bars + HB_EMPTY + st * 8, ph);
          if (elect_one()) {
            tma5d(d, t0, ca, kb + hb * dk, fb);
            if (sz == 0) tma5d(d + 16384, tc, c2 + hb * 64, kb, fb);
          }
          if (++st == H_NST) { st = 0; ph ^= 1; }
        }
      }
    } else if (warp == 9) {
#pragma unroll 1
      for (uint32_t n = 0;; n++) {
        mbar_wait(bars + HB_IFULL + (n & 1) * 8, (n >> 1) & 1);
        const uint32_t itq = lds32(bars + HB_ITEM + (n & 1) * 4);
        const int type = itq & 7, mt = (itq >> 3) & 15;
        if (type == IT_END) break;
        if (n & 1) bar_sync<3, 288>(); else bar_sync<2, 288>();
        if (lane == 0) {
          const uint32_t inc = lds32(bars + HB_INC + (n & 1) * 4);
          mbar_arrive(bars + HB_IEMPTY + (n & 1) * 8);
          if (inc) {
            fence_gpu();
            red_add_u32(&g_flags[type == IT_MOD ? FL_MOD : type == IT_UV ? FL_UV : (type == IT_XT ? FL_XT : type == IT_OUT ? FL_OUT : FL_F1) + 8 * mt], inc);
          }
        }
        __syncwarp();
      }
      asm volatile("griddepcontrol.wait;" ::: "memory");
      uint32_t k = 0;
      if (lane == 0) { fence_gpu(); k = atomicAdd(&g_flags[FL_EXIT], 1); }
      k = __shfl_sync(0xffffffffu, k, 0);
      if (k == gridDim.x - 1) {
        fence_gpu();
        for (int i = lane; i < 1024; i += 32) g_flags[i] = 0;
      }
    }
  } else {
    asm volatile("setmaxnreg.inc.sync.aligned.u32 232;");
    const int wg = warp >> 2;
    const bool leader = (tid & 127) == 0;
    uint32_t st = 0, ph = 0;
#pragma unroll 1
    for (uint32_t n = 0;; n++) {
      mbar_wait(bars + HB_IFULL + (n & 1) * 8, (n >> 1) & 1);
      const uint32_t itq = __shfl_sync(0xffffffffu, lds32(bars + HB_ITEM + (n & 1) * 4), 0);
      const int type = itq & 7, mt = (itq >> 3) & 15, idx = (itq >> 7) & 63, sz = (itq >> 13) & 3, part = (itq >> 15) & 3, lgp = (itq >> 17) & 3;
      uint32_t inc = type == IT_OUT ? 4 >> sz : type == IT_F1 ? 2 >> sz : type != IT_F2;
      if (type == IT_END) break;
      const uint32_t va = sb + H_VEC + (n & 1) * 3072;
      if (type == IT_OUT) {
        if (sz == 0) h_residual<256, false>(sb, va, mt, idx * 256, st, ph, warp, lane, out);
        else if (sz == 1) h_residual<128, false>(sb, va, mt, idx * 128, st, ph, warp, lane, out);
        else inc = h_residual<64, false>(sb, va, mt, idx * 64, st, ph, warp, lane, out, part, lgp);
      } else if (type == IT_F2) {
        if (sz == 0) h_residual<256, true>(sb, va, mt, idx * 256, st, ph, warp, lane, out);
        else if (sz == 1) h_residual<128, true>(sb, va, mt, idx * 128, st, ph, warp, lane, out);
        else h_residual<64, true>(sb, va, mt, idx * 64, st, ph, warp, lane, out, part, lgp);
      } else if (type == IT_XT) {
        const int rg = idx * 8 + warp;
        const uint32_t* xp = reinterpret_cast<const uint32_t*>(x + (size_t)(mt * 128 + rg * 8 + (lane >> 2)) * D_) + (lane & 3);
        uint8_t* tp = g_x1 + (size_t)mt * 262144 + rg * 1024 + (lane & 3) * 128 + (lane >> 2) * 16;
        if (lane < 16) g_stat[(mt * 128 + rg * 8) * 2 + lane] = 0.f;
#pragma unroll 1
        for (int b = 0; b < 2; b++) {
          uint32_t v[64];
#pragma unroll
          for (int i = 0; i < 64; i++) v[i] = __ldg(xp + 256 * b + 4 * i);
#pragma unroll
          for (int i = 0; i < 16; i++)
            *reinterpret_cast<uint4*>(tp + (8 * b + (i >> 1)) * 16384 + (i & 1) * 512) = make_uint4(v[4 * i], v[4 * i + 1], v[4 * i + 2], v[4 * i + 3]);
        }
      } else if (sz == 1) {
        float acc[64];
        h_mainloop<128, 0>(acc, sb, 16, st, ph, wg, leader);
        h_swiglu<128>(acc, va, mt, idx, warp, lane);
      } else {
        if (type != IT_F1) {
          bar_sync<1, 256>();
          for (int i = tid; i < D_; i += 256) {
            __nv_bfloat16* p = reinterpret_cast<__nv_bfloat16*>(smem + H_STG + (i >> 5) * 512 + ((i >> 1) & 3) * 128) + ((i >> 3) & 3) * 2 + (i & 1);
            if (type == IT_UV) { p[0] = __float2bfloat16(1.f); p[8] = __ldcg(g_mod + 4 * D_ + i); p[16] = __ldcg(g_mod + 3 * D_ + i); }
            else { const float c = __bfloat162float(cvec[i]); p[0] = __float2bfloat16(c / (1.f + __expf(-c))); }
          }
          fence_async_smem();
          bar_sync<1, 256>();
        }
        float acc[128];
        h_mainloop<256, 0>(acc, sb, 16, st, ph, wg, leader, type != IT_F1);
        if (type == IT_F1) {
          h_swiglu<256>(acc, va, mt, idx * 2, warp, lane);
        } else if (warp == 0) {
#pragma unroll
          for (int j = 0; j < 32; j++) {
            if (type == IT_MOD) {
              if (lane < 4) reinterpret_cast<uint32_t*>(g_mod + 2048 + idx * 256)[j * 4 + lane] = pack2(acc[4 * j], acc[4 * j + 1]);
            } else {
              const float a = acc[4 * j] + __shfl_down_sync(0xffffffffu, acc[4 * j], 4), b = acc[4 * j + 1] + __shfl_down_sync(0xffffffffu, acc[4 * j + 1], 4);
              float2* up = reinterpret_cast<float2*>(g_uv + idx * 512 + ((j & 15) * 4 + (lane & 3)) * 8 + (j >> 4) * 4);
              if (lane < 4) up[0] = make_float2(a, b);
              else if ((lane >> 2) == 2) up[1] = make_float2(acc[4 * j], acc[4 * j + 1]);
            }
          }
        }
      }
      HT(3);
      if (tid == 0) sts32(bars + HB_INC + (n & 1) * 4, inc);
      if (n & 1) bar_arrive<3, 288>(); else bar_arrive<2, 288>();
    }
  }
}

#define T_FIRST 35.f
#define T_UV 14.f
#define T_SLACK 2.f
#define T_PERIOD 13.4f
#define G_OUT "1111111111111124"
#define G_F1 "0000000000000001"
#define G_F2 "0000000011112233"
#define F2_LEAD 20.f
void build_list(HList& l) {
  int n = 0;
  auto add = [&](int type, int mt, int idx, int g) {
    const int sz = g > 2 ? 2 : g, lgp = g - sz;
    l.it[n++] = type | mt << 3 | (idx >> lgp) << 7 | sz << 13 | (idx & ((1 << lgp) - 1)) << 15 | lgp << 17;
  };
  for (int i = 0; i < 16; i++) add(IT_MOD, 0, i, 0);
  for (int i = 0; i < 32; i++) add(IT_XT, i >> 1, i & 1, 0);
  for (int i = 0; i < 28; i++) add(IT_UV, 0, i, 0);
  const char* gran[3] = {G_OUT, G_F1, G_F2};
  const float dur[3][5] = {{42.f, 22.f, 13.f, 9.f, 7.f}, {11.2f, 7.f, 0.f, 0.f, 0.f}, {37.f, 21.f, 11.5f, 8.f, 6.f}};
  const float t_end = T_FIRST + 15 * T_PERIOD - 1.5f;
  float fr[132];
  for (int i = 0; i < 132; i++) fr[i] = i < 8 ? T_FIRST : i < 36 ? T_FIRST + T_UV : t_end + 1.2f;
  float rdy[3][16];
  int mt[3] = {0, 0, 0}, ix[3] = {0, 0, 0};
  for (int m = 0; m < 16; m++) { rdy[0][m] = m < 15 ? T_FIRST + m * T_PERIOD : t_end; rdy[1][m] = rdy[2][m] = 0.f; }
  while (mt[2] < 16) {
    int w = 0;
    for (int i = 1; i < 132; i++) if (fr[i] < fr[w]) w = i;
    const float t = fr[w];
    int best = -1;
    float tb = 1e9f;
    const bool f2_first = gran[2][mt[2]] == '0' && t > t_end - F2_LEAD;
    const int order[3] = {0, f2_first ? 2 : 1, f2_first ? 1 : 2};
    for (int k = 0; k < 3; k++) {
      const int q = order[k];
      if (mt[q] >= 16 || (q > 0 && mt[q] >= mt[q - 1])) continue;
      const float ts = rdy[q][mt[q]] > t ? rdy[q][mt[q]] : t;
      if (ts < tb - T_SLACK) { tb = ts; best = q; }
    }
    const int m = mt[best], g = gran[best][m] - '0';
    add(best == 0 ? IT_OUT : best == 1 ? IT_F1 : IT_F2, m, ix[best], g);
    fr[w] = tb + dur[best][g];
    if (best < 2 && fr[w] + 0.5f > rdy[best + 1][m]) rdy[best + 1][m] = fr[w] + 0.5f;
    if (++ix[best] == (best == 1 ? 28 : 4) << g) { ix[best] = 0; mt[best]++; }
  }
  l.n = n;
}

typedef CUresult (*EncodeFn)(CUtensorMap*, CUtensorMapDataType, cuuint32_t, void*, const cuuint64_t*, const cuuint64_t*,
                             const cuuint32_t*, const cuuint32_t*, CUtensorMapInterleave, CUtensorMapSwizzle,
                             CUtensorMapL2promotion, CUtensorMapFloatOOBfill);

void make_map(EncodeFn fn, CUtensorMap* m, const void* p, uint64_t cols, uint64_t rows, uint32_t bc, uint32_t br, CUtensorMapSwizzle sw) {
  cuuint64_t dims[2] = {cols, rows};
  cuuint64_t strides[1] = {cols * 2};
  cuuint32_t box[2] = {bc, br};
  cuuint32_t es[2] = {1, 1};
  fn(m, CU_TENSOR_MAP_DATA_TYPE_BFLOAT16, 2, const_cast<void*>(p), dims, strides, box, es, CU_TENSOR_MAP_INTERLEAVE_NONE, sw,
     CU_TENSOR_MAP_L2_PROMOTION_L2_128B, CU_TENSOR_MAP_FLOAT_OOB_FILL_NONE);
}

void make_map_perm(EncodeFn fn, CUtensorMap* m, const void* p, uint64_t cols, uint64_t rows, bool perm) {
  cuuint64_t dims[5] = {cols, 2, 4, 4, rows / 32};
  cuuint64_t strides[4] = {cols * 2, cols * 2 * (perm ? 8 : 2), cols * 2 * (perm ? 2 : 8), cols * 2 * 32};
  cuuint32_t box[5] = {64, 2, 4, 4, 2};
  cuuint32_t es[5] = {1, 1, 1, 1, 1};
  fn(m, CU_TENSOR_MAP_DATA_TYPE_BFLOAT16, 5, const_cast<void*>(p), dims, strides, box, es, CU_TENSOR_MAP_INTERLEAVE_NONE,
     CU_TENSOR_MAP_SWIZZLE_128B, CU_TENSOR_MAP_L2_PROMOTION_L2_128B, CU_TENSOR_MAP_FLOAT_OOB_FILL_NONE);
}

}

extern "C" void kernel_launch(void* const* d_in, const int* in_sizes, int n_in, void* d_out, int out_size) {
  const __nv_bfloat16* x = (const __nv_bfloat16*)d_in[0];
  const __nv_bfloat16* mem0 = (const __nv_bfloat16*)d_in[1];
  const __nv_bfloat16* cvec = (const __nv_bfloat16*)d_in[11];
  static EncodeFn enc = nullptr;
  if (!enc) {
    cudaDriverEntryPointQueryResult qr;
    void* fp = nullptr;
    cudaGetDriverEntryPoint("cuTensorMapEncodeTiled", &fp, cudaEnableDefault, &qr);
    enc = (EncodeFn)fp;
    cudaFuncSetAttribute(kernel_R, cudaFuncAttributeMaxDynamicSharedMemorySize, R_SMEM);
    cudaFuncSetAttribute(kernel_H, cudaFuncAttributeMaxDynamicSharedMemorySize, H_SMEM);
  }
  CUtensorMap tmq, tmk, tmv, tmo, tmm;
  make_map(enc, &tmm, d_in[12], 6144, 1024, 64, 64, CU_TENSOR_MAP_SWIZZLE_NONE);
  make_map(enc, &tmq, d_in[2], 4096, 1024, 64, 64, CU_TENSOR_MAP_SWIZZLE_128B);
  make_map(enc, &tmk, d_in[3], 4096, 1024, 64, 64, CU_TENSOR_MAP_SWIZZLE_128B);
  make_map(enc, &tmv, d_in[4], 4096, 1024, 64, 64, CU_TENSOR_MAP_SWIZZLE_128B);
  make_map(enc, &tmo, d_in[5], 1024, 4096, 16, 128, CU_TENSOR_MAP_SWIZZLE_32B);
  RDesc dsc;
  for (int k = 0; k < 32; k++) {
    dsc.tok[k] = mkdesc(0x400 + (k < 16 ? R_GA : R_GB) + ((k & 15) >> 2) * 4096 + (k & 3) * 256, 128, 1024, 0);
    dsc.tail_a[k] = mkdesc(0x400 + R_TAIL + k * 2048, 1024, 1024, 1);
    if (k < 16) dsc.tail_b[k] = mkdesc(0x400 + R_GA + k * 256, 128, 4096, 0);
  }
  kernel_R<<<96, 256, R_SMEM, cudaStreamPerThread>>>(tmq, tmk, tmv, tmo, tmm, x, mem0, cvec, dsc);

  CUtensorMap ho, h1, h3, h2, hm;
  make_map_perm(enc, &ho, d_in[5], 1024, 4096, false);
  make_map_perm(enc, &h1, d_in[8], F_, 1024, true);
  make_map_perm(enc, &h3, d_in[9], F_, 1024, true);
  make_map_perm(enc, &h2, d_in[10], 1024, F_, true);
  make_map_perm(enc, &hm, d_in[12], 6144, 1024, true);
  HList list;
  build_list(list);
  cudaLaunchConfig_t cfg = {};
#define H_GRID 132
  cfg.gridDim = dim3(H_GRID); cfg.blockDim = dim3(384); cfg.dynamicSmemBytes = H_SMEM; cfg.stream = cudaStreamPerThread;
  cudaLaunchAttribute at[1];
  at[0].id = cudaLaunchAttributeProgrammaticStreamSerialization;
  at[0].val.programmaticStreamSerializationAllowed = 1;
  cfg.attrs = at;
  cfg.numAttrs = 1;
  cudaLaunchKernelEx(&cfg, kernel_H, ho, h1, h3, h2, hm, x, cvec, (__nv_bfloat16*)d_out, list);
}
```

```cpp
#include <cuda_runtime.h>
#include <cuda_bf16.h>
#include <cuda.h>
#include <stdint.h>
#include <type_traits>

namespace {

constexpr int S_ = 2048, D_ = 1024, NSEG = 64, F_ = 3584;

__device__ __align__(1024) uint8_t g_h[S_ * D_ * 2];
__device__ __align__(1024) uint8_t g_att[S_ * 4096 * 2];
__device__ __align__(1024) uint8_t g_x1[S_ * D_ * 2];
__device__ __align__(1024) uint8_t g_h2[S_ * D_ * 2];
__device__ __align__(1024) uint8_t g_act[S_ * F_ * 2];
__device__ __align__(1024) float g_ws[2 * 4 * 16 * 4 * 8192];
__device__ __align__(1024) float g_stat[S_ * 2];
__device__ __align__(1024) float g_uv[F_ * 4];
__device__ __align__(1024) float g_slot[4 * 3 * 8 * 4 * 32 * 4];
__device__ __align__(128) __nv_bfloat16 g_mod[6 * D_];
__device__ __align__(128) float g_modp[3 * 2 * D_];
__device__ __align__(128) uint32_t g_flags[1024];
constexpr int FL_S1 = 0, FL_S2 = 32, FL_MOD = 64, FL_HEAD = 96, FL_EXIT = 128, FL_UV = 160, FL_GO = 192, FL_MODB = 224, FL_ATT = 256, FL_XT = 384, FL_OUT = 512, FL_F1 = 640, FL_SPL = 768;

#define EVF 1
__device__ __forceinline__ uint32_t smem_u32(const void* p) { return (uint32_t)__cvta_generic_to_shared(p); }
__device__ __forceinline__ uint32_t mapa(uint32_t a, uint32_t r) { uint32_t o; asm("mapa.shared::cluster.u32 %0, %1, %2;" : "=r"(o) : "r"(a), "r"(r)); return o; }
__device__ __forceinline__ uint32_t pack2(float a, float b) { uint32_t r; asm("cvt.rn.bf16x2.f32 %0, %1, %2;" : "=r"(r) : "f"(b), "f"(a)); return r; }
__device__ __forceinline__ float bf_lo(uint32_t w) { return __uint_as_float(w << 16); }
__device__ __forceinline__ float bf_hi(uint32_t w) { return __uint_as_float(w & 0xffff0000u); }
__device__ __forceinline__ float ex2(float x) { float y; asm("ex2.approx.ftz.f32 %0, %1;" : "=f"(y) : "f"(x)); return y; }
__device__ __forceinline__ float rcp(float x) { float y; asm("rcp.approx.ftz.f32 %0, %1;" : "=f"(y) : "f"(x)); return y; }
__device__ __forceinline__ uint32_t clk32() { uint64_t c; asm volatile("mov.u64 %0, %%clock64;" : "=l"(c) :: "memory"); return (uint32_t)c; }

__device__ __forceinline__ void mbar_init(uint32_t b, uint32_t n) { asm volatile("mbarrier.init.shared::cta.b64 [%0], %1;" :: "r"(b), "r"(n) : "memory"); }
__device__ __forceinline__ void mbar_arrive(uint32_t b) { asm volatile("mbarrier.arrive.shared::cta.b64 _, [%0];" :: "r"(b) : "memory"); }
__device__ __forceinline__ void mbar_expect(uint32_t b, uint32_t n) { asm volatile("mbarrier.arrive.expect_tx.shared::cta.b64 _, [%0], %1;" :: "r"(b), "r"(n) : "memory"); }
__device__ __forceinline__ uint32_t mbar_try(uint32_t b, uint32_t par) {
  uint32_t ok;
  asm volatile("{\n.reg .pred p;\nmbarrier.try_wait.parity.shared::cta.b64 p, [%1], %2;\nselp.u32 %0, 1, 0, p;\n}" : "=r"(ok) : "r"(b), "r"(par) : "memory");
  return ok;
}
__device__ __forceinline__ void mbar_wait(uint32_t b, uint32_t par) {
  asm volatile("{\n.reg .pred p;\n"
               "LOOP:\n"
               "mbarrier.try_wait.parity.shared::cta.b64 p, [%0], %1;\n"
               "@!p bra.uni LOOP;\n}" :: "r"(b), "r"(par) : "memory");
}
__device__ __forceinline__ void mbar_wait_safe(uint32_t b, uint32_t par) {
  uint32_t c = 0;
  while (!mbar_try(b, par)) { if (++c > 4000000u) __trap(); }
}
__device__ __forceinline__ bool elect_one() {
  uint32_t p;
  asm volatile("{\n.reg .pred p;\nelect.sync _|p, 0xffffffff;\nselp.u32 %0, 1, 0, p;\n}" : "=r"(p));
  return p;
}
__device__ __forceinline__ void sched_fence(uint32_t x, uint32_t y) { asm volatile("{\n.reg .pred p;\nsetp.eq.u32 p, %0, %1;\n@p trap;\n}" :: "r"(x), "r"(y) : "memory"); }
template <class T> __device__ __forceinline__ T opaque32(T x) { asm volatile("" : "+r"(x)); return x; }
template <class T> __device__ __forceinline__ T opaque64(T x) { asm volatile("" : "+l"(x)); return x; }
template <int ID, int N> __device__ __forceinline__ void bar_sync() { asm volatile("bar.sync %0, %1;" :: "n"(ID), "n"(N) : "memory"); }
template <int ID, int N> __device__ __forceinline__ void bar_arrive() { asm volatile("bar.arrive %0, %1;" :: "n"(ID), "n"(N) : "memory"); }
__device__ __forceinline__ void fence_async_smem() { asm volatile("fence.proxy.async.shared::cta;" ::: "memory"); }
__device__ __forceinline__ void fence_async_all() { asm volatile("fence.proxy.async;" ::: "memory"); }
__device__ __forceinline__ void fence_gpu() { asm volatile("fence.acq_rel.gpu;" ::: "memory"); }
__device__ __forceinline__ void red_add_u32(uint32_t* p, uint32_t v) { asm volatile("red.relaxed.gpu.global.add.u32 [%0], %1;" :: "l"(p), "r"(v) : "memory"); }
__device__ __forceinline__ uint32_t ld_acquire(const uint32_t* p) { uint32_t v; asm volatile("ld.acquire.gpu.global.u32 %0, [%1];" : "=r"(v) : "l"(p) : "memory"); return v; }
__device__ __forceinline__ void wait_flag(const uint32_t* p, uint32_t target) {
  uint32_t c = 0;
  while (ld_acquire(p) < target) { if (++c > 20000000u) __trap(); __nanosleep(20); }
}

__device__ __forceinline__ void tma2d(uint32_t dst, const CUtensorMap* m, int c0, int c1, uint32_t bar) {
  asm volatile("cp.async.bulk.tensor.2d.shared::cluster.global.mbarrier::complete_tx::bytes [%0], [%1, {%3, %4}], [%2];"
               :: "r"(dst), "l"(m), "r"(bar), "r"(c0), "r"(c1) : "memory");
}
__device__ __forceinline__ void tma2d_once(uint32_t dst, const CUtensorMap* m, int c0, int c1, uint32_t bar) {
  asm volatile("{\n.reg .b64 pol;\ncreatepolicy.fractional.L2::evict_first.b64 pol, 1.0;\n"
               "cp.async.bulk.tensor.2d.shared::cluster.global.mbarrier::complete_tx::bytes.L2::cache_hint [%0], [%1, {%3, %4}], [%2], pol;\n}"
               :: "r"(dst), "l"(m), "r"(bar), "r"(c0), "r"(c1) : "memory");
}
__device__ __forceinline__ void tma5d(uint32_t dst, const CUtensorMap* m, int n0, int kb, uint32_t bar) {
  asm volatile("cp.async.bulk.tensor.5d.shared::cluster.global.mbarrier::complete_tx::bytes [%0], [%1, {%3, %5, %5, %5, %4}], [%2];"
               :: "r"(dst), "l"(m), "r"(bar), "r"(n0), "r"(2 * kb), "r"(0) : "memory");
}
__device__ __forceinline__ void tma2d_prefetch(const CUtensorMap* m, int c0, int c1) {
  asm volatile("cp.async.bulk.prefetch.tensor.2d.L2.global [%0, {%1, %2}];" :: "l"(m), "r"(c0), "r"(c1) : "memory");
}
__device__ __forceinline__ void bulk_g2s(uint32_t dst, const void* src, uint32_t bytes, uint32_t bar) {
  asm volatile("cp.async.bulk.shared::cluster.global.mbarrier::complete_tx::bytes [%0], [%1], %2, [%3];"
               :: "r"(dst), "l"(src), "r"(bytes), "r"(bar) : "memory");
}
__device__ __forceinline__ void bulk_s2s(uint32_t dst, uint32_t src, uint32_t bytes, uint32_t bar) {
  asm volatile("cp.async.bulk.shared::cluster.shared::cta.mbarrier::complete_tx::bytes [%0], [%1], %2, [%3];"
               :: "r"(dst), "r"(src), "r"(bytes), "r"(bar) : "memory");
}
__device__ __forceinline__ void st_async1(uint32_t dst, uint32_t a, uint32_t bar) {
  asm volatile("st.async.shared::cluster.mbarrier::complete_tx::bytes.b32 [%0], %1, [%2];" :: "r"(dst), "r"(a), "r"(bar) : "memory");
}
__device__ __forceinline__ void st_async2(uint32_t dst, uint32_t a, uint32_t b, uint32_t bar) {
  asm volatile("st.async.shared::cluster.mbarrier::complete_tx::bytes.v2.b32 [%0], {%1, %2}, [%3];" :: "r"(dst), "r"(a), "r"(b), "r"(bar) : "memory");
}
__device__ __forceinline__ void st_async4(uint32_t dst, const uint32_t* r, uint32_t bar) {
  asm volatile("st.async.shared::cluster.mbarrier::complete_tx::bytes.v4.b32 [%0], {%1, %2, %3, %4}, [%5];"
               :: "r"(dst), "r"(r[0]), "r"(r[1]), "r"(r[2]), "r"(r[3]), "r"(bar) : "memory");
}
__device__ __forceinline__ void sts32(uint32_t a, uint32_t v) { asm volatile("st.shared.b32 [%0], %1;" :: "r"(a), "r"(v) : "memory"); }
__device__ __forceinline__ void sts64(uint32_t a, uint32_t x, uint32_t y) { asm volatile("st.shared.v2.b32 [%0], {%1, %2};" :: "r"(a), "r"(x), "r"(y) : "memory"); }
__device__ __forceinline__ void sts128(uint32_t a, uint32_t x, uint32_t y, uint32_t z, uint32_t w) {
  asm volatile("st.shared.v4.b32 [%0], {%1, %2, %3, %4};" :: "r"(a), "r"(x), "r"(y), "r"(z), "r"(w) : "memory");
}
__device__ __forceinline__ void lds128(uint32_t* r, uint32_t a) {
  asm volatile("ld.shared.v4.b32 {%0, %1, %2, %3}, [%4];" : "=r"(r[0]), "=r"(r[1]), "=r"(r[2]), "=r"(r[3]) : "r"(a) : "memory");
}
__device__ __forceinline__ uint32_t lds32(uint32_t a) { uint32_t r; asm volatile("ld.shared.b32 %0, [%1];" : "=r"(r) : "r"(a) : "memory"); return r; }
__device__ __forceinline__ void lds64(uint32_t* r, uint32_t a) {
  asm volatile("ld.shared.v2.b32 {%0, %1}, [%2];" : "=r"(r[0]), "=r"(r[1]) : "r"(a) : "memory");
}
__device__ __forceinline__ void lds128f(float* r, uint32_t a) {
  asm volatile("ld.shared.v4.f32 {%0, %1, %2, %3}, [%4];" : "=f"(r[0]), "=f"(r[1]), "=f"(r[2]), "=f"(r[3]) : "r"(a) : "memory");
}
__device__ __forceinline__ void lds64f(float* r, uint32_t a) {
  asm volatile("ld.shared.v2.f32 {%0, %1}, [%2];" : "=f"(r[0]), "=f"(r[1]) : "r"(a) : "memory");
}
__device__ __forceinline__ void ldsm4(uint32_t* r, uint32_t a) {
  asm volatile("ldmatrix.sync.aligned.m8n8.x4.shared.b16 {%0, %1, %2, %3}, [%4];" : "=r"(r[0]), "=r"(r[1]), "=r"(r[2]), "=r"(r[3]) : "r"(a) : "memory");
}
__device__ __forceinline__ void ldsm4t(uint32_t* r, uint32_t a) {
  asm volatile("ldmatrix.sync.aligned.m8n8.x4.trans.shared.b16 {%0, %1, %2, %3}, [%4];" : "=r"(r[0]), "=r"(r[1]), "=r"(r[2]), "=r"(r[3]) : "r"(a) : "memory");
}
__device__ __forceinline__ void ldsm2(uint32_t* r, uint32_t a) {
  asm volatile("ldmatrix.sync.aligned.m8n8.x2.shared.b16 {%0, %1}, [%2];" : "=r"(r[0]), "=r"(r[1]) : "r"(a) : "memory");
}
__device__ __forceinline__ void stsm4(uint32_t a, const uint32_t* r) {
  asm volatile("stmatrix.sync.aligned.m8n8.x4.shared.b16 [%0], {%1, %2, %3, %4};" :: "r"(a), "r"(r[0]), "r"(r[1]), "r"(r[2]), "r"(r[3]) : "memory");
}
__device__ __forceinline__ uint32_t hadd2(uint32_t a, uint32_t b) { uint32_t t; asm("add.rn.bf16x2 %0, %1, %2;" : "=r"(t) : "r"(a), "r"(b)); return t; }
__device__ __forceinline__ uint32_t hmax2(uint32_t a, uint32_t b) { uint32_t t; asm("max.bf16x2 %0, %1, %2;" : "=r"(t) : "r"(a), "r"(b)); return t; }
__device__ __forceinline__ void ldsm2t(uint32_t* r, uint32_t a) {
  asm volatile("ldmatrix.sync.aligned.m8n8.x2.trans.shared.b16 {%0, %1}, [%2];" : "=r"(r[0]), "=r"(r[1]) : "r"(a) : "memory");
}
__device__ __forceinline__ uint32_t movm(uint32_t x) { uint32_t y; asm volatile("movmatrix.sync.aligned.m8n8.trans.b16 %0, %1;" : "=r"(y) : "r"(x)); return y; }
__device__ __forceinline__ void hmma(float* d, uint32_t a0, uint32_t a1, uint32_t a2, uint32_t a3, uint32_t b0, uint32_t b1) {
  asm volatile("mma.sync.aligned.m16n8k16.row.col.f32.bf16.bf16.f32 {%0,%1,%2,%3}, {%4,%5,%6,%7}, {%8,%9}, {%0,%1,%2,%3};"
               : "+f"(d[0]), "+f"(d[1]), "+f"(d[2]), "+f"(d[3]) : "r"(a0), "r"(a1), "r"(a2), "r"(a3), "r"(b0), "r"(b1));
}
__device__ __forceinline__ void hmma0(float* d, uint32_t a0, uint32_t a1, uint32_t a2, uint32_t a3, uint32_t b0, uint32_t b1) {
  asm volatile("mma.sync.aligned.m16n8k16.row.col.f32.bf16.bf16.f32 {%0,%1,%2,%3}, {%4,%5,%6,%7}, {%8,%9}, {%10,%10,%10,%10};"
               : "=f"(d[0]), "=f"(d[1]), "=f"(d[2]), "=f"(d[3]) : "r"(a0), "r"(a1), "r"(a2), "r"(a3), "r"(b0), "r"(b1), "f"(0.f));
}
__device__ __forceinline__ void hmma_k8(float* d, uint32_t a0, uint32_t a1, uint32_t b0) {
  asm volatile("mma.sync.aligned.m16n8k8.row.col.f32.bf16.bf16.f32 {%0,%1,%2,%3}, {%4,%5}, {%6}, {%0,%1,%2,%3};"
               : "+f"(d[0]), "+f"(d[1]), "+f"(d[2]), "+f"(d[3]) : "r"(a0), "r"(a1), "r"(b0));
}
__host__ __device__ constexpr uint64_t mkdesc(uint32_t addr, uint32_t lbo, uint32_t sbo, uint32_t sw) {
  return (uint64_t)((addr & 0x3FFFF) >> 4) | ((uint64_t)(lbo >> 4) << 16) | ((uint64_t)(sbo >> 4) << 32) | ((uint64_t)sw << 62);
}
#define WG_FENCE() asm volatile("wgmma.fence.sync.aligned;" ::: "memory")
#define WG_COMMIT() asm volatile("wgmma.commit_group.sync.aligned;" ::: "memory")
#define WG_WAIT(n) asm volatile("wgmma.wait_group.sync.aligned " #n ";" ::: "memory")
template <int N> __device__ __forceinline__ void reg_fence(float* d) {
#pragma unroll
  for (int i = 0; i < N; i++) asm volatile("" : "+f"(d[i]) :: "memory");
}
template <int N> __device__ __forceinline__ void zero_regs(float* d) {
#pragma unroll
  for (int i = 0; i < N; i++) asm volatile("mov.b32 %0, 0;" : "=f"(d[i]));
}
template <int SD>
__device__ __forceinline__ void wg_rs32(float* d, uint32_t a0, uint32_t a1, uint32_t a2, uint32_t a3, uint64_t b) {
  asm volatile("wgmma.mma_async.sync.aligned.m64n32k16.f32.bf16.bf16 {%0,%1,%2,%3,%4,%5,%6,%7,%8,%9,%10,%11,%12,%13,%14,%15}, {%16,%17,%18,%19}, %20, %21, 1, 1, 0;"
               : "+f"(d[0]), "+f"(d[1]), "+f"(d[2]), "+f"(d[3]), "+f"(d[4]), "+f"(d[5]), "+f"(d[6]), "+f"(d[7]),
                 "+f"(d[8]), "+f"(d[9]), "+f"(d[10]), "+f"(d[11]), "+f"(d[12]), "+f"(d[13]), "+f"(d[14]), "+f"(d[15])
               : "r"(a0), "r"(a1), "r"(a2), "r"(a3), "l"(b), "n"(SD));
}
template <int TB>
__device__ __forceinline__ void wg_ss40(float* d, uint64_t a, uint64_t b) {
  asm volatile("wgmma.mma_async.sync.aligned.m64n40k16.f32.bf16.bf16 {%0,%1,%2,%3,%4,%5,%6,%7,%8,%9,%10,%11,%12,%13,%14,%15,%16,%17,%18,%19}, %20, %21, 1, 1, 1, 1, %22;"
               : "+f"(d[0]), "+f"(d[1]), "+f"(d[2]), "+f"(d[3]), "+f"(d[4]), "+f"(d[5]), "+f"(d[6]), "+f"(d[7]),
                 "+f"(d[8]), "+f"(d[9]), "+f"(d[10]), "+f"(d[11]), "+f"(d[12]), "+f"(d[13]), "+f"(d[14]), "+f"(d[15]),
                 "+f"(d[16]), "+f"(d[17]), "+f"(d[18]), "+f"(d[19])
               : "l"(a), "l"(b), "n"(TB));
}
template <int T>
__device__ __forceinline__ void wg_ss32(float* d, uint64_t a, uint64_t b) {
  asm volatile("wgmma.mma_async.sync.aligned.m64n32k16.f32.bf16.bf16 {%0,%1,%2,%3,%4,%5,%6,%7,%8,%9,%10,%11,%12,%13,%14,%15}, %16, %17, 1, 1, 1, %18, %18;"
               : "+f"(d[0]), "+f"(d[1]), "+f"(d[2]), "+f"(d[3]), "+f"(d[4]), "+f"(d[5]), "+f"(d[6]), "+f"(d[7]),
                 "+f"(d[8]), "+f"(d[9]), "+f"(d[10]), "+f"(d[11]), "+f"(d[12]), "+f"(d[13]), "+f"(d[14]), "+f"(d[15])
               : "l"(a), "l"(b), "n"(T));
}

constexpr int R_TAIL = 0;
constexpr int R_WO = 65536;
constexpr int R_QK = R_WO + 86016;
constexpr int R_P = R_QK + 10240;
constexpr int R_GA = R_P + 6400;
constexpr int R_M2 = R_GA + 16384;
constexpr int R_M1 = R_M2 + 7168;
constexpr int R_GB = R_M1 + 9216;
constexpr int R_VT = R_GB + 16384;
constexpr int R_VM = R_VT + 8192;
constexpr int R_XS = R_VM + 2048;
constexpr int R_OX = R_XS + 1280;
constexpr int R_BAR = R_OX + 2048;
constexpr int R_TRC = R_BAR + 256;
constexpr int R_SMEM = R_TRC + 1024;
constexpr int B_MB = 0, B_XS = 32, B_VM = 40, B_VT = 48, B_TS = 56, B_FA = 64, B_FB = 72, B_TAIL = 80, B_WO = 88, B_STG = 96, B_WM = 128, B_X = 136;
constexpr int NB_A = 1, NB_B = 2, NB_X = 3, NB_C = 4, NB_D = 5, NB_E = 6, NB_F = 7, NB_G = 8, NB_H = 9, NB_S = 10, NB_E2 = 11, NB_P = 12, NB_W0 = 13;

#define POLL_DELAY 750
#define POLL_DELAY1 700
#define POLL_STAG 150
#define POLL_K0 20
#define PF1 2
#define PF2 2
#define PF3 2
#define PF4 0
#define CLR_D 2
#define PADN 0
#define PFD 0
#define GO_EARLY 0
#define RF_FIRST 1
#define BX_I 5
#define NCH 4
#define TOP2 0
#define CX_I 13
#define ATT_LATE 0
#define V_FENCE 1
#define SELF_STAS 1
#define Q_FENCE 1
#define ND_K 3
#define TRACE(i)
#define TS(i)

__device__ __forceinline__ int rot_chunk(int c, int rank) {
  int G = c;
  if (c < 9) { G = c + 3 * rank; if (G >= 9) G -= 9; }
  return G;
}
__device__ __forceinline__ int wo_tile(int i, int rank) {
  if (i < 12) return 12 * rank + i;
  const int r = i - 12 + 9 * rank;
  return r < 16 ? 48 + r : 20 + r;
}
__device__ __forceinline__ void load_chunk(uint32_t dst, int seg, int G, uint32_t bar) {
  mbar_expect(bar, 4096);
  bulk_g2s(dst, g_h + (size_t)(seg * 16 + G) * 4096, 4096, bar);
}
__device__ __forceinline__ void load_red(uint32_t* v, const float* p) {
#pragma unroll
  for (int j = 0; j < 2; j++)
    asm volatile("ld.relaxed.gpu.global.v4.u32 {%0, %1, %2, %3}, [%4];"
                 : "=r"(v[4 * j]), "=r"(v[4 * j + 1]), "=r"(v[4 * j + 2]), "=r"(v[4 * j + 3]) : "l"(p + j * 256) : "memory");
}
__device__ __forceinline__ bool red_done(const uint32_t* v) { return __all_sync(0xffffffffu, (v[3] & v[7]) == 0x42000000u); }
__device__ __forceinline__ uint32_t finish_red(uint32_t* v, const float* p) {
  uint32_t tries = 0;
  if (__builtin_expect(!red_done(v), 0)) {
    do { if (++tries > 20000000u) __trap(); load_red(v, p); } while (!red_done(v));
  }
  return tries;
}
__device__ __forceinline__ void exp10(float* sv, const uint32_t* x) {
  constexpr float SC = 0.08838834764831845f * 1.4426950408889634f;
  uint32_t m2 = hmax2(hmax2(hmax2(x[0], x[1]), hmax2(x[2], x[3])), x[4]);
  m2 = hmax2(m2, __shfl_xor_sync(0xffffffffu, m2, 1));
  m2 = hmax2(m2, __shfl_xor_sync(0xffffffffu, m2, 2));
  const float nm = -fmaxf(bf_lo(m2), bf_hi(m2)) * SC;
#pragma unroll
  for (int j = 0; j < 5; j++) { sv[2 * j] = ex2(fmaf(bf_lo(x[j]), SC, nm)); sv[2 * j + 1] = ex2(fmaf(bf_hi(x[j]), SC, nm)); }
}

__device__ __forceinline__ uint32_t arm_size(int w, bool isC) {
  return w == 0 ? (isC ? 1280 : 640) : w == 1 ? (isC ? 0 : 2048) : w == 2 ? (isC ? 0 : 8192) : (isC ? 0 : 1792);
}
struct RDesc { uint64_t tok[32], tail_b[16], tail_a[32]; };

template <int WG>
__device__ __forceinline__ void r_main(const uint32_t (&W)[48][4], const RDesc& dsc, int head, uint32_t rank, int lane_, int w) {
  const uint32_t sb = (rank << 24) + 0x400, bars = sb + R_BAR;
  const uint32_t to1 = rank == 0 ? 2u << 24 : 0u - (1u << 24), to2 = rank == 2 ? 0u - (2u << 24) : 1u << 24;
  const bool isC = rank == 2;
  const int lane = opaque32(lane_), warp = WG * 4 + w;
  const int gl = rot_chunk(4 * (lane & 3) + w, rank);
  const int g0 = __shfl_sync(0xffffffffu, gl, 0), g1 = __shfl_sync(0xffffffffu, gl, 1), g2 = __shfl_sync(0xffffffffu, gl, 2);
  const uint32_t arm_bytes = arm_size(w, isC);

#define L16 opaque32(sb + opaque32(lane) * 16)
#define L8 opaque32(sb + opaque32(lane) * 8)
#define L4 opaque32(sb + opaque32(lane) * 4)
#define LV opaque32(sb + R_VT + ((opaque32(lane) >> 3) & 1) * 512 + (opaque32(lane) >> 4) * 128 + (opaque32(lane) & 7) * 16)
#define SLOT(st) opaque64(slot0 + ((st) & 3) * 12288 + ((st) & 4) * 32)
  float* const slot0 = opaque64(g_slot + (rank * 1024 + warp * 128 + lane) * 4);
  const uint32_t woa = opaque32(sb + R_WO + warp * 12288 + ((lane >> 4) * 8 + (lane & 7)) * 32 + ((((lane >> 3) ^ (lane >> 2)) & 1) << 4));
  const bool has_wo = WG == 0 || isC || w < 3;
  float acc[20];
  uint32_t pk[8] = {0u, 0u, 0u, 0u, 0u, 0u, 0u, 0u};

  auto forward = [&](auto rd, const uint32_t* v, int st, uint32_t tries) {
    constexpr int RD = decltype(rd)::value;
    uint32_t u[6];
#pragma unroll
    for (int j = 0; j < 6; j++) u[j] = movm(v[4 * (j / 3) + j % 3]);
    const bool all3 = RD == 0 || w < 3;
    if (RD == 0) {
      const uint32_t a = L16 + R_M1 + w * 768, a2 = L8 + R_M1 + 512 + w * 768;
      st_async4(a + to1 + 3072, u, bars + to1 + B_MB + 8); st_async2(a2 + to1 + 3072, u[4], u[5], bars + to1 + B_MB + 8);
      sts128(a, u[0], u[1], u[2], u[3]); sts64(a2, u[4], u[5]);
      __syncwarp();
      if (elect_one()) mbar_arrive(bars + B_MB);
      st_async4(a + to2 + 6144, u, bars + to2 + B_MB + 16); st_async2(a2 + to2 + 6144, u[4], u[5], bars + to2 + B_MB + 16);
    } else {
      const uint32_t a = L4 + R_M2 + rank * 2304 + w * 768;
#pragma unroll
      for (int j = 0; j < 6; j++) if (j < 2 || all3) st_async1(a + to1 + j * 128, u[j], bars + to1 + B_MB + 24);
#pragma unroll
      for (int j = 0; j < 6; j++) if (j < 2 || all3) st_async1(a + to2 + j * 128, u[j], bars + to2 + B_MB + 24);
      if (SELF_STAS) {
#pragma unroll
        for (int j = 0; j < 6; j++) if (j < 2 || all3) st_async1(a + j * 128, u[j], bars + B_MB + 24);
      } else {
#pragma unroll
        for (int j = 0; j < 6; j++) if (j < 2 || all3) sts32(a + j * 128, u[j]);
        __syncwarp();
        if (elect_one()) mbar_arrive(bars + B_MB + 24);
      }
    }
  };

  auto send_vt = [&]() {
    if (elect_one()) {
      const uint32_t src = sb + R_VT + warp * 1024;
      bulk_s2s(src + to1, src, 1024, bars + to1 + B_VT);
      bulk_s2s(src + to2, src, 1024, bars + to2 + B_VT);
    }
  };
  auto store_att = [&](int sg) {
    uint32_t* op = reinterpret_cast<uint32_t*>(g_att + (size_t)((sg >> 2) * 64 + head * 2 + rank) * 16384 + (2 * w * 16 + (sg & 3) * 4) * 128) + opaque32(lane);
#pragma unroll
    for (int j = 0; j < 8; j++) op[(j & 1) * 512 + (j >> 1) * 32] = pk[j];
  };

  if (WG == 0) bar_arrive<NB_G, 256>();
#pragma unroll 1
  for (int s = -1; s < NSEG; s++) {
    const uint32_t par = (s + 1) & 1;
    const uint32_t last = s == NSEG - 1;
    TRACE(0);
    {
      float c[NCH][4];
      uint32_t b[3][6];
      const uint32_t ma = L16, m8 = L8;
#pragma unroll
      for (int i = 0; i < 18; i++) {
        if (i < 16) {
          if (i % 4 == 0 && !(i == 4 && TOP2)) mbar_wait(bars + B_MB + (i / 4) * 8, par ^ 1);
          if (i == 0 && TOP2) mbar_wait(bars + B_MB + 8, par ^ 1);
          if (i % 4 == 0) TRACE(1 + i / 4);
          if (i < 12) { lds128(b[i % 3], ma + R_M1 + i * 768); lds64(b[i % 3] + 4, m8 + R_M1 + 512 + i * 768); }
          else { ldsm4(b[i % 3], ma + R_M2 + 4096 + (i - 12) * 768); ldsm2(b[i % 3] + 4, ma + R_M2 + 4096 + 512 + (i - 12) * 768); }
          if (WG == 1 && i == BX_I) {
            bar_sync<NB_G, 256>();
            if (!last && elect_one()) load_chunk(sb + R_GB + w * 4096, s + 1, g0, bars + B_FB);
          }
          if (i == CX_I) {
            if (isC && s >= 0) send_vt();
            if (WG == 1 && ATT_LATE && !isC && s > 0) store_att(s - 1);
          }
          __syncwarp();
        }
        if (i >= 2) {
          const int j = i - 2;
#pragma unroll
          for (int q = 0; q < 3; q++) {
            const uint32_t* f = W[3 * j + q];
            if (3 * j + q < NCH) hmma0(c[3 * j + q], f[0], f[1], f[2], f[3], b[j % 3][2 * q], b[j % 3][2 * q + 1]);
            else hmma(c[(3 * j + q) % NCH], f[0], f[1], f[2], f[3], b[j % 3][2 * q], b[j % 3][2 * q + 1]);
          }
        }
        if (i == 14) zero_regs<16>(acc);
        if (i == 16) mbar_wait(bars + B_FA, last);
      }
#pragma unroll
      for (int j = 0; j < 4; j++) acc[16 + j] = NCH == 3 ? (c[0][j] + c[1][j]) + c[2][j] : (c[0][j] + c[1][j]) + (c[2][j] + c[NCH - 1][j]);
    }
    TRACE(5);
    bar_sync<NB_H, 256>();
    WG_FENCE();
#pragma unroll
    for (int k = 0; k < 16; k++) wg_ss40<0>(acc, dsc.tail_a[WG * 16 + k], dsc.tail_b[k]);
    WG_COMMIT();
    uint32_t vt[4][4];
    {
      const uint32_t a = opaque32(L4 + w * 256 + (isC ? WG * 1024 + R_VM : R_QK + 4096 + WG * 5120));
      const uint32_t qa = L16 + R_QK, xa = opaque32(LV + w * 2048 + (WG == 0 ? 0 : (opaque32(lane) & 8) * 64 + R_QK + 5120 - R_VT));
      const uint32_t d = opaque32(L4 + R_XS + rank * 640 + w * 256);
      if (s == 0) {
        mbar_wait_safe(bars + B_WO, 0);
        if (!GO_EARLY && WG == 1 && head == 0 && rank == 0 && w == 0 && elect_one()) red_add_u32(&g_flags[FL_GO], 1);
      }
      mbar_wait(bars + B_FB, last);
      if (WG == 0) mbar_wait(bars + B_VT, par);
      WG_WAIT(0);
      reg_fence<20>(acc);
      TRACE(6);
      const uint32_t p0 = pack2(acc[16], acc[17]), p1 = pack2(acc[18], acc[19]);
      sts32(a, p0); sts32(a + 128, p1);
      if (isC) {
        st_async1(a + to1, p0, bars + B_VM + to1); st_async1(a + to1 + 128, p1, bars + B_VM + to1);
        st_async1(a + to2, p0, bars + B_VM + to2); st_async1(a + to2 + 128, p1, bars + B_VM + to2);
      }
      if (WG == 0) {
        bar_arrive<NB_A, 256>();
        if (Q_FENCE && !isC) fence_async_smem();
#pragma unroll
        for (int i = 0; i < 4; i++) ldsm4(vt[i], xa + (i >> 1) * 1024 + (i & 1) * 256);
        bar_sync<NB_S, 256>();
      } else {
        bar_sync<NB_A, 256>();
        if (!isC) {
          if (w < 3) {
            uint32_t q[8], k[4][4];
            ldsm4t(q, qa + 4096); ldsm4t(k[0], xa); ldsm4t(k[1], xa + 256);
            ldsm4t(q + 4, qa + 4096 + 512); ldsm4t(k[2], xa + 512); ldsm4t(k[3], xa + 768);
            float x[4], y[4];
            hmma0(x, k[0][0], k[0][1], k[0][2], k[0][3], q[0], q[1]); hmma0(y, k[1][0], k[1][1], k[1][2], k[1][3], q[2], q[3]);
            hmma(x, k[2][0], k[2][1], k[2][2], k[2][3], q[4], q[5]); hmma(y, k[3][0], k[3][1], k[3][2], k[3][3], q[6], q[7]);
            const uint32_t s0 = pack2(x[0] + y[0], x[1] + y[1]), s1 = pack2(x[2] + y[2], x[3] + y[3]);
            st_async1(d + to1, s0, bars + B_XS + to1);
            st_async1(d + to2, s0, bars + B_XS + to2);
            if (w < 2) { st_async1(d + to1 + 128, s1, bars + B_XS + to1); st_async1(d + to2 + 128, s1, bars + B_XS + to2); sts32(d + 128, s1); }
            sts32(d, s0);
          }
        }
        bar_arrive<NB_S, 256>();
      }
    }
    if (WG == 1) {
      if (!last && elect_one()) load_chunk(sb + R_GA + w * 4096, s + 1, g1, bars + B_FA);
      {
        if (w > 0 && elect_one()) mbar_expect(bars + B_MB + 8 * w, w < 3 ? 3072 : SELF_STAS ? 28 * 256 : isC ? 18 * 256 : 19 * 256);
      }
      fence_async_smem();
      bar_sync<NB_B, 256>();
    }
    TRACE(7);
    WG_FENCE();
#pragma unroll
    for (int k = 0; k < 16; k++) wg_rs32<1>(acc, W[k][0], W[k][1], W[k][2], W[k][3], dsc.tok[16 + k]);
    WG_COMMIT();
    uint32_t wa[3][4];
    const uint32_t oxa = L16 + R_OX;
    if (WG == 0) {
      const uint32_t vma = oxa - (R_OX - R_VM) + w * 512, oa = opaque32(L4 + w * 512 + R_OX);
      TRACE(8);
      mbar_wait(bars + B_XS, par);
      TRACE(9);
      float sv[10];
      {
        uint32_t x[10];
        ldsm4t(x, oxa - (R_OX - R_XS)); ldsm4t(x + 4, oxa - (R_OX - R_XS) + 512); ldsm2t(x + 8, oxa - (R_OX - R_XS) + 1024);
        bar_arrive<NB_B, 256>();
#pragma unroll
        for (int j = 0; j < 5; j++) x[j] = hadd2(x[j], x[j + 5]);
        exp10(sv, x);
      }
      WG_WAIT(0);
      bar_arrive<NB_X, 256>();
      mbar_wait(bars + B_VM, par);
      uint32_t vm[4];
      ldsm4(vm, vma);
      uint32_t pb[5];
#pragma unroll
      for (int j = 0; j < 5; j++) pb[j] = pack2(sv[2 * j], sv[2 * j + 1]);
      TRACE(10);
      float o0[4], o1[4], sm[4];
      const uint32_t ONE = 0x3f803f80u;
      hmma0(o0, vt[0][0], vt[0][1], vt[0][2], vt[0][3], pb[0], pb[1]);
      hmma0(o1, vt[2][0], vt[2][1], vt[2][2], vt[2][3], pb[0], pb[1]);
      hmma0(sm, ONE, ONE, ONE, ONE, pb[0], pb[1]);
      hmma(sm, ONE, ONE, ONE, ONE, pb[2], pb[3]);
      hmma(o0, vt[1][0], vt[1][1], vt[1][2], vt[1][3], pb[2], pb[3]);
      hmma(o1, vt[3][0], vt[3][1], vt[3][2], vt[3][3], pb[2], pb[3]);
      hmma_k8(sm, ONE, ONE, pb[4]);
      hmma_k8(o0, vm[0], vm[1], pb[4]);
      hmma_k8(o1, vm[2], vm[3], pb[4]);
#pragma unroll
      for (int i = 0; i < 3; i++) ldsm4t(wa[i], woa + i * 4096);
      __syncwarp();
      const float i0 = rcp(sm[0]), i1 = rcp(sm[1]);
      sts32(oa, pack2(o0[0] * i0, o0[1] * i1)); sts32(oa + 128, pack2(o0[2] * i0, o0[3] * i1));
      sts32(oa + 256, pack2(o1[0] * i0, o1[1] * i1)); sts32(oa + 384, pack2(o1[2] * i0, o1[3] * i1));
      TRACE(11);
      bar_sync<NB_C, 128>();
    } else {
      if (!isC) {
        constexpr uint64_t dQ = mkdesc(0x400 + R_QK, 128, 1024, 0), dK = mkdesc(0x400 + R_QK + 5120, 128, 1024, 0);
        float sc[16];
        zero_regs<16>(sc);
        WG_FENCE();
#pragma unroll
        for (int k = 0; k < 4; k++) wg_ss32<1>(sc, dK + k * 16, dQ + k * 16);
        WG_COMMIT();
        const uint32_t top = rank == 0 ? to2 : to1, e = L4 + R_P + w * 256;
        WG_WAIT(0);
        bar_sync<NB_X, 256>();
        if (!last && elect_one()) load_chunk(sb + R_GB + w * 4096, s + 1, g2, bars + B_FB);
        reg_fence<16>(sc);
        if (w < 3) {
#pragma unroll
          for (int j = 0; j < 8; j++) {
            if ((j & 1) ? (j > 1 && (w == 0 || (w == 1 && j == 7))) : (j >= 4 || w != 1)) {
              const uint32_t t = pack2(sc[2 * j], sc[2 * j + 1]), o = (j >> 1) * 768 + (j & 1) * 128;
              st_async1(e + top + 3072 + o, t, bars + top + B_TS);
              sts32(e + o, t);
            }
          }
          __syncwarp();
          if (elect_one()) mbar_arrive(bars + B_TS);
        }
      } else {
        WG_WAIT(0);
        bar_sync<NB_X, 256>();
        if (!last && elect_one()) load_chunk(sb + R_GB + w * 4096, s + 1, g2, bars + B_FB);
      }
      TRACE(8);
      mbar_wait(bars + B_FA, 1);
      TRACE(11);
    }
    if (has_wo) {
      float* rslot = SLOT(s);
      uint32_t ob[4][4];
      float c[3][4];
      if (WG == 1) {
#pragma unroll
        for (int i = 0; i < 3; i++) ldsm4t(wa[i], woa + i * 4096);
        bar_sync<NB_D, 256>();
      }
      ldsm4t(ob[0], oxa);
      __syncwarp();
#pragma unroll
      for (int k = 0; k < 8; k++) {
        uint32_t nx[3][4];
        if ((k & 1) == 0 && k < 6) { ldsm4t(ob[(k >> 1) + 1], oxa + ((k >> 1) + 1) * 512); __syncwarp(); }
#pragma unroll
        for (int i = 0; i < 3; i++) {
          const uint32_t* o = ob[k >> 1] + (k & 1) * 2;
          if (k < 7) { ldsm4t(nx[i], woa + i * 4096 + (k + 1) * 512); if (i == 2) __syncwarp(); }
          if (k == 0) hmma0(c[i], wa[i][0], wa[i][1], wa[i][2], wa[i][3], o[0], o[1]);
          else hmma(c[i], wa[i][0], wa[i][1], wa[i][2], wa[i][3], o[0], o[1]);
#pragma unroll
          for (int q = 0; q < 4; q++) if (k < 7) wa[i][q] = nx[i][q];
        }
        if (k == ND_K && WG == 0) bar_arrive<NB_D, 256>();
      }
      const float* cv = &c[0][0];
      uint32_t r[6];
#pragma unroll
      for (int j = 0; j < 6; j++) r[j] = pack2(cv[2 * j], cv[2 * j + 1]);
      asm volatile("{\n.reg .pred p;\nsetp.lt.s32 p, %8, 0;\n@p bra.uni SKIP;\n"
                   "red.relaxed.gpu.global.add.noftz.v4.bf16x2 [%0], {%1, %2, %3, %7};\n"
                   "red.relaxed.gpu.global.add.noftz.v4.bf16x2 [%0+1024], {%4, %5, %6, %7};\nSKIP:\n}"
                   :: "l"(rslot), "r"(r[0]), "r"(r[1]), "r"(r[2]), "r"(r[3]), "r"(r[4]), "r"(r[5]), "r"(0x3f800000), "r"(s) : "memory");
    } else {
      bar_arrive<NB_D, 256>();
      if ((s & 3) == 0) {
        fence_gpu();
        if (s > 0 && elect_one()) red_add_u32(&g_flags[FL_ATT + 2 * (s - 4)], 1);
      }
      if (PFD && head < 8 && (PFD > 90 || s + PFD < NSEG) && elect_one())
        asm volatile("cp.async.bulk.prefetch.L2.global [%0], 4096;" :: "l"(g_h + (size_t)((PFD > 90 ? 0 : s + PFD) * 16 + head * 2 + rank) * 4096) : "memory");
      if (rank == 0 || head < 16)
        reinterpret_cast<uint4*>(g_slot)[((s + CLR_D) & 3) * 3072 + ((s + CLR_D) & 4) * 8 + rank * 2048 + head * 64 + opaque32(lane)] = make_uint4(0, 0, 0, 0);
    }
    const uint32_t t_red = clk32();
    uint32_t v[8];
    const float* slot = SLOT(s);
    TRACE(13);
    if (WG == 0) {
      if (!isC) {
        const int ln = opaque32(lane), kg = w - (ln >> 3);
        const uint32_t r16 = sb + R_P + w * 768 + (ln & 7) * 16;
        const uint32_t ta = r16 + (kg >= 0 ? kg * 128 : 640);
        const int dg = (ln >> 2) - 2 * (ln & 3);
        const uint32_t keep = dg > 0 ? 0xffffffffu : dg == 0 ? 0x0000ffffu : 0u;
        mbar_wait(bars + B_TS, par);
        uint32_t x[6], y[4];
        ldsm4t(x, ta); ldsm4t(y, ta + 3072); ldsm2t(x + 4, r16 + 512 + ((ln >> 3) & 1) * 3072);
#pragma unroll
        for (int j = 0; j < 5; j++) x[j] = hadd2(x[j], j < 4 ? y[j] : x[5]);
        x[0] = (x[0] & keep) | (0xff80ff80u & ~keep);
        float sv[10];
        exp10(sv, x);
        float sum = (((sv[0] + sv[1]) + (sv[2] + sv[3])) + ((sv[4] + sv[5]) + (sv[6] + sv[7]))) + (sv[8] + sv[9]);
        sum += __shfl_xor_sync(0xffffffffu, sum, 1);
        sum += __shfl_xor_sync(0xffffffffu, sum, 2);
        const float inv = rcp(sum);
#pragma unroll
        for (int j = 0; j < 5; j++) x[j] = pack2(sv[2 * j] * inv, sv[2 * j + 1] * inv);
        stsm4(r16 + (kg & 3) * 128, x);
        sts32(sb + ln * 4 + w * 768 + R_P + 512, x[4]);
        fence_async_smem();
        bar_arrive<NB_P, 256>();
      }
      while (clk32() - t_red < POLL_DELAY) {}
      load_red(v, slot);
      bar_sync<NB_E, 256>();
    } else {
      mbar_wait(bars + B_FB, 1);
    }
    TRACE(14);
    float ao[16];
    if (WG == 1) zero_regs<16>(ao);
    WG_FENCE();
#pragma unroll
    for (int k = 0; k < 32; k++) {
      if (WG == 0 && k == 16) WG_COMMIT();
      wg_rs32<1>(acc, W[16 + k][0], W[16 + k][1], W[16 + k][2], W[16 + k][3], dsc.tok[k]);
    }
    WG_COMMIT();
    TRACE(12);
    if (WG == 1) {
      if (!isC) {
        constexpr uint64_t dP = mkdesc(0x400 + R_P, 128, 768, 0);
        const uint64_t dV = mkdesc(0x400 + R_VT, 128, 512, 0) + rank * 256, dM = mkdesc(0x400 + R_VM, 0, 128, 0) + rank * 64;
        bar_sync<NB_P, 256>();
        WG_FENCE();
        wg_ss32<0>(ao, dV, dP); wg_ss32<0>(ao, dV + 16, dP + 16); wg_ss32<0>(ao, dM, dP + 32);
        WG_COMMIT();
      }
      bar_arrive<NB_E, 256>();
      if (elect_one()) mbar_expect(bars + B_XS + 8 * w, arm_bytes);
      while (clk32() - t_red < POLL_DELAY1) {}
      load_red(v, slot);
      bar_arrive<NB_W0, 128>();
    } else {
      WG_WAIT(1);
      bar_arrive<NB_F, 256>();
      sched_fence(head, 100);
      v[3] = opaque32(v[3]);
      const uint32_t tries = finish_red(v, slot);
      forward(std::integral_constant<int, 0>(), v, s, tries);
      TRACE(16);
    }
    WG_WAIT(0);
    reg_fence<16>(acc);
    if (WG == 0) bar_arrive<NB_G, 256>();
    TRACE(15);
    {
      uint32_t pq[8];
#pragma unroll
      for (int j = 0; j < 8; j++) pq[j] = pack2(acc[2 * j], acc[2 * j + 1]);
      if (WG == 1) {
        reg_fence<16>(ao);
#pragma unroll
        for (int j = 0; j < 8; j++) pk[j] = pack2(ao[2 * j], ao[2 * j + 1]);
      }
      if (!isC) {
        const uint32_t q = L4 + w * 256 + R_QK + WG * 5120;
#pragma unroll
        for (int j = 0; j < 8; j++) sts32(q + (j >> 1) * 1024 + (j & 1) * 128, pq[j]);
        if (WG == 1 && !ATT_LATE && s >= 0) store_att(s);
      } else {
        const uint32_t a = LV + warp * 1024;
        stsm4(a, pq); stsm4(a + 256, pq + 4);
      }
    }
    TRACE(17);
    if (WG == 1) {
      auto refill = [&]() {
        bar_sync<NB_F, 256>();
        if (s < NSEG - 2 && elect_one()) load_chunk(sb + R_GA + w * 4096, s + 2, 12 + w, bars + B_FA);
      };
      if (RF_FIRST) refill();
      if (has_wo) { v[3] = opaque32(v[3]); const uint32_t tries = finish_red(v, slot); forward(std::integral_constant<int, 1>(), v, s, tries); }
      if (!RF_FIRST) refill();
      TRACE(16);
    }
    if (isC && V_FENCE) { fence_async_smem(); __syncwarp(); }
    TRACE(18);
  }
  if (WG == 1 && ATT_LATE && !isC) store_att(NSEG - 1);
  if (WG == 1) bar_sync<NB_G, 256>();
  mbar_wait_safe(bars + B_MB + 8, 0); mbar_wait_safe(bars + B_MB + 16, 0); mbar_wait_safe(bars + B_MB + 24, 0);
#undef L16
#undef L8
#undef L4
#undef SLOT
#undef LV
}

__global__ void __cluster_dims__(3, 1, 1) __launch_bounds__(256, 1)
kernel_R(const __grid_constant__ CUtensorMap tmq, const __grid_constant__ CUtensorMap tmk, const __grid_constant__ CUtensorMap tmv,
         const __grid_constant__ CUtensorMap tmo, const __grid_constant__ CUtensorMap tmm, const __nv_bfloat16* __restrict__ x,
         const __nv_bfloat16* __restrict__ mem0, const __nv_bfloat16* __restrict__ cvec, const __grid_constant__ RDesc dsc) {
  extern __shared__ __align__(1024) uint8_t smem[];
  const uint32_t sb = smem_u32(smem);
  uint32_t rank; asm("mov.u32 %0, %%cluster_ctarank;" : "=r"(rank));
  rank = __shfl_sync(0xffffffffu, rank, 0);
  const int cta = blockIdx.x, head = __shfl_sync(0xffffffffu, cta / 3, 0);
  const int tid = threadIdx.x, lane = tid & 31;
  const int warp = __shfl_sync(0xffffffffu, tid >> 5, 0);
  const int wg = warp >> 2, w = warp & 3;
  const uint32_t bars = sb + R_BAR;
  const CUtensorMap* tmw = rank == 2 ? &tmv : (wg == 0 ? &tmq : &tmk);
  const int fcol = head * 128 + (rank == 2 ? wg * 64 : (int)rank * 64);

  asm volatile("griddepcontrol.launch_dependents;");
  uint32_t W[48][4];
  {
    if (sb != (rank << 24) + 0x400) __trap();
    if (tid == 0) {
      sts64(bars + 248, rank, head);
      mbar_init(bars + B_MB, 4); mbar_init(bars + B_MB + 8, 1); mbar_init(bars + B_MB + 16, 1); mbar_init(bars + B_MB + 24, SELF_STAS ? 1 : rank == 2 ? 5 : 4);
      for (int i = B_XS; i <= B_X; i += 8) mbar_init(bars + i, i == B_FA || i == B_FB || (i == B_TS && rank < 2) ? 4 : 1);
      asm volatile("fence.mbarrier_init.release.cluster;" ::: "memory");
      fence_async_smem();
    }
    __syncthreads();
    asm volatile("barrier.cluster.arrive.relaxed.aligned;" ::: "memory");
    TS(0);
    const int nwm = rank == 0 ? 6 : 5, wm0 = rank == 0 ? 0 : 5 * rank + 1, nrg = cta < 64 ? 3 : 2;
    if (elect_one()) {
      if (warp == 0) { mbar_expect(bars + B_WM, nwm * 8192); mbar_expect(bars + B_X, nrg * 16384); }
      if (warp < nwm) tma2d_once(sb + R_GA + warp * 8192, &tmm, head * 64, (wm0 + warp) * 64, bars + B_WM);
#pragma unroll 1
      for (int r = 0; r < nrg; r++) bulk_g2s(sb + R_TAIL + (r * 8 + warp) * 2064, x + (size_t)((cta + 96 * r) * 8 + warp) * D_, 2048, bars + B_X);
      if (w == 0) mbar_expect(bars + B_STG + wg * 16, 49152);
      if (w < 2) tma2d_once(sb + R_WO + wg * 49152 + w * 8192, tmw, fcol, rot_chunk(w, rank) * 64, bars + B_STG + wg * 16);
    }
    float* scr = reinterpret_cast<float*>(smem + R_VT);
#pragma unroll 1
    for (int i = tid; i < nwm * 64; i += 256) {
      const float c = __bfloat162float(cvec[wm0 * 64 + i]);
      scr[i] = __bfloat162float(__float2bfloat16(c / (1.f + __expf(-c))));
    }
    if (tid < 128) {
      uint32_t e[4] = {0u, 0u, 0u, 0u};
      if (cta >= 72 && (tid & 32)) {
        const uint16_t* mp = reinterpret_cast<const uint16_t*>(mem0) + 2 * (lane & 3) * D_ + (lane >> 2);
#pragma unroll
        for (int q = 0; q < 3; q++) {
          const int n = 3 * (tid >> 6) + q, col = wo_tile(3 * (cta & 7) + (n >> 1), (cta - 72) >> 3) * 16 + 8 * (n & 1);
          e[q] = mp[col] | (uint32_t)mp[col + D_] << 16;
        }
        e[3] = 0x42000000u;
      }
      reinterpret_cast<uint4*>(g_slot)[cta * 128 + tid] = make_uint4(e[0], e[1], e[2], e[3]);
    }
    __syncthreads();
    TS(1);
    mbar_wait_safe(bars + B_WM, 0);
    if (elect_one()) tma2d_once(sb + R_WO + wg * 49152 + (2 + w) * 8192, tmw, fcol, rot_chunk(2 + w, rank) * 64, bars + B_STG + wg * 16);
    {
      float a[8];
#pragma unroll
      for (int j = 0; j < 8; j++) a[j] = 0.f;
#pragma unroll 2
      for (int i = 0; i < 2 * nwm; i++) {
        uint32_t u[4];
        lds128(u, sb + R_GA + i * 4096 + tid * 16);
        const float sc = scr[i * 32 + (tid >> 3)];
#pragma unroll
        for (int j = 0; j < 4; j++) { a[2 * j] += sc * bf_lo(u[j]); a[2 * j + 1] += sc * bf_hi(u[j]); }
      }
#pragma unroll
      for (int j = 0; j < 8; j++) { a[j] += __shfl_xor_sync(0xffffffffu, a[j], 8); a[j] += __shfl_xor_sync(0xffffffffu, a[j], 16); }
      if (lane < 8) {
        sts128(sb + R_VT + 1536 + warp * 256 + lane * 32, __float_as_uint(a[0]), __float_as_uint(a[1]), __float_as_uint(a[2]), __float_as_uint(a[3]));
        sts128(sb + R_VT + 1552 + warp * 256 + lane * 32, __float_as_uint(a[4]), __float_as_uint(a[5]), __float_as_uint(a[6]), __float_as_uint(a[7]));
      }
    }
    __syncthreads();
    TS(2);
    if (warp == 7) {
      float t0 = 0.f, t1 = 0.f;
#pragma unroll
      for (int i = 0; i < 8; i++) { float t[2]; lds64f(t, sb + R_VT + 1536 + i * 256 + lane * 8); t0 += t[0]; t1 += t[1]; }
      reinterpret_cast<float2*>(g_modp + rank * 2048 + head * 64)[lane] = make_float2(t0, t1);
      fence_gpu();
      __syncwarp();
      if (lane == 0) red_add_u32(&g_flags[FL_S1], 1);
      __syncwarp();
    }
    mbar_wait_safe(bars + B_X, 0);
#pragma unroll 1
    for (int r = 0; r < nrg; r++) {
      float f[32];
#pragma unroll
      for (int i = 0; i < 4; i++) {
        uint32_t u[4];
        lds128(u, sb + R_TAIL + (r * 8 + warp) * 2064 + i * 512 + lane * 16);
#pragma unroll
        for (int j = 0; j < 4; j++) { f[8 * i + 2 * j] = bf_lo(u[j]); f[8 * i + 2 * j + 1] = bf_hi(u[j]); }
      }
      float t = 0.f;
#pragma unroll
      for (int i = 0; i < 32; i++) t += f[i];
#pragma unroll
      for (int o = 1; o < 32; o <<= 1) t += __shfl_xor_sync(0xffffffffu, t, o);
      const float mean = t * (1.f / D_);
      t = 0.f;
#pragma unroll
      for (int i = 0; i < 32; i++) t = fmaf(f[i] - mean, f[i] - mean, t);
#pragma unroll
      for (int o = 1; o < 32; o <<= 1) t += __shfl_xor_sync(0xffffffffu, t, o);
      const float rstd = rsqrtf(t * (1.f / D_) + 1e-5f);
      if (lane == 0) sts64(sb + R_VT + 3584 + (r * 8 + warp) * 8, __float_as_uint(rstd), __float_as_uint(-mean * rstd));
    }
    TS(3);
    if (w < PF1 && elect_one()) tma2d_prefetch(tmw, fcol, rot_chunk(6 + w, rank) * 64);
    if (tid == 0) wait_flag(&g_flags[FL_S1], 96);
    __syncthreads();
    TS(4);
    {
      float4 p[6];
#pragma unroll
      for (int i = 0; i < 6; i++) p[i] = __ldcg(reinterpret_cast<const float4*>(g_modp + (i >> 1) * 2048) + 2 * tid + (i & 1));
      if (w < PF2 && elect_one()) tma2d_prefetch(tmw, fcol, (9 + w) * 64);
      sts128(sb + R_VT + 5120 + tid * 16, pack2(p[0].x + p[2].x + p[4].x, p[0].y + p[2].y + p[4].y), pack2(p[0].z + p[2].z + p[4].z, p[0].w + p[2].w + p[4].w),
             pack2(p[1].x + p[3].x + p[5].x, p[1].y + p[3].y + p[5].y), pack2(p[1].z + p[3].z + p[5].z, p[1].w + p[3].w + p[5].w));
    }
    __syncthreads();
#pragma unroll 2
    for (int it = 0; it < 4 * nrg; it++) {
      const int r = it >> 2, rg = cta + 96 * r, c = 16 * warp + (lane >> 3) + 4 * (it & 3);
      uint32_t a[4], b[4], u[4], o[4];
      float t[2];
      lds128(u, sb + R_TAIL + (r * 8 + (lane & 7)) * 2064 + c * 16);
      lds128(a, sb + R_VT + 5120 + c * 16); lds128(b, sb + R_VT + 7168 + c * 16);
      lds64f(t, sb + R_VT + 3584 + (r * 8 + (lane & 7)) * 8);
#pragma unroll
      for (int j = 0; j < 4; j++)
        o[j] = pack2(fmaf(fmaf(bf_lo(u[j]), t[0], t[1]), 1.f + bf_lo(b[j]), bf_lo(a[j])), fmaf(fmaf(bf_hi(u[j]), t[0], t[1]), 1.f + bf_hi(b[j]), bf_hi(a[j])));
      *reinterpret_cast<uint4*>(g_h + (size_t)(rg >> 2) * 65536 + (lane & 7) * 16 + (c & 7) * 128 +
                                (c < 96 ? (c >> 3) * 4096 + (rg & 3) * 1024 : 49152 + (rg & 3) * 4096 + ((c >> 3) - 12) * 1024)) =
          make_uint4(o[0], o[1], o[2], o[3]);
    }
    TS(5);
    __syncthreads();
    TS(6);
    if (w < PF3 && elect_one()) tma2d_once(sb + R_TAIL + warp * 8192, tmw, fcol, 768 + w * 64, bars + B_TAIL);
    if (warp == 3 && lane == 0) { fence_gpu(); red_add_u32(&g_flags[FL_S2], 1); }
    __syncwarp();

    const uint32_t a0 = opaque32(sb + R_WO + wg * 49152 + ((lane >> 4) * 8 + (lane & 7)) * 128 + (((2 * w + ((lane >> 3) & 1)) ^ (lane & 7)) << 4));
    mbar_wait_safe(bars + B_STG + wg * 16, 0);
    TS(7);
#pragma unroll
    for (int i = 0; i < 24; i++) ldsm4t(W[i], a0 + i * 2048);
    if (tid == 0) wait_flag(&g_flags[FL_S2], 96);
    __syncthreads();
    asm volatile("fence.proxy.async.global;" ::: "memory");
    if (elect_one()) {
      if (wg == 0) load_chunk(sb + R_GA + w * 4096, 0, 12 + w, bars + B_FA);
      if (w == 0) mbar_expect(bars + B_STG + wg * 16 + 8, 49152);
#pragma unroll 1
      for (int c = w; c < 6; c += 4) tma2d_once(sb + R_WO + wg * 49152 + c * 8192, tmw, fcol, rot_chunk(6 + c, rank) * 64, bars + B_STG + wg * 16 + 8);
      if (warp == 0) mbar_expect(bars + B_TAIL, 65536);
      if (w >= PF3) tma2d_once(sb + R_TAIL + warp * 8192, tmw, fcol, 768 + w * 64, bars + B_TAIL);
      if (wg == 1) mbar_expect(bars + B_XS + 8 * w, w == 2 ? 0 : arm_size(w, rank == 2));
#pragma unroll 1
      for (int i = warp; i < PF4; i += 8) tma2d_prefetch(&tmo, 16 * wo_tile(i, rank), head * 128);
    }
    TS(8);
    mbar_wait_safe(bars + B_STG + wg * 16 + 8, 0);
    TS(9);
#pragma unroll
    for (int i = 0; i < 24; i++) ldsm4t(W[24 + i], a0 + i * 2048);
    __syncthreads();
    if (elect_one()) {
      const int n = rank == 2 ? 22 : 21;
      if (warp == 0) mbar_expect(bars + B_WO, n * 4096);
#pragma unroll 1
      for (int i = warp; i < n; i += 8) tma2d(sb + R_WO + i * 4096, &tmo, 16 * wo_tile(i, rank), head * 128, bars + B_WO);
    }
    sts32(sb + R_P + warp * 768 + 640 + lane * 4, wg == 0 ? 0u : 0xff80ff80u);
    mbar_wait_safe(bars + B_TAIL, 0);
    if (GO_EARLY && cta == GO_EARLY - 1 && tid == 0) red_add_u32(&g_flags[FL_GO], 1);
    asm volatile("barrier.cluster.wait.aligned;\nbarrier.cluster.arrive.relaxed.aligned;\nbarrier.cluster.wait.aligned;" ::: "memory");
  }
  uint32_t rh[2];
  lds64(rh, bars + 248);
  rh[0] = __shfl_sync(0xffffffffu, rh[0], 0); rh[1] = __shfl_sync(0xffffffffu, rh[1], 0);
  if (wg == 0) r_main<0>(W, dsc, rh[1], rh[0], lane, w);
  else r_main<1>(W, dsc, rh[1], rh[0], lane, w);
  __syncthreads();
  if (rank < 2 && threadIdx.x == 0) { fence_gpu(); red_add_u32(&g_flags[FL_ATT + 8 * 15], 1); }
  asm volatile("barrier.cluster.arrive.release.aligned;\nbarrier.cluster.wait.acquire.aligned;" ::: "memory");
}

template <int TA> __device__ __forceinline__ void wg_ss256(float* d, uint64_t a, uint64_t b) {
  asm volatile("wgmma.mma_async.sync.aligned.m64n256k16.f32.bf16.bf16 {%0,%1,%2,%3,%4,%5,%6,%7,%8,%9,%10,%11,%12,%13,%14,%15,%16,%17,%18,%19,%20,%21,%22,%23,%24,%25,%26,%27,%28,%29,%30,%31,%32,%33,%34,%35,%36,%37,%38,%39,%40,%41,%42,%43,%44,%45,%46,%47,%48,%49,%50,%51,%52,%53,%54,%55,%56,%57,%58,%59,%60,%61,%62,%63,%64,%65,%66,%67,%68,%69,%70,%71,%72,%73,%74,%75,%76,%77,%78,%79,%80,%81,%82,%83,%84,%85,%86,%87,%88,%89,%90,%91,%92,%93,%94,%95,%96,%97,%98,%99,%100,%101,%102,%103,%104,%105,%106,%107,%108,%109,%110,%111,%112,%113,%114,%115,%116,%117,%118,%119,%120,%121,%122,%123,%124,%125,%126,%127}, %128, %129, 1, 1, 1, %130, 1;"
               : "+f"(d[0]), "+f"(d[1]), "+f"(d[2]), "+f"(d[3]), "+f"(d[4]), "+f"(d[5]), "+f"(d[6]), "+f"(d[7]),
                 "+f"(d[8]), "+f"(d[9]), "+f"(d[10]), "+f"(d[11]), "+f"(d[12]), "+f"(d[13]), "+f"(d[14]), "+f"(d[15]),
                 "+f"(d[16]), "+f"(d[17]), "+f"(d[18]), "+f"(d[19]), "+f"(d[20]), "+f"(d[21]), "+f"(d[22]), "+f"(d[23]),
                 "+f"(d[24]), "+f"(d[25]), "+f"(d[26]), "+f"(d[27]), "+f"(d[28]), "+f"(d[29]), "+f"(d[30]), "+f"(d[31]),
                 "+f"(d[32]), "+f"(d[33]), "+f"(d[34]), "+f"(d[35]), "+f"(d[36]), "+f"(d[37]), "+f"(d[38]), "+f"(d[39]),
                 "+f"(d[40]), "+f"(d[41]), "+f"(d[42]), "+f"(d[43]), "+f"(d[44]), "+f"(d[45]), "+f"(d[46]), "+f"(d[47]),
                 "+f"(d[48]), "+f"(d[49]), "+f"(d[50]), "+f"(d[51]), "+f"(d[52]), "+f"(d[53]), "+f"(d[54]), "+f"(d[55]),
                 "+f"(d[56]), "+f"(d[57]), "+f"(d[58]), "+f"(d[59]), "+f"(d[60]), "+f"(d[61]), "+f"(d[62]), "+f"(d[63]),
                 "+f"(d[64]), "+f"(d[65]), "+f"(d[66]), "+f"(d[67]), "+f"(d[68]), "+f"(d[69]), "+f"(d[70]), "+f"(d[71]),
                 "+f"(d[72]), "+f"(d[73]), "+f"(d[74]), "+f"(d[75]), "+f"(d[76]), "+f"(d[77]), "+f"(d[78]), "+f"(d[79]),
                 "+f"(d[80]), "+f"(d[81]), "+f"(d[82]), "+f"(d[83]), "+f"(d[84]), "+f"(d[85]), "+f"(d[86]), "+f"(d[87]),
                 "+f"(d[88]), "+f"(d[89]), "+f"(d[90]), "+f"(d[91]), "+f"(d[92]), "+f"(d[93]), "+f"(d[94]), "+f"(d[95]),
                 "+f"(d[96]), "+f"(d[97]), "+f"(d[98]), "+f"(d[99]), "+f"(d[100]), "+f"(d[101]), "+f"(d[102]), "+f"(d[103]),
                 "+f"(d[104]), "+f"(d[105]), "+f"(d[106]), "+f"(d[107]), "+f"(d[108]), "+f"(d[109]), "+f"(d[110]), "+f"(d[111]),
                 "+f"(d[112]), "+f"(d[113]), "+f"(d[114]), "+f"(d[115]), "+f"(d[116]), "+f"(d[117]), "+f"(d[118]), "+f"(d[119]),
                 "+f"(d[120]), "+f"(d[121]), "+f"(d[122]), "+f"(d[123]), "+f"(d[124]), "+f"(d[125]), "+f"(d[126]), "+f"(d[127])
               : "l"(a), "l"(b), "n"(TA));
}
template <int TA> __device__ __forceinline__ void wg_ss128(float* d, uint64_t a, uint64_t b) {
  asm volatile("wgmma.mma_async.sync.aligned.m64n128k16.f32.bf16.bf16 {%0,%1,%2,%3,%4,%5,%6,%7,%8,%9,%10,%11,%12,%13,%14,%15,%16,%17,%18,%19,%20,%21,%22,%23,%24,%25,%26,%27,%28,%29,%30,%31,%32,%33,%34,%35,%36,%37,%38,%39,%40,%41,%42,%43,%44,%45,%46,%47,%48,%49,%50,%51,%52,%53,%54,%55,%56,%57,%58,%59,%60,%61,%62,%63}, %64, %65, 1, 1, 1, %66, 1;"
               : "+f"(d[0]), "+f"(d[1]), "+f"(d[2]), "+f"(d[3]), "+f"(d[4]), "+f"(d[5]), "+f"(d[6]), "+f"(d[7]),
                 "+f"(d[8]), "+f"(d[9]), "+f"(d[10]), "+f"(d[11]), "+f"(d[12]), "+f"(d[13]), "+f"(d[14]), "+f"(d[15]),
                 "+f"(d[16]), "+f"(d[17]), "+f"(d[18]), "+f"(d[19]), "+f"(d[20]), "+f"(d[21]), "+f"(d[22]), "+f"(d[23]),
                 "+f"(d[24]), "+f"(d[25]), "+f"(d[26]), "+f"(d[27]), "+f"(d[28]), "+f"(d[29]), "+f"(d[30]), "+f"(d[31]),
                 "+f"(d[32]), "+f"(d[33]), "+f"(d[34]), "+f"(d[35]), "+f"(d[36]), "+f"(d[37]), "+f"(d[38]), "+f"(d[39]),
                 "+f"(d[40]), "+f"(d[41]), "+f"(d[42]), "+f"(d[43]), "+f"(d[44]), "+f"(d[45]), "+f"(d[46]), "+f"(d[47]),
                 "+f"(d[48]), "+f"(d[49]), "+f"(d[50]), "+f"(d[51]), "+f"(d[52]), "+f"(d[53]), "+f"(d[54]), "+f"(d[55]),
                 "+f"(d[56]), "+f"(d[57]), "+f"(d[58]), "+f"(d[59]), "+f"(d[60]), "+f"(d[61]), "+f"(d[62]), "+f"(d[63])
               : "l"(a), "l"(b), "n"(TA));
}
template <int TA> __device__ __forceinline__ void wg_ss64(float* d, uint64_t a, uint64_t b) {
  asm volatile("wgmma.mma_async.sync.aligned.m64n64k16.f32.bf16.bf16 {%0,%1,%2,%3,%4,%5,%6,%7,%8,%9,%10,%11,%12,%13,%14,%15,%16,%17,%18,%19,%20,%21,%22,%23,%24,%25,%26,%27,%28,%29,%30,%31}, %32, %33, 1, 1, 1, %34, 1;"
               : "+f"(d[0]), "+f"(d[1]), "+f"(d[2]), "+f"(d[3]), "+f"(d[4]), "+f"(d[5]), "+f"(d[6]), "+f"(d[7]),
                 "+f"(d[8]), "+f"(d[9]), "+f"(d[10]), "+f"(d[11]), "+f"(d[12]), "+f"(d[13]), "+f"(d[14]), "+f"(d[15]),
                 "+f"(d[16]), "+f"(d[17]), "+f"(d[18]), "+f"(d[19]), "+f"(d[20]), "+f"(d[21]), "+f"(d[22]), "+f"(d[23]),
                 "+f"(d[24]), "+f"(d[25]), "+f"(d[26]), "+f"(d[27]), "+f"(d[28]), "+f"(d[29]), "+f"(d[30]), "+f"(d[31])
               : "l"(a), "l"(b), "n"(TA));
}

constexpr int H_STAGE = 49152, H_NST = 4;
constexpr int H_STG = H_NST * H_STAGE;
constexpr int H_VEC = H_STG + 16384;
constexpr int H_BAR = H_VEC + 6144;
constexpr int H_SMEM = H_BAR + 256;
constexpr int HB_FULL = 0, HB_EMPTY = 32, HB_IFULL = 64, HB_IEMPTY = 80, HB_ITEM = 96, HB_INC = 104;
enum { IT_END = 0, IT_MOD = 1, IT_XT = 2, IT_OUT = 3, IT_UV = 4, IT_F1 = 5, IT_F2 = 6 };
constexpr int MAX_ITEMS = 1400;
#define D_MOD 4
#define D_UV 2
#define N_UV1 20
#define XT_GO 0
struct HList { uint32_t n; uint32_t it[MAX_ITEMS]; };
#define HT(i)

template <int BN, int TA>
__device__ __forceinline__ void h_mainloop(float* acc, uint32_t sb, int nst, uint32_t& st, uint32_t& ph, int wg, bool leader, bool fixed_a = false) {
  constexpr int KS = BN == 64 ? 8 : 4;
  constexpr uint32_t BOFF = BN == 64 ? 32768 : 16384;
  const uint64_t da0 = fixed_a ? mkdesc(sb + H_STG, 128, 0, 0) : TA ? mkdesc(sb + wg * 1024, 2048, 128, 0) : mkdesc(sb + wg * 8192, 128, 1024, 0);
  const uint64_t db0 = mkdesc(sb + BOFF, 8192, 1024, 1);
  uint32_t prev = 0;
  zero_regs<BN / 2>(acc);
  if (fixed_a && wg == 1) {
#pragma unroll 1
    for (int i = 0; i < nst; i++) {
      mbar_wait(sb + H_BAR + HB_FULL + st * 8, ph);
      if (leader) mbar_arrive(sb + H_BAR + HB_EMPTY + st * 8);
      if (++st == H_NST) { st = 0; ph ^= 1; }
    }
    return;
  }
#pragma unroll 1
  for (int i = 0; i < nst; i++) {
    mbar_wait(sb + H_BAR + HB_FULL + st * 8, ph);
    const uint64_t da = da0 + (fixed_a ? i * 64 : st * (H_STAGE >> 4)), db = db0 + st * (H_STAGE >> 4);
    WG_FENCE();
#pragma unroll
    for (int k = 0; k < KS; k++) {
      const uint64_t a = da + (k >> 2) * 1024 + (k & 3) * (TA ? 256 : 16), b = db + k * 128;
      if (BN == 256) wg_ss256<TA>(acc, a, b); else if (BN == 128) wg_ss128<TA>(acc, a, b); else wg_ss64<TA>(acc, a, b);
    }
    WG_COMMIT();
    WG_WAIT(1);
    if (i > 0 && leader) mbar_arrive(sb + H_BAR + HB_EMPTY + prev * 8);
    prev = st;
    if (++st == H_NST) { st = 0; ph ^= 1; }
  }
  WG_WAIT(0);
  HT(2);
  reg_fence<BN / 2>(acc);
  if (leader) mbar_arrive(sb + H_BAR + HB_EMPTY + prev * 8);
}

template <int BN, bool FINAL>
__device__ __forceinline__ bool h_residual(uint32_t sb, uint32_t va, int mt, int n0, uint32_t& st, uint32_t& ph, int warp, int lane, __nv_bfloat16* out,
                                           int part = 0, int lgp = 0) {
  const size_t toff = (size_t)(mt * 16 + (n0 >> 6)) * 16384 + warp * 2048 + (lane & 3) * 128 + (lane >> 2) * 16;
  uint4 r[BN / 16];
#pragma unroll
  for (int i = 0; i < BN / 16; i++) r[i] = __ldcg(reinterpret_cast<const uint4*>(g_x1 + toff + (i >> 2) * 16384 + ((i >> 1) & 1) * 512 + (i & 1) * 1024));
  float acc[BN / 2];
  h_mainloop<BN, FINAL ? 0 : 1>(acc, sb, ((FINAL ? 56 : 64) / (BN == 64 ? 2 : 1)) >> lgp, st, ph, warp >> 2, (warp & 3) == 0 && lane == 0);
  if (BN == 64 && lgp > 0) {
    const int tile = (FINAL * 4 + (mt & 3)) * 16 + (n0 >> 6);
    float4* ws = reinterpret_cast<float4*>(g_ws) + (size_t)tile * 8192 + warp * 32 + lane;
#pragma unroll
    for (int i = 0; i < 8; i++) ws[part * 2048 + i * 256] = make_float4(acc[4 * i], acc[4 * i + 1], acc[4 * i + 2], acc[4 * i + 3]);
    bar_sync<1, 256>();
    if (warp == 0 && lane == 0) { fence_gpu(); const uint32_t t = atomicAdd(&g_flags[FL_SPL + tile], 1); fence_gpu(); sts32(sb + H_BAR + HB_INC + 8, t); }
    bar_sync<1, 256>();
    if (lds32(sb + H_BAR + HB_INC + 8) != (1u << lgp) - 1) return false;
#pragma unroll 1
    for (int p = 1; p < (1 << lgp); p++) {
      float4 o[8];
#pragma unroll
      for (int i = 0; i < 8; i++) o[i] = __ldcg(ws + (part ^ p) * 2048 + i * 256);
#pragma unroll
      for (int i = 0; i < 8; i++) { acc[4 * i] += o[i].x; acc[4 * i + 1] += o[i].y; acc[4 * i + 2] += o[i].z; acc[4 * i + 3] += o[i].w; }
    }
  }
  float sm[4] = {0.f, 0.f, 0.f, 0.f};
  const uint32_t stg = sb + H_STG + warp * 2048;
#pragma unroll
  for (int c = 0; c < BN / 32; c++) {
    uint32_t y[2][4] = {{r[2 * c].x, r[2 * c].y, r[2 * c].z, r[2 * c].w}, {r[2 * c + 1].x, r[2 * c + 1].y, r[2 * c + 1].z, r[2 * c + 1].w}}, z[2][4];
#pragma unroll
    for (int j = 0; j < 4; j++) {
      const uint32_t gt = lds32(va + c * 64 + j * 16 + (lane & 3) * 4);
      const uint32_t cb = FINAL ? 0 : lds32(va + 512 + c * 64 + j * 16 + (lane & 3) * 4);
#pragma unroll
      for (int h = 0; h < 2; h++) {
        const float* a = acc + c * 16 + j * 4 + h * 2;
        y[h][j] = pack2(fmaf(bf_lo(gt), a[0], bf_lo(y[h][j])), fmaf(bf_hi(gt), a[1], bf_hi(y[h][j])));
        if (!FINAL) {
          const float p = bf_lo(y[h][j]), q = bf_hi(y[h][j]);
          sm[2 * h] += p + q;
          sm[2 * h + 1] = fmaf(p, p, fmaf(q, q, sm[2 * h + 1]));
          z[h][j] = pack2(fmaf(p, bf_lo(cb), p), fmaf(q, bf_hi(cb), q));
        }
      }
    }
    if (!FINAL) {
#pragma unroll
      for (int h = 0; h < 2; h++) {
        const size_t o = toff + (c >> 1) * 16384 + (c & 1) * 512 + h * 1024;
        *reinterpret_cast<uint4*>(g_x1 + o) = make_uint4(y[h][0], y[h][1], y[h][2], y[h][3]);
        *reinterpret_cast<uint4*>(g_h2 + o) = make_uint4(z[h][0], z[h][1], z[h][2], z[h][3]);
      }
    } else {
#pragma unroll
      for (int h = 0; h < 2; h++) stsm4(stg + (h * 8 + (lane & 7)) * 128 + ((((c & 1) * 4 + (lane >> 3)) ^ (lane & 7)) << 4), y[h]);
      if (c & 1) {
        __syncwarp();
#pragma unroll
        for (int j = 0; j < 4; j++) {
          const int rr = 4 * j + (lane >> 3);
          uint32_t v[4];
          lds128(v, stg + rr * 128 + (((lane & 7) ^ (rr & 7)) << 4));
          *reinterpret_cast<uint4*>(out + (size_t)(mt * 128 + warp * 16 + rr) * D_ + n0 + (c >> 1) * 64 + (lane & 7) * 8) = make_uint4(v[0], v[1], v[2], v[3]);
        }
        __syncwarp();
      }
    }
  }
  if (!FINAL) {
#pragma unroll
    for (int j = 0; j < 4; j++) { sm[j] += __shfl_xor_sync(0xffffffffu, sm[j], 1); sm[j] += __shfl_xor_sync(0xffffffffu, sm[j], 2); }
    const int t = lane & 3;
    atomicAdd(g_stat + (mt * 128 + warp * 16 + (t >> 1) * 8 + (lane >> 2)) * 2 + (t & 1), t == 0 ? sm[0] : t == 1 ? sm[1] : t == 2 ? sm[2] : sm[3]);
  }
  return true;
}

__device__ __forceinline__ float silu_mul(float g, float u) {
  float t; asm("tanh.approx.f32 %0, %1;" : "=f"(t) : "f"(0.5f * g));
  const float h = 0.5f * g * u;
  return fmaf(h, t, h);
}

template <int BN>
__device__ __forceinline__ void h_swiglu(const float* acc, uint32_t va, int mt, int kb0, int warp, int lane) {
  uint8_t* ap = g_act + (size_t)(mt * 56 + kb0) * 16384 + warp * 2048 + (lane & 3) * 128 + (lane >> 2) * 16;
  float rs[2], nm[2];
#pragma unroll
  for (int h = 0; h < 2; h++) {
    float t[2];
    lds64f(t, va + 2048 + (warp * 16 + h * 8 + (lane >> 2)) * 8);
    const float mean = t[0] * (1.f / D_);
    rs[h] = rsqrtf(fmaxf(t[1] * (1.f / D_) - mean * mean, 0.f) + 1e-5f);
    nm[h] = -mean * rs[h];
  }
#pragma unroll
  for (int c = 0; c < BN / 64; c++) {
    uint32_t y[2][4];
#pragma unroll
    for (int j = 0; j < 4; j++) {
      const float* g = acc + 16 * c + 4 * j; const float* u = g + BN / 4;
      float p[4], q[4], o[4];
      lds128f(p, va + (4 * c + j) * 128 + (lane & 3) * 32); lds128f(q, va + (4 * c + j) * 128 + (lane & 3) * 32 + 16);
#pragma unroll
      for (int e = 0; e < 4; e++)
        o[e] = silu_mul(fmaf(rs[e >> 1], g[e], fmaf(nm[e >> 1], p[e & 1], p[2 + (e & 1)])), fmaf(rs[e >> 1], u[e], fmaf(nm[e >> 1], q[e & 1], q[2 + (e & 1)])));
      y[0][j] = pack2(o[0], o[1]); y[1][j] = pack2(o[2], o[3]);
    }
#pragma unroll
    for (int h = 0; h < 2; h++)
      *reinterpret_cast<uint4*>(ap + (c >> 1) * 16384 + (c & 1) * 512 + h * 1024) = make_uint4(y[h][0], y[h][1], y[h][2], y[h][3]);
  }
}

__global__ void __launch_bounds__(384, 1)
kernel_H(const __grid_constant__ CUtensorMap tmo, const __grid_constant__ CUtensorMap tm1, const __grid_constant__ CUtensorMap tm3,
         const __grid_constant__ CUtensorMap tm2, const __grid_constant__ CUtensorMap tmm, const __nv_bfloat16* __restrict__ x,
         const __nv_bfloat16* __restrict__ cvec, __nv_bfloat16* __restrict__ out, const __grid_constant__ HList list) {
  extern __shared__ __align__(1024) uint8_t smem[];
  constexpr uint32_t sb = 0x400, bars = sb + H_BAR;
  const int tid = threadIdx.x, lane = tid & 31;
  const int warp = __shfl_sync(0xffffffffu, tid >> 5, 0);
  if (tid == 0) {
    if (smem_u32(smem) != sb) __trap();
    for (int i = 0; i < H_NST; i++) { mbar_init(bars + HB_FULL + i * 8, 1); mbar_init(bars + HB_EMPTY + i * 8, 2); }
    for (int i = 0; i < 2; i++) { mbar_init(bars + HB_IFULL + i * 8, 1); mbar_init(bars + HB_IEMPTY + i * 8, 3); }
    fence_async_smem();
  }
  __syncthreads();
  if (warp >= 8) {
    asm volatile("setmaxnreg.dec.sync.aligned.u32 40;");
    if (warp == 8) {
      uint32_t st = 0, ph = 1;
#pragma unroll 1
      for (uint32_t n = 0;; n++) {
        uint32_t q = 0;
        if (lane == 0) q = atomicAdd(&g_flags[FL_HEAD], 1);
        q = __shfl_sync(0xffffffffu, q, 0);
        const uint32_t it = q < list.n ? list.it[q] : 0;
        const int type = it & 7, mt = (it >> 3) & 15, idx = (it >> 7) & 63, sz = (it >> 13) & 3, part = (it >> 15) & 3, lgp = (it >> 17) & 3;
        int f = FL_GO; uint32_t target = 0;
        if (type == IT_OUT) { f = lane == 0 ? FL_ATT + 8 * mt : lane == 1 ? FL_XT + 8 * mt : FL_MOD; target = lane == 0 ? 64 : lane == 1 ? 2 : 12; }
        else if (type == IT_F1) { f = lane == 0 ? FL_OUT + 8 * mt : FL_UV; target = lane == 0 ? 16 : 28; }
        else if (type == IT_F2) { f = lane == 0 ? FL_F1 + 8 * mt : FL_MODB; target = lane == 0 ? 56 : 4; }
        else if (type == IT_UV) { f = FL_MOD; target = 12; }
        else if (type == IT_MOD || (XT_GO && type == IT_XT)) target = 1;
        bool late = false;
        if (lane < 2 && (lane == 0 || type == IT_OUT)) wait_flag(&g_flags[f], target);
        else if (lane == 2) late = ld_acquire(&g_flags[f]) < target;
        late = __shfl_sync(0xffffffffu, late, 2);
        asm volatile("fence.proxy.async.global;" ::: "memory");
        mbar_wait(bars + HB_IEMPTY + (n & 1) * 8, ((n >> 1) & 1) ^ 1);
        if (elect_one()) {
          sts32(bars + HB_ITEM + (n & 1) * 4, it | (q << 19));
          mbar_arrive(bars + HB_IFULL + (n & 1) * 8);
        }
        if (type == IT_END) break;
        if (type != IT_XT) {
          const bool has_a = type == IT_OUT || type >= IT_F1;
          const uint8_t* ap = type == IT_OUT ? g_att + (size_t)mt * 64 * 16384 : type == IT_F1 ? g_h2 + (size_t)mt * 16 * 16384 : g_act + (size_t)mt * 56 * 16384;
          const int nkb = (type == IT_OUT ? 64 : type == IT_F2 ? 56 : 16) >> lgp;
          const uint32_t abytes = has_a ? (sz == 2 ? 32768 : 16384) : 0, bytes = (sz == 0 ? 32768 : 16384) + abytes;
          const int dk = sz == 2 ? 1 : 0;
#pragma unroll 1
          for (int kb = part * nkb; kb < (part + 1) * nkb; kb += 1 + dk) {
            const uint32_t d = sb + st * H_STAGE, fb = bars + HB_FULL + st * 8;
            mbar_wait(bars + HB_EMPTY + st * 8, ph);
            if (has_a && kb + 1 + dk >= (part + 1) * nkb) {
              if (late) {
                if (lane == 2) wait_flag(&g_flags[f], target);
                __syncwarp();
                asm volatile("fence.proxy.async.global;" ::: "memory");
              }
              if (elect_one()) {
                const bool f1 = type == IT_F1;
                const int c0 = f1 ? idx * (128 >> sz) : idx * (256 >> sz);
                const uint32_t v = sb + H_VEC + (n & 1) * 3072;
                const uint32_t n0 = (f1 ? 2048 : 512) >> sz, n1 = f1 ? 1024 : n0;
                asm volatile("mbarrier.expect_tx.relaxed.cta.shared::cta.b64 [%0], %1;" :: "r"(fb), "r"(n0 + n1) : "memory");
                bulk_g2s(v, f1 ? (const void*)(g_uv + c0 * 4) : (const void*)(g_mod + (type == IT_OUT ? 2 : 5) * D_ + c0), n0, fb);
                bulk_g2s(v + (f1 ? 2048 : 512), f1 ? (const void*)(g_stat + mt * 256) : (const void*)(g_mod + 4 * D_ + c0), n1, fb);
              }
            }
            if (elect_one()) {
              mbar_expect(fb, bytes);
              if (has_a) bulk_g2s(d, ap + (size_t)kb * 16384, abytes, fb);
            }
            if (++st == H_NST) { st = 0; ph ^= 1; }
          }
        }
      }
    } else if (warp >= 10) {
      const int hb = warp - 10;
      uint32_t st = 0, ph = 1;
#pragma unroll 1
      for (uint32_t n = 0;; n++) {
        mbar_wait(bars + HB_IFULL + (n & 1) * 8, (n >> 1) & 1);
        const uint32_t it = __shfl_sync(0xffffffffu, lds32(bars + HB_ITEM + (n & 1) * 4), 0);
        const int type = it & 7, idx = (it >> 7) & 63, sz = (it >> 13) & 3, part = (it >> 15) & 3, lgp = (it >> 17) & 3;
        if (type == IT_END) break;
        if (elect_one()) mbar_arrive(bars + HB_IEMPTY + (n & 1) * 8);
        if (type == IT_XT) continue;
        const bool ffn1 = type == IT_F1 || type == IT_UV;
        const int nkb = (type == IT_OUT ? 64 : type == IT_F2 ? 56 : 16) >> lgp;
        const CUtensorMap* tb = type == IT_OUT ? &tmo : ffn1 ? &tm1 : type == IT_F2 ? &tm2 : &tmm;
        const CUtensorMap* tc = ffn1 ? &tm3 : tb;
        const int c0 = ffn1 ? idx * (128 >> sz) : idx * (256 >> sz) + (type == IT_MOD ? 2048 : 0), c2 = ffn1 ? c0 : c0 + 128;
        const int dk = sz == 2 ? 1 : 0;
        const CUtensorMap* t0 = hb == 1 && sz == 1 ? tc : tb;
        const int ca = hb == 0 || sz == 2 || (sz == 1 && ffn1) ? c0 : c0 + 64;
        const uint32_t off = (sz == 2 ? 32768 : 16384) + hb * 8192;
        const uint32_t cold = type == IT_MOD ? D_MOD : type == IT_UV ? D_UV : H_NST;
#pragma unroll 1
        for (int kb = part * nkb; kb < (part + 1) * nkb; kb += 1 + dk) {
          const uint32_t d = sb + st * H_STAGE + off, fb = bars + HB_FULL + st * 8;
          mbar_wait(bars + HB_EMPTY + st * 8, ph);
          if (cold < H_NST) mbar_wait(bars + HB_FULL + ((st - cold) & 3) * 8, st >= cold ? ph ^ 1 : ph);
          if (elect_one()) {
            tma5d(d, t0, ca, kb + hb * dk, fb);
            if (sz == 0) tma5d(d + 16384, tc, c2 + hb * 64, kb, fb);
          }
          if (++st == H_NST) { st = 0; ph ^= 1; }
        }
      }
    } else if (warp == 9) {
#pragma unroll 1
      for (uint32_t n = 0;; n++) {
        mbar_wait(bars + HB_IFULL + (n & 1) * 8, (n >> 1) & 1);
        const uint32_t itq = lds32(bars + HB_ITEM + (n & 1) * 4);
        const int type = itq & 7, mt = (itq >> 3) & 15;
        if (type == IT_END) break;
        if (n & 1) bar_sync<3, 288>(); else bar_sync<2, 288>();
        if (lane == 0) {
          const uint32_t inc = lds32(bars + HB_INC + (n & 1) * 4);
          mbar_arrive(bars + HB_IEMPTY + (n & 1) * 8);
          if (inc) {
            fence_gpu();
            red_add_u32(&g_flags[type == IT_MOD ? (((itq >> 7) & 63) < 12 ? FL_MOD : FL_MODB) : type == IT_UV ? FL_UV : (type == IT_XT ? FL_XT : type == IT_OUT ? FL_OUT : FL_F1) + 8 * mt], inc);
          }
        }
        __syncwarp();
      }
      asm volatile("griddepcontrol.wait;" ::: "memory");
      uint32_t k = 0;
      if (lane == 0) { fence_gpu(); k = atomicAdd(&g_flags[FL_EXIT], 1); }
      k = __shfl_sync(0xffffffffu, k, 0);
      if (k == gridDim.x - 1) {
        fence_gpu();
        for (int i = lane; i < 1024; i += 32) g_flags[i] = 0;
      }
    }
  } else {
    asm volatile("setmaxnreg.inc.sync.aligned.u32 232;");
    const int wg = warp >> 2;
    const bool leader = (tid & 127) == 0;
    uint32_t st = 0, ph = 0;
#pragma unroll 1
    for (uint32_t n = 0;; n++) {
      mbar_wait(bars + HB_IFULL + (n & 1) * 8, (n >> 1) & 1);
      const uint32_t itq = __shfl_sync(0xffffffffu, lds32(bars + HB_ITEM + (n & 1) * 4), 0);
      const int type = itq & 7, mt = (itq >> 3) & 15, idx = (itq >> 7) & 63, sz = (itq >> 13) & 3, part = (itq >> 15) & 3, lgp = (itq >> 17) & 3;
      uint32_t inc = type == IT_OUT ? 4 >> sz : type == IT_F1 ? 2 >> sz : type != IT_F2;
      if (type == IT_END) break;
      HT(0);
      const uint32_t va = sb + H_VEC + (n & 1) * 3072;
      if (type == IT_OUT) {
        if (sz == 0) h_residual<256, false>(sb, va, mt, idx * 256, st, ph, warp, lane, out);
        else if (sz == 1) h_residual<128, false>(sb, va, mt, idx * 128, st, ph, warp, lane, out);
        else inc = h_residual<64, false>(sb, va, mt, idx * 64, st, ph, warp, lane, out, part, lgp);
      } else if (type == IT_F2) {
        if (sz == 0) h_residual<256, true>(sb, va, mt, idx * 256, st, ph, warp, lane, out);
        else if (sz == 1) h_residual<128, true>(sb, va, mt, idx * 128, st, ph, warp, lane, out);
        else h_residual<64, true>(sb, va, mt, idx * 64, st, ph, warp, lane, out, part, lgp);
      } else if (type == IT_XT) {
        const int rg = idx * 8 + warp;
        const uint32_t* xp = reinterpret_cast<const uint32_t*>(x + (size_t)(mt * 128 + rg * 8 + (lane >> 2)) * D_) + (lane & 3);
        uint8_t* tp = g_x1 + (size_t)mt * 262144 + rg * 1024 + (lane & 3) * 128 + (lane >> 2) * 16;
        if (lane < 16) g_stat[(mt * 128 + rg * 8) * 2 + lane] = 0.f;
#pragma unroll 1
        for (int b = 0; b < 2; b++) {
          uint32_t v[64];
#pragma unroll
          for (int i = 0; i < 64; i++) v[i] = __ldg(xp + 256 * b + 4 * i);
#pragma unroll
          for (int i = 0; i < 16; i++)
            *reinterpret_cast<uint4*>(tp + (8 * b + (i >> 1)) * 16384 + (i & 1) * 512) = make_uint4(v[4 * i], v[4 * i + 1], v[4 * i + 2], v[4 * i + 3]);
        }
      } else if (sz == 1) {
        float acc[64];
        h_mainloop<128, 0>(acc, sb, 16, st, ph, wg, leader);
        h_swiglu<128>(acc, va, mt, idx, warp, lane);
      } else {
        if (type != IT_F1) {
          bar_sync<1, 256>();
          for (int i = tid; i < D_; i += 256) {
            __nv_bfloat16* p = reinterpret_cast<__nv_bfloat16*>(smem + H_STG + (i >> 5) * 512 + ((i >> 1) & 3) * 128) + ((i >> 3) & 3) * 2 + (i & 1);
            if (type == IT_UV) { p[0] = __float2bfloat16(1.f); p[8] = __ldcg(g_mod + 4 * D_ + i); p[16] = __ldcg(g_mod + 3 * D_ + i); }
            else { const float c = __bfloat162float(cvec[i]); p[0] = __float2bfloat16(c / (1.f + __expf(-c))); }
          }
          fence_async_smem();
          bar_sync<1, 256>();
        }
        float acc[128];
        h_mainloop<256, 0>(acc, sb, 16, st, ph, wg, leader, type != IT_F1);
        if (type == IT_F1) {
          h_swiglu<256>(acc, va, mt, idx * 2, warp, lane);
        } else if (warp == 0) {
#pragma unroll
          for (int j = 0; j < 32; j++) {
            if (type == IT_MOD) {
              if (lane < 4) reinterpret_cast<uint32_t*>(g_mod + 2048 + idx * 256)[j * 4 + lane] = pack2(acc[4 * j], acc[4 * j + 1]);
            } else {
              const float a = acc[4 * j] + __shfl_down_sync(0xffffffffu, acc[4 * j], 4), b = acc[4 * j + 1] + __shfl_down_sync(0xffffffffu, acc[4 * j + 1], 4);
              float2* up = reinterpret_cast<float2*>(g_uv + idx * 512 + ((j & 15) * 4 + (lane & 3)) * 8 + (j >> 4) * 4);
              if (lane < 4) up[0] = make_float2(a, b);
              else if ((lane >> 2) == 2) up[1] = make_float2(acc[4 * j], acc[4 * j + 1]);
            }
          }
        }
      }
      if (tid == 0) sts32(bars + HB_INC + (n & 1) * 4, inc);
      if (n & 1) bar_arrive<3, 288>(); else bar_arrive<2, 288>();
    }
  }
}

#define T_FIRST 35.f
#define T_UV 43.f
#define T_UV2 55.f
#define T_OUT0 50.f
#define T_SLACK 2.f
#define T_PERIOD 13.4f
#define G_OUT "2211111111111124"
#define G_F1 "0000000000000001"
#define G_F2 "0000000011112233"
#define F2_LEAD 20.f
void build_list(HList& l) {
  int n = 0;
  auto add = [&](int type, int mt, int idx, int g) {
    const int sz = g > 2 ? 2 : g, lgp = g - sz;
    l.it[n++] = type | mt << 3 | (idx >> lgp) << 7 | sz << 13 | (idx & ((1 << lgp) - 1)) << 15 | lgp << 17;
  };
  const char* gran[3] = {G_OUT, G_F1, G_F2};
  if (XT_GO) for (int i = 0; i < 12; i++) add(IT_MOD, 0, i, 0);
  for (int i = 0; i < 32; i++) add(IT_XT, i >> 1, i & 1, 0);
  if (!XT_GO) for (int i = 0; i < 12; i++) add(IT_MOD, 0, i, 0);
  for (int i = 0; i < N_UV1; i++) add(IT_UV, 0, i, 0);
  for (int i = 0; i < 4 << (G_OUT[0] - '0'); i++) add(IT_OUT, 0, i, G_OUT[0] - '0');
  for (int i = N_UV1; i < 28; i++) add(IT_UV, 0, i, 0);
  for (int i = 12; i < 16; i++) add(IT_MOD, 0, i, 0);
  const float dur[3][5] = {{42.f, 22.f, 13.f, 9.f, 7.f}, {11.2f, 7.f, 0.f, 0.f, 0.f}, {37.f, 21.f, 11.5f, 8.f, 6.f}};
  const float t_end = T_FIRST + 15 * T_PERIOD - 1.5f;
  float fr[132];
  for (int i = 0; i < 132; i++) fr[i] = i < 36 - N_UV1 ? T_OUT0 : i < 36 - N_UV1 + 32 - N_UV1 ? T_UV2 : i < 36 ? T_UV : t_end + 1.2f;
  float rdy[3][16];
  int mt[3] = {1, 0, 0}, ix[3] = {0, 0, 0};
  for (int m = 0; m < 16; m++) { rdy[0][m] = m < 15 ? T_FIRST + m * T_PERIOD : t_end; rdy[1][m] = rdy[2][m] = 0.f; }
  rdy[1][0] = T_OUT0 + 0.5f;
  while (mt[2] < 16) {
    int w = 0;
    for (int i = 1; i < 132; i++) if (fr[i] < fr[w]) w = i;
    const float t = fr[w];
    int best = -1;
    float tb = 1e9f;
    const bool f2_first = gran[2][mt[2]] == '0' && t > t_end - F2_LEAD;
    const int order[3] = {0, f2_first ? 2 : 1, f2_first ? 1 : 2};
    for (int k = 0; k < 3; k++) {
      const int q = order[k];
      if (mt[q] >= 16 || (q > 0 && mt[q] >= mt[q - 1])) continue;
      const float ts = rdy[q][mt[q]] > t ? rdy[q][mt[q]] : t;
      if (ts < tb - T_SLACK) { tb = ts; best = q; }
    }
    const int m = mt[best], g = gran[best][m] - '0';
    add(best == 0 ? IT_OUT : best == 1 ? IT_F1 : IT_F2, m, ix[best], g);
    fr[w] = tb + dur[best][g];
    if (best < 2 && fr[w] + 0.5f > rdy[best + 1][m]) rdy[best + 1][m] = fr[w] + 0.5f;
    if (++ix[best] == (best == 1 ? 28 : 4) << g) { ix[best] = 0; mt[best]++; }
  }
  l.n = n;
}

typedef CUresult (*EncodeFn)(CUtensorMap*, CUtensorMapDataType, cuuint32_t, void*, const cuuint64_t*, const cuuint64_t*,
                             const cuuint32_t*, const cuuint32_t*, CUtensorMapInterleave, CUtensorMapSwizzle,
                             CUtensorMapL2promotion, CUtensorMapFloatOOBfill);

void make_map(EncodeFn fn, CUtensorMap* m, const void* p, uint64_t cols, uint64_t rows, uint32_t bc, uint32_t br, CUtensorMapSwizzle sw) {
  cuuint64_t dims[2] = {cols, rows};
  cuuint64_t strides[1] = {cols * 2};
  cuuint32_t box[2] = {bc, br};
  cuuint32_t es[2] = {1, 1};
  fn(m, CU_TENSOR_MAP_DATA_TYPE_BFLOAT16, 2, const_cast<void*>(p), dims, strides, box, es, CU_TENSOR_MAP_INTERLEAVE_NONE, sw,
     CU_TENSOR_MAP_L2_PROMOTION_L2_128B, CU_TENSOR_MAP_FLOAT_OOB_FILL_NONE);
}

void make_map_perm(EncodeFn fn, CUtensorMap* m, const void* p, uint64_t cols, uint64_t rows, bool perm) {
  cuuint64_t dims[5] = {cols, 2, 4, 4, rows / 32};
  cuuint64_t strides[4] = {cols * 2, cols * 2 * (perm ? 8 : 2), cols * 2 * (perm ? 2 : 8), cols * 2 * 32};
  cuuint32_t box[5] = {64, 2, 4, 4, 2};
  cuuint32_t es[5] = {1, 1, 1, 1, 1};
  fn(m, CU_TENSOR_MAP_DATA_TYPE_BFLOAT16, 5, const_cast<void*>(p), dims, strides, box, es, CU_TENSOR_MAP_INTERLEAVE_NONE,
     CU_TENSOR_MAP_SWIZZLE_128B, CU_TENSOR_MAP_L2_PROMOTION_L2_128B, CU_TENSOR_MAP_FLOAT_OOB_FILL_NONE);
}

}

extern "C" void kernel_launch(void* const* d_in, const int* in_sizes, int n_in, void* d_out, int out_size) {
  const __nv_bfloat16* x = (const __nv_bfloat16*)d_in[0];
  const __nv_bfloat16* mem0 = (const __nv_bfloat16*)d_in[1];
  const __nv_bfloat16* cvec = (const __nv_bfloat16*)d_in[11];
  static EncodeFn enc = nullptr;
  if (!enc) {
    cudaDriverEntryPointQueryResult qr;
    void* fp = nullptr;
    cudaGetDriverEntryPoint("cuTensorMapEncodeTiled", &fp, cudaEnableDefault, &qr);
    enc = (EncodeFn)fp;
    cudaFuncSetAttribute(kernel_R, cudaFuncAttributeMaxDynamicSharedMemorySize, R_SMEM);
    cudaFuncSetAttribute(kernel_H, cudaFuncAttributeMaxDynamicSharedMemorySize, H_SMEM);
  }
  CUtensorMap tmq, tmk, tmv, tmo, tmm;
  make_map(enc, &tmm, d_in[12], 6144, 1024, 64, 64, CU_TENSOR_MAP_SWIZZLE_NONE);
  make_map(enc, &tmq, d_in[2], 4096, 1024, 64, 64, CU_TENSOR_MAP_SWIZZLE_128B);
  make_map(enc, &tmk, d_in[3], 4096, 1024, 64, 64, CU_TENSOR_MAP_SWIZZLE_128B);
  make_map(enc, &tmv, d_in[4], 4096, 1024, 64, 64, CU_TENSOR_MAP_SWIZZLE_128B);
  make_map(enc, &tmo, d_in[5], 1024, 4096, 16, 128, CU_TENSOR_MAP_SWIZZLE_32B);
  RDesc dsc;
  for (int k = 0; k < 32; k++) {
    dsc.tok[k] = mkdesc(0x400 + (k < 16 ? R_GA : R_GB) + ((k & 15) >> 2) * 4096 + (k & 3) * 256, 128, 1024, 0);
    dsc.tail_a[k] = mkdesc(0x400 + R_TAIL + k * 2048, 1024, 1024, 1);
    if (k < 16) dsc.tail_b[k] = mkdesc(0x400 + R_GA + k * 256, 128, 4096, 0);
  }
  kernel_R<<<96, 256, R_SMEM, cudaStreamPerThread>>>(tmq, tmk, tmv, tmo, tmm, x, mem0, cvec, dsc);

  CUtensorMap ho, h1, h3, h2, hm;
  make_map_perm(enc, &ho, d_in[5], 1024, 4096, false);
  make_map_perm(enc, &h1, d_in[8], F_, 1024, true);
  make_map_perm(enc, &h3, d_in[9], F_, 1024, true);
  make_map_perm(enc, &h2, d_in[10], 1024, F_, true);
  make_map_perm(enc, &hm, d_in[12], 6144, 1024, true);
  HList list;
  build_list(list);
  cudaLaunchConfig_t cfg = {};
#define H_GRID 132
  cfg.gridDim = dim3(H_GRID); cfg.blockDim = dim3(384); cfg.dynamicSmemBytes = H_SMEM; cfg.stream = cudaStreamPerThread;
  cudaLaunchAttribute at[1];
  at[0].id = cudaLaunchAttributeProgrammaticStreamSerialization;
  at[0].val.programmaticStreamSerializationAllowed = 1;
  cfg.attrs = at;
  cfg.numAttrs = 1;
  cudaLaunchKernelEx(&cfg, kernel_H, ho, h1, h3, h2, hm, x, cvec, (__nv_bfloat16*)d_out, list);
}
```

```cpp
#include <cuda_runtime.h>
#include <cuda_bf16.h>
#include <cuda.h>
#include <stdint.h>
#include <type_traits>

namespace {

constexpr int S_ = 2048, D_ = 1024, NSEG = 64, F_ = 3584;

__device__ __align__(1024) uint8_t g_h[S_ * D_ * 2];
__device__ __align__(1024) uint8_t g_att[S_ * 4096 * 2];
__device__ __align__(1024) uint8_t g_x1[S_ * D_ * 2];
__device__ __align__(1024) uint8_t g_h2[S_ * D_ * 2];
__device__ __align__(1024) uint8_t g_act[S_ * F_ * 2];
__device__ __align__(1024) float g_ws[2 * 4 * 16 * 4 * 8192];
__device__ __align__(1024) float g_stat[S_ * 2];
__device__ __align__(1024) float g_uv[F_ * 4];
__device__ __align__(1024) float g_slot[4 * 3 * 8 * 4 * 32 * 4];
__device__ __align__(128) __nv_bfloat16 g_mod[6 * D_];
__device__ __align__(128) float g_modp[3 * 2 * D_];
__device__ __align__(128) uint32_t g_flags[1024];
constexpr int FL_S1 = 0, FL_S2 = 32, FL_MOD = 64, FL_HEAD = 96, FL_EXIT = 128, FL_UV = 160, FL_GO = 192, FL_MODB = 224, FL_ATT = 256, FL_XT = 384, FL_OUT = 512, FL_F1 = 640, FL_SPL = 768;

#define EVF 1
__device__ __forceinline__ uint32_t smem_u32(const void* p) { return (uint32_t)__cvta_generic_to_shared(p); }
__device__ __forceinline__ uint32_t mapa(uint32_t a, uint32_t r) { uint32_t o; asm("mapa.shared::cluster.u32 %0, %1, %2;" : "=r"(o) : "r"(a), "r"(r)); return o; }
__device__ __forceinline__ uint32_t pack2(float a, float b) { uint32_t r; asm("cvt.rn.bf16x2.f32 %0, %1, %2;" : "=r"(r) : "f"(b), "f"(a)); return r; }
__device__ __forceinline__ float bf_lo(uint32_t w) { return __uint_as_float(w << 16); }
__device__ __forceinline__ float bf_hi(uint32_t w) { return __uint_as_float(w & 0xffff0000u); }
__device__ __forceinline__ float ex2(float x) { float y; asm("ex2.approx.ftz.f32 %0, %1;" : "=f"(y) : "f"(x)); return y; }
__device__ __forceinline__ float rcp(float x) { float y; asm("rcp.approx.ftz.f32 %0, %1;" : "=f"(y) : "f"(x)); return y; }
__device__ __forceinline__ uint32_t clk32() { uint64_t c; asm volatile("mov.u64 %0, %%clock64;" : "=l"(c) :: "memory"); return (uint32_t)c; }

__device__ __forceinline__ void mbar_init(uint32_t b, uint32_t n) { asm volatile("mbarrier.init.shared::cta.b64 [%0], %1;" :: "r"(b), "r"(n) : "memory"); }
__device__ __forceinline__ void mbar_arrive(uint32_t b) { asm volatile("mbarrier.arrive.shared::cta.b64 _, [%0];" :: "r"(b) : "memory"); }
__device__ __forceinline__ void mbar_expect(uint32_t b, uint32_t n) { asm volatile("mbarrier.arrive.expect_tx.shared::cta.b64 _, [%0], %1;" :: "r"(b), "r"(n) : "memory"); }
__device__ __forceinline__ uint32_t mbar_try(uint32_t b, uint32_t par) {
  uint32_t ok;
  asm volatile("{\n.reg .pred p;\nmbarrier.try_wait.parity.shared::cta.b64 p, [%1], %2;\nselp.u32 %0, 1, 0, p;\n}" : "=r"(ok) : "r"(b), "r"(par) : "memory");
  return ok;
}
__device__ __forceinline__ void mbar_wait(uint32_t b, uint32_t par) {
  asm volatile("{\n.reg .pred p;\n"
               "LOOP:\n"
               "mbarrier.try_wait.parity.shared::cta.b64 p, [%0], %1;\n"
               "@!p bra.uni LOOP;\n}" :: "r"(b), "r"(par) : "memory");
}
__device__ __forceinline__ void mbar_wait_safe(uint32_t b, uint32_t par) {
  uint32_t c = 0;
  while (!mbar_try(b, par)) { if (++c > 4000000u) __trap(); }
}
__device__ __forceinline__ bool elect_one() {
  uint32_t p;
  asm volatile("{\n.reg .pred p;\nelect.sync _|p, 0xffffffff;\nselp.u32 %0, 1, 0, p;\n}" : "=r"(p));
  return p;
}
__device__ __forceinline__ void sched_fence(uint32_t x, uint32_t y) { asm volatile("{\n.reg .pred p;\nsetp.eq.u32 p, %0, %1;\n@p trap;\n}" :: "r"(x), "r"(y) : "memory"); }
template <class T> __device__ __forceinline__ T opaque32(T x) { asm volatile("" : "+r"(x)); return x; }
template <class T> __device__ __forceinline__ T opaque64(T x) { asm volatile("" : "+l"(x)); return x; }
template <int ID, int N> __device__ __forceinline__ void bar_sync() { asm volatile("bar.sync %0, %1;" :: "n"(ID), "n"(N) : "memory"); }
template <int ID, int N> __device__ __forceinline__ void bar_arrive() { asm volatile("bar.arrive %0, %1;" :: "n"(ID), "n"(N) : "memory"); }
__device__ __forceinline__ void fence_async_smem() { asm volatile("fence.proxy.async.shared::cta;" ::: "memory"); }
__device__ __forceinline__ void fence_async_all() { asm volatile("fence.proxy.async;" ::: "memory"); }
__device__ __forceinline__ void fence_gpu() { asm volatile("fence.acq_rel.gpu;" ::: "memory"); }
__device__ __forceinline__ void red_add_u32(uint32_t* p, uint32_t v) { asm volatile("red.relaxed.gpu.global.add.u32 [%0], %1;" :: "l"(p), "r"(v) : "memory"); }
__device__ __forceinline__ uint32_t ld_acquire(const uint32_t* p) { uint32_t v; asm volatile("ld.acquire.gpu.global.u32 %0, [%1];" : "=r"(v) : "l"(p) : "memory"); return v; }
__device__ __forceinline__ void wait_flag(const uint32_t* p, uint32_t target) {
  uint32_t c = 0;
  while (ld_acquire(p) < target) { if (++c > 20000000u) __trap(); __nanosleep(20); }
}

__device__ __forceinline__ void tma2d(uint32_t dst, const CUtensorMap* m, int c0, int c1, uint32_t bar) {
  asm volatile("cp.async.bulk.tensor.2d.shared::cluster.global.mbarrier::complete_tx::bytes [%0], [%1, {%3, %4}], [%2];"
               :: "r"(dst), "l"(m), "r"(bar), "r"(c0), "r"(c1) : "memory");
}
__device__ __forceinline__ void tma2d_once(uint32_t dst, const CUtensorMap* m, int c0, int c1, uint32_t bar) {
  asm volatile("{\n.reg .b64 pol;\ncreatepolicy.fractional.L2::evict_first.b64 pol, 1.0;\n"
               "cp.async.bulk.tensor.2d.shared::cluster.global.mbarrier::complete_tx::bytes.L2::cache_hint [%0], [%1, {%3, %4}], [%2], pol;\n}"
               :: "r"(dst), "l"(m), "r"(bar), "r"(c0), "r"(c1) : "memory");
}
__device__ __forceinline__ void tma5d(uint32_t dst, const CUtensorMap* m, int n0, int kb, uint32_t bar) {
  asm volatile("cp.async.bulk.tensor.5d.shared::cluster.global.mbarrier::complete_tx::bytes [%0], [%1, {%3, %5, %5, %5, %4}], [%2];"
               :: "r"(dst), "l"(m), "r"(bar), "r"(n0), "r"(2 * kb), "r"(0) : "memory");
}
__device__ __forceinline__ void tma2d_prefetch(const CUtensorMap* m, int c0, int c1) {
  asm volatile("cp.async.bulk.prefetch.tensor.2d.L2.global [%0, {%1, %2}];" :: "l"(m), "r"(c0), "r"(c1) : "memory");
}
__device__ __forceinline__ void bulk_g2s(uint32_t dst, const void* src, uint32_t bytes, uint32_t bar) {
  asm volatile("cp.async.bulk.shared::cluster.global.mbarrier::complete_tx::bytes [%0], [%1], %2, [%3];"
               :: "r"(dst), "l"(src), "r"(bytes), "r"(bar) : "memory");
}
__device__ __forceinline__ void bulk_s2s(uint32_t dst, uint32_t src, uint32_t bytes, uint32_t bar) {
  asm volatile("cp.async.bulk.shared::cluster.shared::cta.mbarrier::complete_tx::bytes [%0], [%1], %2, [%3];"
               :: "r"(dst), "r"(src), "r"(bytes), "r"(bar) : "memory");
}
__device__ __forceinline__ void st_async1(uint32_t dst, uint32_t a, uint32_t bar) {
  asm volatile("st.async.shared::cluster.mbarrier::complete_tx::bytes.b32 [%0], %1, [%2];" :: "r"(dst), "r"(a), "r"(bar) : "memory");
}
__device__ __forceinline__ void st_async2(uint32_t dst, uint32_t a, uint32_t b, uint32_t bar) {
  asm volatile("st.async.shared::cluster.mbarrier::complete_tx::bytes.v2.b32 [%0], {%1, %2}, [%3];" :: "r"(dst), "r"(a), "r"(b), "r"(bar) : "memory");
}
__device__ __forceinline__ void st_async4(uint32_t dst, const uint32_t* r, uint32_t bar) {
  asm volatile("st.async.shared::cluster.mbarrier::complete_tx::bytes.v4.b32 [%0], {%1, %2, %3, %4}, [%5];"
               :: "r"(dst), "r"(r[0]), "r"(r[1]), "r"(r[2]), "r"(r[3]), "r"(bar) : "memory");
}
__device__ __forceinline__ void sts32(uint32_t a, uint32_t v) { asm volatile("st.shared.b32 [%0], %1;" :: "r"(a), "r"(v) : "memory"); }
__device__ __forceinline__ void sts64(uint32_t a, uint32_t x, uint32_t y) { asm volatile("st.shared.v2.b32 [%0], {%1, %2};" :: "r"(a), "r"(x), "r"(y) : "memory"); }
__device__ __forceinline__ void sts128(uint32_t a, uint32_t x, uint32_t y, uint32_t z, uint32_t w) {
  asm volatile("st.shared.v4.b32 [%0], {%1, %2, %3, %4};" :: "r"(a), "r"(x), "r"(y), "r"(z), "r"(w) : "memory");
}
__device__ __forceinline__ void lds128(uint32_t* r, uint32_t a) {
  asm volatile("ld.shared.v4.b32 {%0, %1, %2, %3}, [%4];" : "=r"(r[0]), "=r"(r[1]), "=r"(r[2]), "=r"(r[3]) : "r"(a) : "memory");
}
__device__ __forceinline__ uint32_t lds32(uint32_t a) { uint32_t r; asm volatile("ld.shared.b32 %0, [%1];" : "=r"(r) : "r"(a) : "memory"); return r; }
__device__ __forceinline__ void lds64(uint32_t* r, uint32_t a) {
  asm volatile("ld.shared.v2.b32 {%0, %1}, [%2];" : "=r"(r[0]), "=r"(r[1]) : "r"(a) : "memory");
}
__device__ __forceinline__ void lds128f(float* r, uint32_t a) {
  asm volatile("ld.shared.v4.f32 {%0, %1, %2, %3}, [%4];" : "=f"(r[0]), "=f"(r[1]), "=f"(r[2]), "=f"(r[3]) : "r"(a) : "memory");
}
__device__ __forceinline__ void lds64f(float* r, uint32_t a) {
  asm volatile("ld.shared.v2.f32 {%0, %1}, [%2];" : "=f"(r[0]), "=f"(r[1]) : "r"(a) : "memory");
}
__device__ __forceinline__ void ldsm4(uint32_t* r, uint32_t a) {
  asm volatile("ldmatrix.sync.aligned.m8n8.x4.shared.b16 {%0, %1, %2, %3}, [%4];" : "=r"(r[0]), "=r"(r[1]), "=r"(r[2]), "=r"(r[3]) : "r"(a) : "memory");
}
__device__ __forceinline__ void ldsm4t(uint32_t* r, uint32_t a) {
  asm volatile("ldmatrix.sync.aligned.m8n8.x4.trans.shared.b16 {%0, %1, %2, %3}, [%4];" : "=r"(r[0]), "=r"(r[1]), "=r"(r[2]), "=r"(r[3]) : "r"(a) : "memory");
}
__device__ __forceinline__ void ldsm2(uint32_t* r, uint32_t a) {
  asm volatile("ldmatrix.sync.aligned.m8n8.x2.shared.b16 {%0, %1}, [%2];" : "=r"(r[0]), "=r"(r[1]) : "r"(a) : "memory");
}
__device__ __forceinline__ void stsm4(uint32_t a, const uint32_t* r) {
  asm volatile("stmatrix.sync.aligned.m8n8.x4.shared.b16 [%0], {%1, %2, %3, %4};" :: "r"(a), "r"(r[0]), "r"(r[1]), "r"(r[2]), "r"(r[3]) : "memory");
}
__device__ __forceinline__ uint32_t hadd2(uint32_t a, uint32_t b) { uint32_t t; asm("add.rn.bf16x2 %0, %1, %2;" : "=r"(t) : "r"(a), "r"(b)); return t; }
__device__ __forceinline__ uint32_t hmax2(uint32_t a, uint32_t b) { uint32_t t; asm("max.bf16x2 %0, %1, %2;" : "=r"(t) : "r"(a), "r"(b)); return t; }
__device__ __forceinline__ void ldsm2t(uint32_t* r, uint32_t a) {
  asm volatile("ldmatrix.sync.aligned.m8n8.x2.trans.shared.b16 {%0, %1}, [%2];" : "=r"(r[0]), "=r"(r[1]) : "r"(a) : "memory");
}
__device__ __forceinline__ uint32_t movm(uint32_t x) { uint32_t y; asm volatile("movmatrix.sync.aligned.m8n8.trans.b16 %0, %1;" : "=r"(y) : "r"(x)); return y; }
__device__ __forceinline__ void hmma(float* d, uint32_t a0, uint32_t a1, uint32_t a2, uint32_t a3, uint32_t b0, uint32_t b1) {
  asm volatile("mma.sync.aligned.m16n8k16.row.col.f32.bf16.bf16.f32 {%0,%1,%2,%3}, {%4,%5,%6,%7}, {%8,%9}, {%0,%1,%2,%3};"
               : "+f"(d[0]), "+f"(d[1]), "+f"(d[2]), "+f"(d[3]) : "r"(a0), "r"(a1), "r"(a2), "r"(a3), "r"(b0), "r"(b1));
}
__device__ __forceinline__ void hmma0(float* d, uint32_t a0, uint32_t a1, uint32_t a2, uint32_t a3, uint32_t b0, uint32_t b1) {
  asm volatile("mma.sync.aligned.m16n8k16.row.col.f32.bf16.bf16.f32 {%0,%1,%2,%3}, {%4,%5,%6,%7}, {%8,%9}, {%10,%10,%10,%10};"
               : "=f"(d[0]), "=f"(d[1]), "=f"(d[2]), "=f"(d[3]) : "r"(a0), "r"(a1), "r"(a2), "r"(a3), "r"(b0), "r"(b1), "f"(0.f));
}
__device__ __forceinline__ void hmma_k8(float* d, uint32_t a0, uint32_t a1, uint32_t b0) {
  asm volatile("mma.sync.aligned.m16n8k8.row.col.f32.bf16.bf16.f32 {%0,%1,%2,%3}, {%4,%5}, {%6}, {%0,%1,%2,%3};"
               : "+f"(d[0]), "+f"(d[1]), "+f"(d[2]), "+f"(d[3]) : "r"(a0), "r"(a1), "r"(b0));
}
__host__ __device__ constexpr uint64_t mkdesc(uint32_t addr, uint32_t lbo, uint32_t sbo, uint32_t sw) {
  return (uint64_t)((addr & 0x3FFFF) >> 4) | ((uint64_t)(lbo >> 4) << 16) | ((uint64_t)(sbo >> 4) << 32) | ((uint64_t)sw << 62);
}
#define WG_FENCE() asm volatile("wgmma.fence.sync.aligned;" ::: "memory")
#define WG_COMMIT() asm volatile("wgmma.commit_group.sync.aligned;" ::: "memory")
#define WG_WAIT(n) asm volatile("wgmma.wait_group.sync.aligned " #n ";" ::: "memory")
template <int N> __device__ __forceinline__ void reg_fence(float* d) {
#pragma unroll
  for (int i = 0; i < N; i++) asm volatile("" : "+f"(d[i]) :: "memory");
}
template <int N> __device__ __forceinline__ void zero_regs(float* d) {
#pragma unroll
  for (int i = 0; i < N; i++) asm volatile("mov.b32 %0, 0;" : "=f"(d[i]));
}
template <int SD>
__device__ __forceinline__ void wg_rs32(float* d, uint32_t a0, uint32_t a1, uint32_t a2, uint32_t a3, uint64_t b) {
  asm volatile("wgmma.mma_async.sync.aligned.m64n32k16.f32.bf16.bf16 {%0,%1,%2,%3,%4,%5,%6,%7,%8,%9,%10,%11,%12,%13,%14,%15}, {%16,%17,%18,%19}, %20, %21, 1, 1, 0;"
               : "+f"(d[0]), "+f"(d[1]), "+f"(d[2]), "+f"(d[3]), "+f"(d[4]), "+f"(d[5]), "+f"(d[6]), "+f"(d[7]),
                 "+f"(d[8]), "+f"(d[9]), "+f"(d[10]), "+f"(d[11]), "+f"(d[12]), "+f"(d[13]), "+f"(d[14]), "+f"(d[15])
               : "r"(a0), "r"(a1), "r"(a2), "r"(a3), "l"(b), "n"(SD));
}
template <int TB>
__device__ __forceinline__ void wg_ss40(float* d, uint64_t a, uint64_t b) {
  asm volatile("wgmma.mma_async.sync.aligned.m64n40k16.f32.bf16.bf16 {%0,%1,%2,%3,%4,%5,%6,%7,%8,%9,%10,%11,%12,%13,%14,%15,%16,%17,%18,%19}, %20, %21, 1, 1, 1, 1, %22;"
               : "+f"(d[0]), "+f"(d[1]), "+f"(d[2]), "+f"(d[3]), "+f"(d[4]), "+f"(d[5]), "+f"(d[6]), "+f"(d[7]),
                 "+f"(d[8]), "+f"(d[9]), "+f"(d[10]), "+f"(d[11]), "+f"(d[12]), "+f"(d[13]), "+f"(d[14]), "+f"(d[15]),
                 "+f"(d[16]), "+f"(d[17]), "+f"(d[18]), "+f"(d[19])
               : "l"(a), "l"(b), "n"(TB));
}
template <int T>
__device__ __forceinline__ void wg_ss32(float* d, uint64_t a, uint64_t b) {
  asm volatile("wgmma.mma_async.sync.aligned.m64n32k16.f32.bf16.bf16 {%0,%1,%2,%3,%4,%5,%6,%7,%8,%9,%10,%11,%12,%13,%14,%15}, %16, %17, 1, 1, 1, %18, %18;"
               : "+f"(d[0]), "+f"(d[1]), "+f"(d[2]), "+f"(d[3]), "+f"(d[4]), "+f"(d[5]), "+f"(d[6]), "+f"(d[7]),
                 "+f"(d[8]), "+f"(d[9]), "+f"(d[10]), "+f"(d[11]), "+f"(d[12]), "+f"(d[13]), "+f"(d[14]), "+f"(d[15])
               : "l"(a), "l"(b), "n"(T));
}

constexpr int R_TAIL = 0;
constexpr int R_WO = 65536;
constexpr int R_QK = R_WO + 86016;
constexpr int R_P = R_QK + 10240;
constexpr int R_GA = R_P + 6400;
constexpr int R_M2 = R_GA + 16384;
constexpr int R_M1 = R_M2 + 7168;
constexpr int R_GB = R_M1 + 9216;
constexpr int R_VT = R_GB + 16384;
constexpr int R_VM = R_VT + 8192;
constexpr int R_XS = R_VM + 2048;
constexpr int R_OX = R_XS + 1280;
constexpr int R_BAR = R_OX + 2048;
constexpr int R_TRC = R_BAR + 256;
constexpr int R_SMEM = R_TRC + 1024;
constexpr int B_MB = 0, B_XS = 32, B_VM = 40, B_VT = 48, B_TS = 56, B_FA = 64, B_FB = 72, B_TAIL = 80, B_WO = 88, B_STG = 96, B_WM = 128, B_X = 136;
constexpr int NB_A = 1, NB_B = 2, NB_X = 3, NB_C = 4, NB_D = 5, NB_E = 6, NB_F = 7, NB_G = 8, NB_H = 9, NB_S = 10, NB_E2 = 11, NB_P = 12, NB_W0 = 13;

#define POLL_DELAY 750
#define POLL_DELAY1 700
#define POLL_STAG 150
#define POLL_K0 20
#define PF1 2
#define PF2 2
#define PF3 2
#define PF4 0
#define CLR_D 2
#define PADN 0
#define PFD 0
#define GO_EARLY 0
#define RF_FIRST 1
#define BX_I 5
#define NCH 4
#define TOP2 0
#define CX_I 13
#define ATT_LATE 0
#define V_FENCE 1
#define SELF_STAS 1
#define Q_FENCE 1
#define ND_K 3
#define TRACE(i)
#define TS(i)

__device__ __forceinline__ int rot_chunk(int c, int rank) {
  int G = c;
  if (c < 9) { G = c + 3 * rank; if (G >= 9) G -= 9; }
  return G;
}
__device__ __forceinline__ int wo_tile(int i, int rank) {
  if (i < 12) return 12 * rank + i;
  const int r = i - 12 + 9 * rank;
  return r < 16 ? 48 + r : 20 + r;
}
__device__ __forceinline__ void load_chunk(uint32_t dst, int seg, int G, uint32_t bar) {
  mbar_expect(bar, 4096);
  bulk_g2s(dst, g_h + (size_t)(seg * 16 + G) * 4096, 4096, bar);
}
__device__ __forceinline__ void load_red(uint32_t* v, const float* p) {
#pragma unroll
  for (int j = 0; j < 2; j++)
    asm volatile("ld.relaxed.gpu.global.v4.u32 {%0, %1, %2, %3}, [%4];"
                 : "=r"(v[4 * j]), "=r"(v[4 * j + 1]), "=r"(v[4 * j + 2]), "=r"(v[4 * j + 3]) : "l"(p + j * 256) : "memory");
}
__device__ __forceinline__ bool red_done(const uint32_t* v) { return __all_sync(0xffffffffu, (v[3] & v[7]) == 0x42000000u); }
__device__ __forceinline__ uint32_t finish_red(uint32_t* v, const float* p) {
  uint32_t tries = 0;
  if (__builtin_expect(!red_done(v), 0)) {
    do { if (++tries > 20000000u) __trap(); load_red(v, p); } while (!red_done(v));
  }
  return tries;
}
__device__ __forceinline__ void exp10(float* sv, const uint32_t* x) {
  constexpr float SC = 0.08838834764831845f * 1.4426950408889634f;
  uint32_t m2 = hmax2(hmax2(hmax2(x[0], x[1]), hmax2(x[2], x[3])), x[4]);
  m2 = hmax2(m2, __shfl_xor_sync(0xffffffffu, m2, 1));
  m2 = hmax2(m2, __shfl_xor_sync(0xffffffffu, m2, 2));
  const float nm = -fmaxf(bf_lo(m2), bf_hi(m2)) * SC;
#pragma unroll
  for (int j = 0; j < 5; j++) { sv[2 * j] = ex2(fmaf(bf_lo(x[j]), SC, nm)); sv[2 * j + 1] = ex2(fmaf(bf_hi(x[j]), SC, nm)); }
}

__device__ __forceinline__ uint32_t arm_size(int w, bool isC) {
  return w == 0 ? (isC ? 1280 : 640) : w == 1 ? (isC ? 0 : 2048) : w == 2 ? (isC ? 0 : 8192) : (isC ? 0 : 1792);
}
struct RDesc { uint64_t tok[32], tail_b[16], tail_a[32]; };

template <int WG>
__device__ __forceinline__ void r_main(const uint32_t (&W)[48][4], const RDesc& dsc, int head, uint32_t rank, int lane_, int w) {
  const uint32_t sb = (rank << 24) + 0x400, bars = sb + R_BAR;
  const uint32_t to1 = rank == 0 ? 2u << 24 : 0u - (1u << 24), to2 = rank == 2 ? 0u - (2u << 24) : 1u << 24;
  const bool isC = rank == 2;
  const int lane = opaque32(lane_), warp = WG * 4 + w;
  const int gl = rot_chunk(4 * (lane & 3) + w, rank);
  const int g0 = __shfl_sync(0xffffffffu, gl, 0), g1 = __shfl_sync(0xffffffffu, gl, 1), g2 = __shfl_sync(0xffffffffu, gl, 2);
  const uint32_t arm_bytes = arm_size(w, isC);

#define L16 opaque32(sb + opaque32(lane) * 16)
#define L8 opaque32(sb + opaque32(lane) * 8)
#define L4 opaque32(sb + opaque32(lane) * 4)
#define LV opaque32(sb + R_VT + ((opaque32(lane) >> 3) & 1) * 512 + (opaque32(lane) >> 4) * 128 + (opaque32(lane) & 7) * 16)
#define SLOT(st) opaque64(slot0 + ((st) & 3) * 12288 + ((st) & 4) * 32)
  float* const slot0 = opaque64(g_slot + (rank * 1024 + warp * 128 + lane) * 4);
  const uint32_t woa = opaque32(sb + R_WO + warp * 12288 + ((lane >> 4) * 8 + (lane & 7)) * 32 + ((((lane >> 3) ^ (lane >> 2)) & 1) << 4));
  const bool has_wo = WG == 0 || isC || w < 3;
  float acc[20];
  uint32_t pk[8] = {0u, 0u, 0u, 0u, 0u, 0u, 0u, 0u};

  auto forward = [&](auto rd, const uint32_t* v, int st, uint32_t tries) {
    constexpr int RD = decltype(rd)::value;
    uint32_t u[6];
#pragma unroll
    for (int j = 0; j < 6; j++) u[j] = movm(v[4 * (j / 3) + j % 3]);
    const bool all3 = RD == 0 || w < 3;
    if (RD == 0) {
      const uint32_t a = L16 + R_M1 + w * 768, a2 = L8 + R_M1 + 512 + w * 768;
      st_async4(a + to1 + 3072, u, bars + to1 + B_MB + 8); st_async2(a2 + to1 + 3072, u[4], u[5], bars + to1 + B_MB + 8);
      sts128(a, u[0], u[1], u[2], u[3]); sts64(a2, u[4], u[5]);
      __syncwarp();
      if (elect_one()) mbar_arrive(bars + B_MB);
      st_async4(a + to2 + 6144, u, bars + to2 + B_MB + 16); st_async2(a2 + to2 + 6144, u[4], u[5], bars + to2 + B_MB + 16);
    } else {
      const uint32_t a = L4 + R_M2 + rank * 2304 + w * 768;
#pragma unroll
      for (int j = 0; j < 6; j++) if (j < 2 || all3) st_async1(a + to1 + j * 128, u[j], bars + to1 + B_MB + 24);
#pragma unroll
      for (int j = 0; j < 6; j++) if (j < 2 || all3) st_async1(a + to2 + j * 128, u[j], bars + to2 + B_MB + 24);
      if (SELF_STAS) {
#pragma unroll
        for (int j = 0; j < 6; j++) if (j < 2 || all3) st_async1(a + j * 128, u[j], bars + B_MB + 24);
      } else {
#pragma unroll
        for (int j = 0; j < 6; j++) if (j < 2 || all3) sts32(a + j * 128, u[j]);
        __syncwarp();
        if (elect_one()) mbar_arrive(bars + B_MB + 24);
      }
    }
  };

  auto send_vt = [&]() {
    if (elect_one()) {
      const uint32_t src = sb + R_VT + warp * 1024;
      bulk_s2s(src + to1, src, 1024, bars + to1 + B_VT);
      bulk_s2s(src + to2, src, 1024, bars + to2 + B_VT);
    }
  };
  auto store_att = [&](int sg) {
    uint32_t* op = reinterpret_cast<uint32_t*>(g_att + (size_t)((sg >> 2) * 64 + head * 2 + rank) * 16384 + (2 * w * 16 + (sg & 3) * 4) * 128) + opaque32(lane);
#pragma unroll
    for (int j = 0; j < 8; j++) op[(j & 1) * 512 + (j >> 1) * 32] = pk[j];
  };

  if (WG == 0) bar_arrive<NB_G, 256>();
#pragma unroll 1
  for (int s = -1; s < NSEG; s++) {
    const uint32_t par = (s + 1) & 1;
    const uint32_t last = s == NSEG - 1;
    TRACE(0);
    {
      float c[NCH][4];
      uint32_t b[3][6];
      const uint32_t ma = L16, m8 = L8;
#pragma unroll
      for (int i = 0; i < 18; i++) {
        if (i < 16) {
          if (i % 4 == 0 && !(i == 4 && TOP2)) mbar_wait(bars + B_MB + (i / 4) * 8, par ^ 1);
          if (i == 0 && TOP2) mbar_wait(bars + B_MB + 8, par ^ 1);
          if (i % 4 == 0) TRACE(1 + i / 4);
          if (i < 12) { lds128(b[i % 3], ma + R_M1 + i * 768); lds64(b[i % 3] + 4, m8 + R_M1 + 512 + i * 768); }
          else { ldsm4(b[i % 3], ma + R_M2 + 4096 + (i - 12) * 768); ldsm2(b[i % 3] + 4, ma + R_M2 + 4096 + 512 + (i - 12) * 768); }
          if (WG == 1 && i == BX_I) {
            bar_sync<NB_G, 256>();
            if (!last && elect_one()) load_chunk(sb + R_GB + w * 4096, s + 1, g0, bars + B_FB);
          }
          if (i == CX_I) {
            if (isC && s >= 0) send_vt();
            if (WG == 1 && ATT_LATE && !isC && s > 0) store_att(s - 1);
          }
          __syncwarp();
        }
        if (i >= 2) {
          const int j = i - 2;
#pragma unroll
          for (int q = 0; q < 3; q++) {
            const uint32_t* f = W[3 * j + q];
            if (3 * j + q < NCH) hmma0(c[3 * j + q], f[0], f[1], f[2], f[3], b[j % 3][2 * q], b[j % 3][2 * q + 1]);
            else hmma(c[(3 * j + q) % NCH], f[0], f[1], f[2], f[3], b[j % 3][2 * q], b[j % 3][2 * q + 1]);
          }
        }
        if (i == 14) zero_regs<16>(acc);
        if (i == 16) mbar_wait(bars + B_FA, last);
      }
#pragma unroll
      for (int j = 0; j < 4; j++) acc[16 + j] = NCH == 3 ? (c[0][j] + c[1][j]) + c[2][j] : (c[0][j] + c[1][j]) + (c[2][j] + c[NCH - 1][j]);
    }
    TRACE(5);
    bar_sync<NB_H, 256>();
    WG_FENCE();
#pragma unroll
    for (int k = 0; k < 16; k++) wg_ss40<0>(acc, dsc.tail_a[WG * 16 + k], dsc.tail_b[k]);
    WG_COMMIT();
    uint32_t vt[4][4];
    {
      const uint32_t a = opaque32(L4 + w * 256 + (isC ? WG * 1024 + R_VM : R_QK + 4096 + WG * 5120));
      const uint32_t qa = L16 + R_QK, xa = opaque32(LV + w * 2048 + (WG == 0 ? 0 : (opaque32(lane) & 8) * 64 + R_QK + 5120 - R_VT));
      const uint32_t d = opaque32(L4 + R_XS + rank * 640 + w * 256);
      if (s == 0) {
        mbar_wait_safe(bars + B_WO, 0);
        if (!GO_EARLY && WG == 1 && head == 0 && rank == 0 && w == 0 && elect_one()) red_add_u32(&g_flags[FL_GO], 1);
      }
      mbar_wait(bars + B_FB, last);
      if (WG == 0) mbar_wait(bars + B_VT, par);
      WG_WAIT(0);
      reg_fence<20>(acc);
      TRACE(6);
      const uint32_t p0 = pack2(acc[16], acc[17]), p1 = pack2(acc[18], acc[19]);
      sts32(a, p0); sts32(a + 128, p1);
      if (isC) {
        st_async1(a + to1, p0, bars + B_VM + to1); st_async1(a + to1 + 128, p1, bars + B_VM + to1);
        st_async1(a + to2, p0, bars + B_VM + to2); st_async1(a + to2 + 128, p1, bars + B_VM + to2);
      }
      if (WG == 0) {
        bar_arrive<NB_A, 256>();
        if (Q_FENCE && !isC) fence_async_smem();
#pragma unroll
        for (int i = 0; i < 4; i++) ldsm4(vt[i], xa + (i >> 1) * 1024 + (i & 1) * 256);
        bar_sync<NB_S, 256>();
      } else {
        bar_sync<NB_A, 256>();
        if (!isC) {
          if (w < 3) {
            uint32_t q[8], k[4][4];
            ldsm4t(q, qa + 4096); ldsm4t(k[0], xa); ldsm4t(k[1], xa + 256);
            ldsm4t(q + 4, qa + 4096 + 512); ldsm4t(k[2], xa + 512); ldsm4t(k[3], xa + 768);
            float x[4], y[4];
            hmma0(x, k[0][0], k[0][1], k[0][2], k[0][3], q[0], q[1]); hmma0(y, k[1][0], k[1][1], k[1][2], k[1][3], q[2], q[3]);
            hmma(x, k[2][0], k[2][1], k[2][2], k[2][3], q[4], q[5]); hmma(y, k[3][0], k[3][1], k[3][2], k[3][3], q[6], q[7]);
            const uint32_t s0 = pack2(x[0] + y[0], x[1] + y[1]), s1 = pack2(x[2] + y[2], x[3] + y[3]);
            st_async1(d + to1, s0, bars + B_XS + to1);
            st_async1(d + to2, s0, bars + B_XS + to2);
            if (w < 2) { st_async1(d + to1 + 128, s1, bars + B_XS + to1); st_async1(d + to2 + 128, s1, bars + B_XS + to2); sts32(d + 128, s1); }
            sts32(d, s0);
          }
        }
        bar_arrive<NB_S, 256>();
      }
    }
    if (WG == 1) {
      if (!last && elect_one()) load_chunk(sb + R_GA + w * 4096, s + 1, g1, bars + B_FA);
      {
        if (w > 0 && elect_one()) mbar_expect(bars + B_MB + 8 * w, w < 3 ? 3072 : SELF_STAS ? 28 * 256 : isC ? 18 * 256 : 19 * 256);
      }
      fence_async_smem();
      bar_sync<NB_B, 256>();
    }
    TRACE(7);
    WG_FENCE();
#pragma unroll
    for (int k = 0; k < 16; k++) wg_rs32<1>(acc, W[k][0], W[k][1], W[k][2], W[k][3], dsc.tok[16 + k]);
    WG_COMMIT();
    uint32_t wa[3][4];
    const uint32_t oxa = L16 + R_OX;
    if (WG == 0) {
      const uint32_t vma = oxa - (R_OX - R_VM) + w * 512, oa = opaque32(L4 + w * 512 + R_OX);
      TRACE(8);
      mbar_wait(bars + B_XS, par);
      TRACE(9);
      float sv[10];
      {
        uint32_t x[10];
        ldsm4t(x, oxa - (R_OX - R_XS)); ldsm4t(x + 4, oxa - (R_OX - R_XS) + 512); ldsm2t(x + 8, oxa - (R_OX - R_XS) + 1024);
        bar_arrive<NB_B, 256>();
#pragma unroll
        for (int j = 0; j < 5; j++) x[j] = hadd2(x[j], x[j + 5]);
        exp10(sv, x);
      }
      WG_WAIT(0);
      bar_arrive<NB_X, 256>();
      mbar_wait(bars + B_VM, par);
      uint32_t vm[4];
      ldsm4(vm, vma);
      uint32_t pb[5];
#pragma unroll
      for (int j = 0; j < 5; j++) pb[j] = pack2(sv[2 * j], sv[2 * j + 1]);
      TRACE(10);
      float o0[4], o1[4], sm[4];
      const uint32_t ONE = 0x3f803f80u;
      hmma0(o0, vt[0][0], vt[0][1], vt[0][2], vt[0][3], pb[0], pb[1]);
      hmma0(o1, vt[2][0], vt[2][1], vt[2][2], vt[2][3], pb[0], pb[1]);
      hmma0(sm, ONE, ONE, ONE, ONE, pb[0], pb[1]);
      hmma(sm, ONE, ONE, ONE, ONE, pb[2], pb[3]);
      hmma(o0, vt[1][0], vt[1][1], vt[1][2], vt[1][3], pb[2], pb[3]);
      hmma(o1, vt[3][0], vt[3][1], vt[3][2], vt[3][3], pb[2], pb[3]);
      hmma_k8(sm, ONE, ONE, pb[4]);
      hmma_k8(o0, vm[0], vm[1], pb[4]);
      hmma_k8(o1, vm[2], vm[3], pb[4]);
#pragma unroll
      for (int i = 0; i < 3; i++) ldsm4t(wa[i], woa + i * 4096);
      __syncwarp();
      const float i0 = rcp(sm[0]), i1 = rcp(sm[1]);
      sts32(oa, pack2(o0[0] * i0, o0[1] * i1)); sts32(oa + 128, pack2(o0[2] * i0, o0[3] * i1));
      sts32(oa + 256, pack2(o1[0] * i0, o1[1] * i1)); sts32(oa + 384, pack2(o1[2] * i0, o1[3] * i1));
      TRACE(11);
      bar_sync<NB_C, 128>();
    } else {
      if (!isC) {
        constexpr uint64_t dQ = mkdesc(0x400 + R_QK, 128, 1024, 0), dK = mkdesc(0x400 + R_QK + 5120, 128, 1024, 0);
        float sc[16];
        zero_regs<16>(sc);
        WG_FENCE();
#pragma unroll
        for (int k = 0; k < 4; k++) wg_ss32<1>(sc, dK + k * 16, dQ + k * 16);
        WG_COMMIT();
        const uint32_t top = rank == 0 ? to2 : to1, e = L4 + R_P + w * 256;
        WG_WAIT(0);
        bar_sync<NB_X, 256>();
        if (!last && elect_one()) load_chunk(sb + R_GB + w * 4096, s + 1, g2, bars + B_FB);
        reg_fence<16>(sc);
        if (w < 3) {
#pragma unroll
          for (int j = 0; j < 8; j++) {
            if ((j & 1) ? (j > 1 && (w == 0 || (w == 1 && j == 7))) : (j >= 4 || w != 1)) {
              const uint32_t t = pack2(sc[2 * j], sc[2 * j + 1]), o = (j >> 1) * 768 + (j & 1) * 128;
              st_async1(e + top + 3072 + o, t, bars + top + B_TS);
              sts32(e + o, t);
            }
          }
          __syncwarp();
          if (elect_one()) mbar_arrive(bars + B_TS);
        }
      } else {
        WG_WAIT(0);
        bar_sync<NB_X, 256>();
        if (!last && elect_one()) load_chunk(sb + R_GB + w * 4096, s + 1, g2, bars + B_FB);
      }
      TRACE(8);
      mbar_wait(bars + B_FA, 1);
      TRACE(11);
    }
    if (has_wo) {
      float* rslot = SLOT(s);
      uint32_t ob[4][4];
      float c[3][4];
      if (WG == 1) {
#pragma unroll
        for (int i = 0; i < 3; i++) ldsm4t(wa[i], woa + i * 4096);
        bar_sync<NB_D, 256>();
      }
      ldsm4t(ob[0], oxa);
      __syncwarp();
#pragma unroll
      for (int k = 0; k < 8; k++) {
        uint32_t nx[3][4];
        if ((k & 1) == 0 && k < 6) { ldsm4t(ob[(k >> 1) + 1], oxa + ((k >> 1) + 1) * 512); __syncwarp(); }
#pragma unroll
        for (int i = 0; i < 3; i++) {
          const uint32_t* o = ob[k >> 1] + (k & 1) * 2;
          if (k < 7) { ldsm4t(nx[i], woa + i * 4096 + (k + 1) * 512); if (i == 2) __syncwarp(); }
          if (k == 0) hmma0(c[i], wa[i][0], wa[i][1], wa[i][2], wa[i][3], o[0], o[1]);
          else hmma(c[i], wa[i][0], wa[i][1], wa[i][2], wa[i][3], o[0], o[1]);
#pragma unroll
          for (int q = 0; q < 4; q++) if (k < 7) wa[i][q] = nx[i][q];
        }
        if (k == ND_K && WG == 0) bar_arrive<NB_D, 256>();
      }
      const float* cv = &c[0][0];
      uint32_t r[6];
#pragma unroll
      for (int j = 0; j < 6; j++) r[j] = pack2(cv[2 * j], cv[2 * j + 1]);
      asm volatile("{\n.reg .pred p;\nsetp.lt.s32 p, %8, 0;\n@p bra.uni SKIP;\n"
                   "red.relaxed.gpu.global.add.noftz.v4.bf16x2 [%0], {%1, %2, %3, %7};\n"
                   "red.relaxed.gpu.global.add.noftz.v4.bf16x2 [%0+1024], {%4, %5, %6, %7};\nSKIP:\n}"
                   :: "l"(rslot), "r"(r[0]), "r"(r[1]), "r"(r[2]), "r"(r[3]), "r"(r[4]), "r"(r[5]), "r"(0x3f800000), "r"(s) : "memory");
    } else {
      bar_arrive<NB_D, 256>();
      if ((s & 3) == 0) {
        fence_gpu();
        if (s > 0 && elect_one()) red_add_u32(&g_flags[FL_ATT + 2 * (s - 4)], 1);
      }
      if (PFD && head < 8 && (PFD > 90 || s + PFD < NSEG) && elect_one())
        asm volatile("cp.async.bulk.prefetch.L2.global [%0], 4096;" :: "l"(g_h + (size_t)((PFD > 90 ? 0 : s + PFD) * 16 + head * 2 + rank) * 4096) : "memory");
      if (rank == 0 || head < 16)
        reinterpret_cast<uint4*>(g_slot)[((s + CLR_D) & 3) * 3072 + ((s + CLR_D) & 4) * 8 + rank * 2048 + head * 64 + opaque32(lane)] = make_uint4(0, 0, 0, 0);
    }
    const uint32_t t_red = clk32();
    uint32_t v[8];
    const float* slot = SLOT(s);
    TRACE(13);
    if (WG == 0) {
      if (!isC) {
        const int ln = opaque32(lane), kg = w - (ln >> 3);
        const uint32_t r16 = sb + R_P + w * 768 + (ln & 7) * 16;
        const uint32_t ta = r16 + (kg >= 0 ? kg * 128 : 640);
        const int dg = (ln >> 2) - 2 * (ln & 3);
        const uint32_t keep = dg > 0 ? 0xffffffffu : dg == 0 ? 0x0000ffffu : 0u;
        mbar_wait(bars + B_TS, par);
        uint32_t x[6], y[4];
        ldsm4t(x, ta); ldsm4t(y, ta + 3072); ldsm2t(x + 4, r16 + 512 + ((ln >> 3) & 1) * 3072);
#pragma unroll
        for (int j = 0; j < 5; j++) x[j] = hadd2(x[j], j < 4 ? y[j] : x[5]);
        x[0] = (x[0] & keep) | (0xff80ff80u & ~keep);
        float sv[10];
        exp10(sv, x);
        float sum = (((sv[0] + sv[1]) + (sv[2] + sv[3])) + ((sv[4] + sv[5]) + (sv[6] + sv[7]))) + (sv[8] + sv[9]);
        sum += __shfl_xor_sync(0xffffffffu, sum, 1);
        sum += __shfl_xor_sync(0xffffffffu, sum, 2);
        const float inv = rcp(sum);
#pragma unroll
        for (int j = 0; j < 5; j++) x[j] = pack2(sv[2 * j] * inv, sv[2 * j + 1] * inv);
        stsm4(r16 + (kg & 3) * 128, x);
        sts32(sb + ln * 4 + w * 768 + R_P + 512, x[4]);
        fence_async_smem();
        bar_arrive<NB_P, 256>();
      }
      while (clk32() - t_red < POLL_DELAY) {}
      load_red(v, slot);
      bar_sync<NB_E, 256>();
    } else {
      mbar_wait(bars + B_FB, 1);
    }
    TRACE(14);
    float ao[16];
    if (WG == 1) zero_regs<16>(ao);
    WG_FENCE();
#pragma unroll
    for (int k = 0; k < 32; k++) {
      if (WG == 0 && k == 16) WG_COMMIT();
      wg_rs32<1>(acc, W[16 + k][0], W[16 + k][1], W[16 + k][2], W[16 + k][3], dsc.tok[k]);
    }
    WG_COMMIT();
    TRACE(12);
    if (WG == 1) {
      if (!isC) {
        constexpr uint64_t dP = mkdesc(0x400 + R_P, 128, 768, 0);
        const uint64_t dV = mkdesc(0x400 + R_VT, 128, 512, 0) + rank * 256, dM = mkdesc(0x400 + R_VM, 0, 128, 0) + rank * 64;
        bar_sync<NB_P, 256>();
        WG_FENCE();
        wg_ss32<0>(ao, dV, dP); wg_ss32<0>(ao, dV + 16, dP + 16); wg_ss32<0>(ao, dM, dP + 32);
        WG_COMMIT();
      }
      bar_arrive<NB_E, 256>();
      if (elect_one()) mbar_expect(bars + B_XS + 8 * w, arm_bytes);
      while (clk32() - t_red < POLL_DELAY1) {}
      load_red(v, slot);
      bar_arrive<NB_W0, 128>();
    } else {
      WG_WAIT(1);
      bar_arrive<NB_F, 256>();
      sched_fence(head, 100);
      v[3] = opaque32(v[3]);
      const uint32_t tries = finish_red(v, slot);
      forward(std::integral_constant<int, 0>(), v, s, tries);
      TRACE(16);
    }
    WG_WAIT(0);
    reg_fence<16>(acc);
    if (WG == 0) bar_arrive<NB_G, 256>();
    TRACE(15);
    {
      uint32_t pq[8];
#pragma unroll
      for (int j = 0; j < 8; j++) pq[j] = pack2(acc[2 * j], acc[2 * j + 1]);
      if (WG == 1) {
        reg_fence<16>(ao);
#pragma unroll
        for (int j = 0; j < 8; j++) pk[j] = pack2(ao[2 * j], ao[2 * j + 1]);
      }
      if (!isC) {
        const uint32_t q = L4 + w * 256 + R_QK + WG * 5120;
#pragma unroll
        for (int j = 0; j < 8; j++) sts32(q + (j >> 1) * 1024 + (j & 1) * 128, pq[j]);
        if (WG == 1 && !ATT_LATE && s >= 0) store_att(s);
      } else {
        const uint32_t a = LV + warp * 1024;
        stsm4(a, pq); stsm4(a + 256, pq + 4);
      }
    }
    TRACE(17);
    if (WG == 1) {
      auto refill = [&]() {
        bar_sync<NB_F, 256>();
        if (s < NSEG - 2 && elect_one()) load_chunk(sb + R_GA + w * 4096, s + 2, 12 + w, bars + B_FA);
      };
      if (RF_FIRST) refill();
      if (has_wo) { v[3] = opaque32(v[3]); const uint32_t tries = finish_red(v, slot); forward(std::integral_constant<int, 1>(), v, s, tries); }
      if (!RF_FIRST) refill();
      TRACE(16);
    }
    if (isC && V_FENCE) { fence_async_smem(); __syncwarp(); }
    TRACE(18);
  }
  if (WG == 1 && ATT_LATE && !isC) store_att(NSEG - 1);
  if (WG == 1) bar_sync<NB_G, 256>();
  mbar_wait_safe(bars + B_MB + 8, 0); mbar_wait_safe(bars + B_MB + 16, 0); mbar_wait_safe(bars + B_MB + 24, 0);
#undef L16
#undef L8
#undef L4
#undef SLOT
#undef LV
}

__global__ void __cluster_dims__(3, 1, 1) __launch_bounds__(256, 1)
kernel_R(const __grid_constant__ CUtensorMap tmq, const __grid_constant__ CUtensorMap tmk, const __grid_constant__ CUtensorMap tmv,
         const __grid_constant__ CUtensorMap tmo, const __grid_constant__ CUtensorMap tmm, const __nv_bfloat16* __restrict__ x,
         const __nv_bfloat16* __restrict__ mem0, const __nv_bfloat16* __restrict__ cvec, const __grid_constant__ RDesc dsc) {
  extern __shared__ __align__(1024) uint8_t smem[];
  const uint32_t sb = smem_u32(smem);
  uint32_t rank; asm("mov.u32 %0, %%cluster_ctarank;" : "=r"(rank));
  rank = __shfl_sync(0xffffffffu, rank, 0);
  const int cta = blockIdx.x, head = __shfl_sync(0xffffffffu, cta / 3, 0);
  const int tid = threadIdx.x, lane = tid & 31;
  const int warp = __shfl_sync(0xffffffffu, tid >> 5, 0);
  const int wg = warp >> 2, w = warp & 3;
  const uint32_t bars = sb + R_BAR;
  const CUtensorMap* tmw = rank == 2 ? &tmv : (wg == 0 ? &tmq : &tmk);
  const int fcol = head * 128 + (rank == 2 ? wg * 64 : (int)rank * 64);

  asm volatile("griddepcontrol.launch_dependents;");
  uint32_t W[48][4];
  {
    if (sb != (rank << 24) + 0x400) __trap();
    if (tid == 0) {
      sts64(bars + 248, rank, head);
      mbar_init(bars + B_MB, 4); mbar_init(bars + B_MB + 8, 1); mbar_init(bars + B_MB + 16, 1); mbar_init(bars + B_MB + 24, SELF_STAS ? 1 : rank == 2 ? 5 : 4);
      for (int i = B_XS; i <= B_X; i += 8) mbar_init(bars + i, i == B_FA || i == B_FB || (i == B_TS && rank < 2) ? 4 : 1);
      asm volatile("fence.mbarrier_init.release.cluster;" ::: "memory");
      fence_async_smem();
    }
    __syncthreads();
    asm volatile("barrier.cluster.arrive.relaxed.aligned;" ::: "memory");
    TS(0);
    const int nwm = rank == 0 ? 6 : 5, wm0 = rank == 0 ? 0 : 5 * rank + 1, nrg = cta < 64 ? 3 : 2;
    if (elect_one()) {
      if (warp == 0) { mbar_expect(bars + B_WM, nwm * 8192); mbar_expect(bars + B_X, nrg * 16384); }
      if (warp < nwm) tma2d_once(sb + R_GA + warp * 8192, &tmm, head * 64, (wm0 + warp) * 64, bars + B_WM);
#pragma unroll 1
      for (int r = 0; r < nrg; r++) bulk_g2s(sb + R_TAIL + (r * 8 + warp) * 2064, x + (size_t)((cta + 96 * r) * 8 + warp) * D_, 2048, bars + B_X);
      if (w == 0) mbar_expect(bars + B_STG + wg * 16, 49152);
      if (w < 2) tma2d_once(sb + R_WO + wg * 49152 + w * 8192, tmw, fcol, rot_chunk(w, rank) * 64, bars + B_STG + wg * 16);
    }
    float* scr = reinterpret_cast<float*>(smem + R_VT);
#pragma unroll 1
    for (int i = tid; i < nwm * 64; i += 256) {
      const float c = __bfloat162float(cvec[wm0 * 64 + i]);
      scr[i] = __bfloat162float(__float2bfloat16(c / (1.f + __expf(-c))));
    }
    if (tid < 128) {
      uint32_t e[4] = {0u, 0u, 0u, 0u};
      if (cta >= 72 && (tid & 32)) {
        const uint16_t* mp = reinterpret_cast<const uint16_t*>(mem0) + 2 * (lane & 3) * D_ + (lane >> 2);
#pragma unroll
        for (int q = 0; q < 3; q++) {
          const int n = 3 * (tid >> 6) + q, col = wo_tile(3 * (cta & 7) + (n >> 1), (cta - 72) >> 3) * 16 + 8 * (n & 1);
          e[q] = mp[col] | (uint32_t)mp[col + D_] << 16;
        }
        e[3] = 0x42000000u;
      }
      reinterpret_cast<uint4*>(g_slot)[cta * 128 + tid] = make_uint4(e[0], e[1], e[2], e[3]);
    }
    __syncthreads();
    TS(1);
    mbar_wait_safe(bars + B_WM, 0);
    if (elect_one()) tma2d_once(sb + R_WO + wg * 49152 + (2 + w) * 8192, tmw, fcol, rot_chunk(2 + w, rank) * 64, bars + B_STG + wg * 16);
    {
      float a[8];
#pragma unroll
      for (int j = 0; j < 8; j++) a[j] = 0.f;
#pragma unroll 2
      for (int i = 0; i < 2 * nwm; i++) {
        uint32_t u[4];
        lds128(u, sb + R_GA + i * 4096 + tid * 16);
        const float sc = scr[i * 32 + (tid >> 3)];
#pragma unroll
        for (int j = 0; j < 4; j++) { a[2 * j] += sc * bf_lo(u[j]); a[2 * j + 1] += sc * bf_hi(u[j]); }
      }
#pragma unroll
      for (int j = 0; j < 8; j++) { a[j] += __shfl_xor_sync(0xffffffffu, a[j], 8); a[j] += __shfl_xor_sync(0xffffffffu, a[j], 16); }
      if (lane < 8) {
        sts128(sb + R_VT + 1536 + warp * 256 + lane * 32, __float_as_uint(a[0]), __float_as_uint(a[1]), __float_as_uint(a[2]), __float_as_uint(a[3]));
        sts128(sb + R_VT + 1552 + warp * 256 + lane * 32, __float_as_uint(a[4]), __float_as_uint(a[5]), __float_as_uint(a[6]), __float_as_uint(a[7]));
      }
    }
    __syncthreads();
    TS(2);
    if (warp == 7) {
      float t0 = 0.f, t1 = 0.f;
#pragma unroll
      for (int i = 0; i < 8; i++) { float t[2]; lds64f(t, sb + R_VT + 1536 + i * 256 + lane * 8); t0 += t[0]; t1 += t[1]; }
      reinterpret_cast<float2*>(g_modp + rank * 2048 + head * 64)[lane] = make_float2(t0, t1);
      fence_gpu();
      __syncwarp();
      if (lane == 0) red_add_u32(&g_flags[FL_S1], 1);
      __syncwarp();
    }
    mbar_wait_safe(bars + B_X, 0);
#pragma unroll 1
    for (int r = 0; r < nrg; r++) {
      float f[32];
#pragma unroll
      for (int i = 0; i < 4; i++) {
        uint32_t u[4];
        lds128(u, sb + R_TAIL + (r * 8 + warp) * 2064 + i * 512 + lane * 16);
#pragma unroll
        for (int j = 0; j < 4; j++) { f[8 * i + 2 * j] = bf_lo(u[j]); f[8 * i + 2 * j + 1] = bf_hi(u[j]); }
      }
      float t = 0.f;
#pragma unroll
      for (int i = 0; i < 32; i++) t += f[i];
#pragma unroll
      for (int o = 1; o < 32; o <<= 1) t += __shfl_xor_sync(0xffffffffu, t, o);
      const float mean = t * (1.f / D_);
      t = 0.f;
#pragma unroll
      for (int i = 0; i < 32; i++) t = fmaf(f[i] - mean, f[i] - mean, t);
#pragma unroll
      for (int o = 1; o < 32; o <<= 1) t += __shfl_xor_sync(0xffffffffu, t, o);
      const float rstd = rsqrtf(t * (1.f / D_) + 1e-5f);
      if (lane == 0) sts64(sb + R_VT + 3584 + (r * 8 + warp) * 8, __float_as_uint(rstd), __float_as_uint(-mean * rstd));
    }
    TS(3);
    if (w < PF1 && elect_one()) tma2d_prefetch(tmw, fcol, rot_chunk(6 + w, rank) * 64);
    if (tid == 0) wait_flag(&g_flags[FL_S1], 96);
    __syncthreads();
    TS(4);
    {
      float4 p[6];
#pragma unroll
      for (int i = 0; i < 6; i++) p[i] = __ldcg(reinterpret_cast<const float4*>(g_modp + (i >> 1) * 2048) + 2 * tid + (i & 1));
      if (w < PF2 && elect_one()) tma2d_prefetch(tmw, fcol, (9 + w) * 64);
      sts128(sb + R_VT + 5120 + tid * 16, pack2(p[0].x + p[2].x + p[4].x, p[0].y + p[2].y + p[4].y), pack2(p[0].z + p[2].z + p[4].z, p[0].w + p[2].w + p[4].w),
             pack2(p[1].x + p[3].x + p[5].x, p[1].y + p[3].y + p[5].y), pack2(p[1].z + p[3].z + p[5].z, p[1].w + p[3].w + p[5].w));
    }
    __syncthreads();
#pragma unroll 2
    for (int it = 0; it < 4 * nrg; it++) {
      const int r = it >> 2, rg = cta + 96 * r, c = 16 * warp + (lane >> 3) + 4 * (it & 3);
      uint32_t a[4], b[4], u[4], o[4];
      float t[2];
      lds128(u, sb + R_TAIL + (r * 8 + (lane & 7)) * 2064 + c * 16);
      lds128(a, sb + R_VT + 5120 + c * 16); lds128(b, sb + R_VT + 7168 + c * 16);
      lds64f(t, sb + R_VT + 3584 + (r * 8 + (lane & 7)) * 8);
#pragma unroll
      for (int j = 0; j < 4; j++)
        o[j] = pack2(fmaf(fmaf(bf_lo(u[j]), t[0], t[1]), 1.f + bf_lo(b[j]), bf_lo(a[j])), fmaf(fmaf(bf_hi(u[j]), t[0], t[1]), 1.f + bf_hi(b[j]), bf_hi(a[j])));
      *reinterpret_cast<uint4*>(g_h + (size_t)(rg >> 2) * 65536 + (lane & 7) * 16 + (c & 7) * 128 +
                                (c < 96 ? (c >> 3) * 4096 + (rg & 3) * 1024 : 49152 + (rg & 3) * 4096 + ((c >> 3) - 12) * 1024)) =
          make_uint4(o[0], o[1], o[2], o[3]);
    }
    TS(5);
    __syncthreads();
    TS(6);
    if (w < PF3 && elect_one()) tma2d_once(sb + R_TAIL + warp * 8192, tmw, fcol, 768 + w * 64, bars + B_TAIL);
    if (warp == 3 && lane == 0) { fence_gpu(); red_add_u32(&g_flags[FL_S2], 1); }
    __syncwarp();

    const uint32_t a0 = opaque32(sb + R_WO + wg * 49152 + ((lane >> 4) * 8 + (lane & 7)) * 128 + (((2 * w + ((lane >> 3) & 1)) ^ (lane & 7)) << 4));
    mbar_wait_safe(bars + B_STG + wg * 16, 0);
    TS(7);
#pragma unroll
    for (int i = 0; i < 24; i++) ldsm4t(W[i], a0 + i * 2048);
    if (tid == 0) wait_flag(&g_flags[FL_S2], 96);
    __syncthreads();
    asm volatile("fence.proxy.async.global;" ::: "memory");
    if (elect_one()) {
      if (wg == 0) load_chunk(sb + R_GA + w * 4096, 0, 12 + w, bars + B_FA);
      if (w == 0) mbar_expect(bars + B_STG + wg * 16 + 8, 49152);
#pragma unroll 1
      for (int c = w; c < 6; c += 4) tma2d_once(sb + R_WO + wg * 49152 + c * 8192, tmw, fcol, rot_chunk(6 + c, rank) * 64, bars + B_STG + wg * 16 + 8);
      if (warp == 0) mbar_expect(bars + B_TAIL, 65536);
      if (w >= PF3) tma2d_once(sb + R_TAIL + warp * 8192, tmw, fcol, 768 + w * 64, bars + B_TAIL);
      if (wg == 1) mbar_expect(bars + B_XS + 8 * w, w == 2 ? 0 : arm_size(w, rank == 2));
#pragma unroll 1
      for (int i = warp; i < PF4; i += 8) tma2d_prefetch(&tmo, 16 * wo_tile(i, rank), head * 128);
    }
    TS(8);
    mbar_wait_safe(bars + B_STG + wg * 16 + 8, 0);
    TS(9);
#pragma unroll
    for (int i = 0; i < 24; i++) ldsm4t(W[24 + i], a0 + i * 2048);
    __syncthreads();
    if (elect_one()) {
      const int n = rank == 2 ? 22 : 21;
      if (warp == 0) mbar_expect(bars + B_WO, n * 4096);
#pragma unroll 1
      for (int i = warp; i < n; i += 8) tma2d(sb + R_WO + i * 4096, &tmo, 16 * wo_tile(i, rank), head * 128, bars + B_WO);
    }
    sts32(sb + R_P + warp * 768 + 640 + lane * 4, wg == 0 ? 0u : 0xff80ff80u);
    mbar_wait_safe(bars + B_TAIL, 0);
    if (GO_EARLY && cta == GO_EARLY - 1 && tid == 0) red_add_u32(&g_flags[FL_GO], 1);
    asm volatile("barrier.cluster.wait.aligned;\nbarrier.cluster.arrive.relaxed.aligned;\nbarrier.cluster.wait.aligned;" ::: "memory");
  }
  uint32_t rh[2];
  lds64(rh, bars + 248);
  rh[0] = __shfl_sync(0xffffffffu, rh[0], 0); rh[1] = __shfl_sync(0xffffffffu, rh[1], 0);
  if (wg == 0) r_main<0>(W, dsc, rh[1], rh[0], lane, w);
  else r_main<1>(W, dsc, rh[1], rh[0], lane, w);
  __syncthreads();
  if (rank < 2 && threadIdx.x == 0) { fence_gpu(); red_add_u32(&g_flags[FL_ATT + 8 * 15], 1); }
  asm volatile("barrier.cluster.arrive.release.aligned;\nbarrier.cluster.wait.acquire.aligned;" ::: "memory");
}

template <int TA, bool FIRST> __device__ __forceinline__ void wg_ss256(float* d, uint64_t a, uint64_t b) {
  if (FIRST)
    asm volatile("wgmma.mma_async.sync.aligned.m64n256k16.f32.bf16.bf16 {%0,%1,%2,%3,%4,%5,%6,%7,%8,%9,%10,%11,%12,%13,%14,%15,%16,%17,%18,%19,%20,%21,%22,%23,%24,%25,%26,%27,%28,%29,%30,%31,%32,%33,%34,%35,%36,%37,%38,%39,%40,%41,%42,%43,%44,%45,%46,%47,%48,%49,%50,%51,%52,%53,%54,%55,%56,%57,%58,%59,%60,%61,%62,%63,%64,%65,%66,%67,%68,%69,%70,%71,%72,%73,%74,%75,%76,%77,%78,%79,%80,%81,%82,%83,%84,%85,%86,%87,%88,%89,%90,%91,%92,%93,%94,%95,%96,%97,%98,%99,%100,%101,%102,%103,%104,%105,%106,%107,%108,%109,%110,%111,%112,%113,%114,%115,%116,%117,%118,%119,%120,%121,%122,%123,%124,%125,%126,%127}, %128, %129, 0, 1, 1, %130, 1;"
               : "=f"(d[0]), "=f"(d[1]), "=f"(d[2]), "=f"(d[3]), "=f"(d[4]), "=f"(d[5]), "=f"(d[6]), "=f"(d[7]),
                 "=f"(d[8]), "=f"(d[9]), "=f"(d[10]), "=f"(d[11]), "=f"(d[12]), "=f"(d[13]), "=f"(d[14]), "=f"(d[15]),
                 "=f"(d[16]), "=f"(d[17]), "=f"(d[18]), "=f"(d[19]), "=f"(d[20]), "=f"(d[21]), "=f"(d[22]), "=f"(d[23]),
                 "=f"(d[24]), "=f"(d[25]), "=f"(d[26]), "=f"(d[27]), "=f"(d[28]), "=f"(d[29]), "=f"(d[30]), "=f"(d[31]),
                 "=f"(d[32]), "=f"(d[33]), "=f"(d[34]), "=f"(d[35]), "=f"(d[36]), "=f"(d[37]), "=f"(d[38]), "=f"(d[39]),
                 "=f"(d[40]), "=f"(d[41]), "=f"(d[42]), "=f"(d[43]), "=f"(d[44]), "=f"(d[45]), "=f"(d[46]), "=f"(d[47]),
                 "=f"(d[48]), "=f"(d[49]), "=f"(d[50]), "=f"(d[51]), "=f"(d[52]), "=f"(d[53]), "=f"(d[54]), "=f"(d[55]),
                 "=f"(d[56]), "=f"(d[57]), "=f"(d[58]), "=f"(d[59]), "=f"(d[60]), "=f"(d[61]), "=f"(d[62]), "=f"(d[63]),
                 "=f"(d[64]), "=f"(d[65]), "=f"(d[66]), "=f"(d[67]), "=f"(d[68]), "=f"(d[69]), "=f"(d[70]), "=f"(d[71]),
                 "=f"(d[72]), "=f"(d[73]), "=f"(d[74]), "=f"(d[75]), "=f"(d[76]), "=f"(d[77]), "=f"(d[78]), "=f"(d[79]),
                 "=f"(d[80]), "=f"(d[81]), "=f"(d[82]), "=f"(d[83]), "=f"(d[84]), "=f"(d[85]), "=f"(d[86]), "=f"(d[87]),
                 "=f"(d[88]), "=f"(d[89]), "=f"(d[90]), "=f"(d[91]), "=f"(d[92]), "=f"(d[93]), "=f"(d[94]), "=f"(d[95]),
                 "=f"(d[96]), "=f"(d[97]), "=f"(d[98]), "=f"(d[99]), "=f"(d[100]), "=f"(d[101]), "=f"(d[102]), "=f"(d[103]),
                 "=f"(d[104]), "=f"(d[105]), "=f"(d[106]), "=f"(d[107]), "=f"(d[108]), "=f"(d[109]), "=f"(d[110]), "=f"(d[111]),
                 "=f"(d[112]), "=f"(d[113]), "=f"(d[114]), "=f"(d[115]), "=f"(d[116]), "=f"(d[117]), "=f"(d[118]), "=f"(d[119]),
                 "=f"(d[120]), "=f"(d[121]), "=f"(d[122]), "=f"(d[123]), "=f"(d[124]), "=f"(d[125]), "=f"(d[126]), "=f"(d[127])
               : "l"(a), "l"(b), "n"(TA));
  else
    asm volatile("wgmma.mma_async.sync.aligned.m64n256k16.f32.bf16.bf16 {%0,%1,%2,%3,%4,%5,%6,%7,%8,%9,%10,%11,%12,%13,%14,%15,%16,%17,%18,%19,%20,%21,%22,%23,%24,%25,%26,%27,%28,%29,%30,%31,%32,%33,%34,%35,%36,%37,%38,%39,%40,%41,%42,%43,%44,%45,%46,%47,%48,%49,%50,%51,%52,%53,%54,%55,%56,%57,%58,%59,%60,%61,%62,%63,%64,%65,%66,%67,%68,%69,%70,%71,%72,%73,%74,%75,%76,%77,%78,%79,%80,%81,%82,%83,%84,%85,%86,%87,%88,%89,%90,%91,%92,%93,%94,%95,%96,%97,%98,%99,%100,%101,%102,%103,%104,%105,%106,%107,%108,%109,%110,%111,%112,%113,%114,%115,%116,%117,%118,%119,%120,%121,%122,%123,%124,%125,%126,%127}, %128, %129, 1, 1, 1, %130, 1;"
               : "+f"(d[0]), "+f"(d[1]), "+f"(d[2]), "+f"(d[3]), "+f"(d[4]), "+f"(d[5]), "+f"(d[6]), "+f"(d[7]),
                 "+f"(d[8]), "+f"(d[9]), "+f"(d[10]), "+f"(d[11]), "+f"(d[12]), "+f"(d[13]), "+f"(d[14]), "+f"(d[15]),
                 "+f"(d[16]), "+f"(d[17]), "+f"(d[18]), "+f"(d[19]), "+f"(d[20]), "+f"(d[21]), "+f"(d[22]), "+f"(d[23]),
                 "+f"(d[24]), "+f"(d[25]), "+f"(d[26]), "+f"(d[27]), "+f"(d[28]), "+f"(d[29]), "+f"(d[30]), "+f"(d[31]),
                 "+f"(d[32]), "+f"(d[33]), "+f"(d[34]), "+f"(d[35]), "+f"(d[36]), "+f"(d[37]), "+f"(d[38]), "+f"(d[39]),
                 "+f"(d[40]), "+f"(d[41]), "+f"(d[42]), "+f"(d[43]), "+f"(d[44]), "+f"(d[45]), "+f"(d[46]), "+f"(d[47]),
                 "+f"(d[48]), "+f"(d[49]), "+f"(d[50]), "+f"(d[51]), "+f"(d[52]), "+f"(d[53]), "+f"(d[54]), "+f"(d[55]),
                 "+f"(d[56]), "+f"(d[57]), "+f"(d[58]), "+f"(d[59]), "+f"(d[60]), "+f"(d[61]), "+f"(d[62]), "+f"(d[63]),
                 "+f"(d[64]), "+f"(d[65]), "+f"(d[66]), "+f"(d[67]), "+f"(d[68]), "+f"(d[69]), "+f"(d[70]), "+f"(d[71]),
                 "+f"(d[72]), "+f"(d[73]), "+f"(d[74]), "+f"(d[75]), "+f"(d[76]), "+f"(d[77]), "+f"(d[78]), "+f"(d[79]),
                 "+f"(d[80]), "+f"(d[81]), "+f"(d[82]), "+f"(d[83]), "+f"(d[84]), "+f"(d[85]), "+f"(d[86]), "+f"(d[87]),
                 "+f"(d[88]), "+f"(d[89]), "+f"(d[90]), "+f"(d[91]), "+f"(d[92]), "+f"(d[93]), "+f"(d[94]), "+f"(d[95]),
                 "+f"(d[96]), "+f"(d[97]), "+f"(d[98]), "+f"(d[99]), "+f"(d[100]), "+f"(d[101]), "+f"(d[102]), "+f"(d[103]),
                 "+f"(d[104]), "+f"(d[105]), "+f"(d[106]), "+f"(d[107]), "+f"(d[108]), "+f"(d[109]), "+f"(d[110]), "+f"(d[111]),
                 "+f"(d[112]), "+f"(d[113]), "+f"(d[114]), "+f"(d[115]), "+f"(d[116]), "+f"(d[117]), "+f"(d[118]), "+f"(d[119]),
                 "+f"(d[120]), "+f"(d[121]), "+f"(d[122]), "+f"(d[123]), "+f"(d[124]), "+f"(d[125]), "+f"(d[126]), "+f"(d[127])
               : "l"(a), "l"(b), "n"(TA));
}
template <int TA, bool FIRST> __device__ __forceinline__ void wg_ss128(float* d, uint64_t a, uint64_t b) {
  if (FIRST)
    asm volatile("wgmma.mma_async.sync.aligned.m64n128k16.f32.bf16.bf16 {%0,%1,%2,%3,%4,%5,%6,%7,%8,%9,%10,%11,%12,%13,%14,%15,%16,%17,%18,%19,%20,%21,%22,%23,%24,%25,%26,%27,%28,%29,%30,%31,%32,%33,%34,%35,%36,%37,%38,%39,%40,%41,%42,%43,%44,%45,%46,%47,%48,%49,%50,%51,%52,%53,%54,%55,%56,%57,%58,%59,%60,%61,%62,%63}, %64, %65, 0, 1, 1, %66, 1;"
               : "=f"(d[0]), "=f"(d[1]), "=f"(d[2]), "=f"(d[3]), "=f"(d[4]), "=f"(d[5]), "=f"(d[6]), "=f"(d[7]),
                 "=f"(d[8]), "=f"(d[9]), "=f"(d[10]), "=f"(d[11]), "=f"(d[12]), "=f"(d[13]), "=f"(d[14]), "=f"(d[15]),
                 "=f"(d[16]), "=f"(d[17]), "=f"(d[18]), "=f"(d[19]), "=f"(d[20]), "=f"(d[21]), "=f"(d[22]), "=f"(d[23]),
                 "=f"(d[24]), "=f"(d[25]), "=f"(d[26]), "=f"(d[27]), "=f"(d[28]), "=f"(d[29]), "=f"(d[30]), "=f"(d[31]),
                 "=f"(d[32]), "=f"(d[33]), "=f"(d[34]), "=f"(d[35]), "=f"(d[36]), "=f"(d[37]), "=f"(d[38]), "=f"(d[39]),
                 "=f"(d[40]), "=f"(d[41]), "=f"(d[42]), "=f"(d[43]), "=f"(d[44]), "=f"(d[45]), "=f"(d[46]), "=f"(d[47]),
                 "=f"(d[48]), "=f"(d[49]), "=f"(d[50]), "=f"(d[51]), "=f"(d[52]), "=f"(d[53]), "=f"(d[54]), "=f"(d[55]),
                 "=f"(d[56]), "=f"(d[57]), "=f"(d[58]), "=f"(d[59]), "=f"(d[60]), "=f"(d[61]), "=f"(d[62]), "=f"(d[63])
               : "l"(a), "l"(b), "n"(TA));
  else
    asm volatile("wgmma.mma_async.sync.aligned.m64n128k16.f32.bf16.bf16 {%0,%1,%2,%3,%4,%5,%6,%7,%8,%9,%10,%11,%12,%13,%14,%15,%16,%17,%18,%19,%20,%21,%22,%23,%24,%25,%26,%27,%28,%29,%30,%31,%32,%33,%34,%35,%36,%37,%38,%39,%40,%41,%42,%43,%44,%45,%46,%47,%48,%49,%50,%51,%52,%53,%54,%55,%56,%57,%58,%59,%60,%61,%62,%63}, %64, %65, 1, 1, 1, %66, 1;"
               : "+f"(d[0]), "+f"(d[1]), "+f"(d[2]), "+f"(d[3]), "+f"(d[4]), "+f"(d[5]), "+f"(d[6]), "+f"(d[7]),
                 "+f"(d[8]), "+f"(d[9]), "+f"(d[10]), "+f"(d[11]), "+f"(d[12]), "+f"(d[13]), "+f"(d[14]), "+f"(d[15]),
                 "+f"(d[16]), "+f"(d[17]), "+f"(d[18]), "+f"(d[19]), "+f"(d[20]), "+f"(d[21]), "+f"(d[22]), "+f"(d[23]),
                 "+f"(d[24]), "+f"(d[25]), "+f"(d[26]), "+f"(d[27]), "+f"(d[28]), "+f"(d[29]), "+f"(d[30]), "+f"(d[31]),
                 "+f"(d[32]), "+f"(d[33]), "+f"(d[34]), "+f"(d[35]), "+f"(d[36]), "+f"(d[37]), "+f"(d[38]), "+f"(d[39]),
                 "+f"(d[40]), "+f"(d[41]), "+f"(d[42]), "+f"(d[43]), "+f"(d[44]), "+f"(d[45]), "+f"(d[46]), "+f"(d[47]),
                 "+f"(d[48]), "+f"(d[49]), "+f"(d[50]), "+f"(d[51]), "+f"(d[52]), "+f"(d[53]), "+f"(d[54]), "+f"(d[55]),
                 "+f"(d[56]), "+f"(d[57]), "+f"(d[58]), "+f"(d[59]), "+f"(d[60]), "+f"(d[61]), "+f"(d[62]), "+f"(d[63])
               : "l"(a), "l"(b), "n"(TA));
}
template <int TA, bool FIRST> __device__ __forceinline__ void wg_ss64(float* d, uint64_t a, uint64_t b) {
  if (FIRST)
    asm volatile("wgmma.mma_async.sync.aligned.m64n64k16.f32.bf16.bf16 {%0,%1,%2,%3,%4,%5,%6,%7,%8,%9,%10,%11,%12,%13,%14,%15,%16,%17,%18,%19,%20,%21,%22,%23,%24,%25,%26,%27,%28,%29,%30,%31}, %32, %33, 0, 1, 1, %34, 1;"
               : "=f"(d[0]), "=f"(d[1]), "=f"(d[2]), "=f"(d[3]), "=f"(d[4]), "=f"(d[5]), "=f"(d[6]), "=f"(d[7]),
                 "=f"(d[8]), "=f"(d[9]), "=f"(d[10]), "=f"(d[11]), "=f"(d[12]), "=f"(d[13]), "=f"(d[14]), "=f"(d[15]),
                 "=f"(d[16]), "=f"(d[17]), "=f"(d[18]), "=f"(d[19]), "=f"(d[20]), "=f"(d[21]), "=f"(d[22]), "=f"(d[23]),
                 "=f"(d[24]), "=f"(d[25]), "=f"(d[26]), "=f"(d[27]), "=f"(d[28]), "=f"(d[29]), "=f"(d[30]), "=f"(d[31])
               : "l"(a), "l"(b), "n"(TA));
  else
    asm volatile("wgmma.mma_async.sync.aligned.m64n64k16.f32.bf16.bf16 {%0,%1,%2,%3,%4,%5,%6,%7,%8,%9,%10,%11,%12,%13,%14,%15,%16,%17,%18,%19,%20,%21,%22,%23,%24,%25,%26,%27,%28,%29,%30,%31}, %32, %33, 1, 1, 1, %34, 1;"
               : "+f"(d[0]), "+f"(d[1]), "+f"(d[2]), "+f"(d[3]), "+f"(d[4]), "+f"(d[5]), "+f"(d[6]), "+f"(d[7]),
                 "+f"(d[8]), "+f"(d[9]), "+f"(d[10]), "+f"(d[11]), "+f"(d[12]), "+f"(d[13]), "+f"(d[14]), "+f"(d[15]),
                 "+f"(d[16]), "+f"(d[17]), "+f"(d[18]), "+f"(d[19]), "+f"(d[20]), "+f"(d[21]), "+f"(d[22]), "+f"(d[23]),
                 "+f"(d[24]), "+f"(d[25]), "+f"(d[26]), "+f"(d[27]), "+f"(d[28]), "+f"(d[29]), "+f"(d[30]), "+f"(d[31])
               : "l"(a), "l"(b), "n"(TA));
}

constexpr int H_STAGE = 49152, H_NST = 4;
constexpr int H_STG = H_NST * H_STAGE;
constexpr int H_VEC = H_STG + 16384;
constexpr int H_BAR = H_VEC + 6144;
constexpr int H_SMEM = H_BAR + 256;
constexpr int HB_FULL = 0, HB_EMPTY = 32, HB_IFULL = 64, HB_IEMPTY = 80, HB_ITEM = 96, HB_INC = 104;
enum { IT_END = 0, IT_MOD = 1, IT_XT = 2, IT_OUT = 3, IT_UV = 4, IT_F1 = 5, IT_F2 = 6 };
constexpr int MAX_ITEMS = 1400;
#define D_MOD 4
#define D_UV 2
#define R_LATE 1
#define CH_FENCE 1
#define CH_FENCE1 1
#define N_UV1 20
#define XT_GO 0
struct HList { uint32_t n; uint32_t it[MAX_ITEMS]; };
#define HT(i)

__device__ __forceinline__ uint32_t tile_lane(int warp, int lane) { return warp * 1024 + (lane >> 2) * 64 + (((lane & 3) ^ (lane >> 3)) << 4); }
__device__ __forceinline__ constexpr uint32_t tile_off(int c, int h) { return (c >> 1) * 16384 + (c & 1) * 8192 + h * 512; }

__device__ __forceinline__ void h_pass(uint32_t sb, int nst, uint32_t& st, uint32_t& ph, bool leader) {
#pragma unroll 1
  for (int i = 0; i < nst; i++) {
    mbar_wait(sb + H_BAR + HB_FULL + st * 8, ph);
    if (leader) mbar_arrive(sb + H_BAR + HB_EMPTY + st * 8);
    if (++st == H_NST) { st = 0; ph ^= 1; }
  }
}
template <int BN, int TA, class PRE>
__device__ __forceinline__ void h_mainloop(float* acc, uint32_t sb, int nst, uint32_t& st, uint32_t& ph, int wg, bool leader, bool fixed_a, PRE pre) {
  constexpr int KS = BN == 64 ? 8 : 4;
  constexpr uint32_t BOFF = BN == 64 ? 32768 : 16384;
  const uint64_t da0 = fixed_a ? mkdesc(sb + H_STG, 16, 0, 2) : TA ? mkdesc(sb + wg * 1024, 2048, 128, 0) : mkdesc(sb + wg * 4096, 16, 512, 2);
  const uint64_t db0 = mkdesc(sb + BOFF, 8192, 1024, 1);
  const uint32_t kh = fixed_a ? 32 : 512;
  uint32_t prev = 0;
  auto stage = [&](auto first, int i) {
    constexpr bool FIRST = decltype(first)::value;
    mbar_wait(sb + H_BAR + HB_FULL + st * 8, ph);
    if (FIRST) HT(1);
    const uint64_t da = da0 + (fixed_a ? i * 64 : st * (H_STAGE >> 4)), db = db0 + st * (H_STAGE >> 4);
    WG_FENCE();
#pragma unroll
    for (int k = 0; k < KS; k++) {
      const uint64_t a = da + (k >> 2) * 1024 + (TA ? (k & 3) * 256 : ((k >> 1) & 1) * kh + (k & 1) * 2), b = db + k * 128;
      if (FIRST && k == 0) { if (BN == 256) wg_ss256<TA, true>(acc, a, b); else if (BN == 128) wg_ss128<TA, true>(acc, a, b); else wg_ss64<TA, true>(acc, a, b); }
      else { if (BN == 256) wg_ss256<TA, false>(acc, a, b); else if (BN == 128) wg_ss128<TA, false>(acc, a, b); else wg_ss64<TA, false>(acc, a, b); }
    }
    WG_COMMIT();
  };
  stage(std::true_type(), 0);
  pre();
  prev = st;
  if (++st == H_NST) { st = 0; ph ^= 1; }
#pragma unroll 1
  for (int i = 1; i < nst; i++) {
    stage(std::false_type(), i);
    WG_WAIT(1);
    if (leader) mbar_arrive(sb + H_BAR + HB_EMPTY + prev * 8);
    prev = st;
    if (++st == H_NST) { st = 0; ph ^= 1; }
  }
  WG_WAIT(0);
  HT(2);
  reg_fence<BN / 2>(acc);
  if (leader) mbar_arrive(sb + H_BAR + HB_EMPTY + prev * 8);
}

template <int BN, bool FINAL>
__device__ __forceinline__ bool h_residual(uint32_t sb, uint32_t va, int mt, int n0, uint32_t& st, uint32_t& ph, int warp, int lane, __nv_bfloat16* out,
                                           int part = 0, int lgp = 0) {
  const size_t toff = (size_t)(mt * 16 + (n0 >> 6)) * 16384 + tile_lane(warp, lane);
  uint4 r[BN / 16];
  auto load_r = [&]() {
#pragma unroll
    for (int i = 0; i < BN / 16; i++) r[i] = __ldcg(reinterpret_cast<const uint4*>(g_x1 + toff + tile_off(i >> 1, i & 1)));
  };
  if (!R_LATE) load_r();
  float acc[BN / 2];
  h_mainloop<BN, FINAL ? 0 : 1>(acc, sb, ((FINAL ? 56 : 64) / (BN == 64 ? 2 : 1)) >> lgp, st, ph, warp >> 2, (warp & 3) == 0 && lane == 0, false,
                                [&]() { if (R_LATE) load_r(); });
  if (BN == 64 && lgp > 0) {
    const int tile = (FINAL * 4 + (mt & 3)) * 16 + (n0 >> 6);
    float4* ws = reinterpret_cast<float4*>(g_ws) + (size_t)tile * 8192 + warp * 32 + lane;
#pragma unroll
    for (int i = 0; i < 8; i++) ws[part * 2048 + i * 256] = make_float4(acc[4 * i], acc[4 * i + 1], acc[4 * i + 2], acc[4 * i + 3]);
    bar_sync<1, 256>();
    if (warp == 0 && lane == 0) { fence_gpu(); const uint32_t t = atomicAdd(&g_flags[FL_SPL + tile], 1); fence_gpu(); sts32(sb + H_BAR + HB_INC + 8, t); }
    bar_sync<1, 256>();
    if (lds32(sb + H_BAR + HB_INC + 8) != (1u << lgp) - 1) return false;
#pragma unroll 1
    for (int p = 1; p < (1 << lgp); p++) {
      float4 o[8];
#pragma unroll
      for (int i = 0; i < 8; i++) o[i] = __ldcg(ws + (part ^ p) * 2048 + i * 256);
#pragma unroll
      for (int i = 0; i < 8; i++) { acc[4 * i] += o[i].x; acc[4 * i + 1] += o[i].y; acc[4 * i + 2] += o[i].z; acc[4 * i + 3] += o[i].w; }
    }
  }
  float sm[4] = {0.f, 0.f, 0.f, 0.f};
  const uint32_t stg = sb + H_STG + warp * 2048;
#pragma unroll
  for (int c = 0; c < BN / 32; c++) {
    uint32_t y[2][4] = {{r[2 * c].x, r[2 * c].y, r[2 * c].z, r[2 * c].w}, {r[2 * c + 1].x, r[2 * c + 1].y, r[2 * c + 1].z, r[2 * c + 1].w}}, z[2][4];
#pragma unroll
    for (int j = 0; j < 4; j++) {
      const uint32_t gt = lds32(va + c * 64 + j * 16 + (lane & 3) * 4);
      const uint32_t cb = FINAL ? 0 : lds32(va + 512 + c * 64 + j * 16 + (lane & 3) * 4);
#pragma unroll
      for (int h = 0; h < 2; h++) {
        const float* a = acc + c * 16 + j * 4 + h * 2;
        y[h][j] = pack2(fmaf(bf_lo(gt), a[0], bf_lo(y[h][j])), fmaf(bf_hi(gt), a[1], bf_hi(y[h][j])));
        if (!FINAL) {
          const float p = bf_lo(y[h][j]), q = bf_hi(y[h][j]);
          sm[2 * h] += p + q;
          sm[2 * h + 1] = fmaf(p, p, fmaf(q, q, sm[2 * h + 1]));
          z[h][j] = pack2(fmaf(p, bf_lo(cb), p), fmaf(q, bf_hi(cb), q));
        }
      }
    }
    if (!FINAL) {
#pragma unroll
      for (int h = 0; h < 2; h++) {
        const size_t o = toff + tile_off(c, h);
        *reinterpret_cast<uint4*>(g_x1 + o) = make_uint4(y[h][0], y[h][1], y[h][2], y[h][3]);
        *reinterpret_cast<uint4*>(g_h2 + o) = make_uint4(z[h][0], z[h][1], z[h][2], z[h][3]);
      }
    } else {
#pragma unroll
      for (int h = 0; h < 2; h++) stsm4(stg + (h * 8 + (lane & 7)) * 128 + ((((c & 1) * 4 + (lane >> 3)) ^ (lane & 7)) << 4), y[h]);
      if (c & 1) {
        __syncwarp();
#pragma unroll
        for (int j = 0; j < 4; j++) {
          const int rr = 4 * j + (lane >> 3);
          uint32_t v[4];
          lds128(v, stg + rr * 128 + (((lane & 7) ^ (rr & 7)) << 4));
          *reinterpret_cast<uint4*>(out + (size_t)(mt * 128 + warp * 16 + rr) * D_ + n0 + (c >> 1) * 64 + (lane & 7) * 8) = make_uint4(v[0], v[1], v[2], v[3]);
        }
        __syncwarp();
      }
    }
    if (CH_FENCE && c + 1 < BN / 32) sched_fence(lane, 100);
  }
  if (!FINAL) {
#pragma unroll
    for (int j = 0; j < 4; j++) { sm[j] += __shfl_xor_sync(0xffffffffu, sm[j], 1); sm[j] += __shfl_xor_sync(0xffffffffu, sm[j], 2); }
    const int t = lane & 3;
    const float sv = t == 0 ? sm[0] : t == 1 ? sm[1] : t == 2 ? sm[2] : sm[3];
    asm volatile("red.relaxed.gpu.global.add.f32 [%0], %1;" :: "l"(g_stat + (mt * 128 + warp * 16 + (t >> 1) * 8 + (lane >> 2)) * 2 + (t & 1)), "f"(sv) : "memory");
  }
  return true;
}

__device__ __forceinline__ float silu_mul(float hg, float u) {
  float t; asm("tanh.approx.f32 %0, %1;" : "=f"(t) : "f"(hg));
  const float h = hg * u;
  return fmaf(h, t, h);
}

template <int BN>
__device__ __forceinline__ void h_swiglu(const float* acc, uint32_t va, int mt, int kb0, int warp, int lane) {
  uint8_t* ap = g_act + (size_t)(mt * 56 + kb0) * 16384 + tile_lane(warp, lane);
  float rs[2], nm[2], rh[2];
#pragma unroll
  for (int h = 0; h < 2; h++) {
    float t[2];
    lds64f(t, va + 2048 + (warp * 16 + h * 8 + (lane >> 2)) * 8);
    const float mean = t[0] * (1.f / D_);
    rs[h] = rsqrtf(fmaxf(t[1] * (1.f / D_) - mean * mean, 0.f) + 1e-5f);
    nm[h] = -mean * rs[h];
    rh[h] = 0.5f * rs[h];
  }
#pragma unroll
  for (int c = 0; c < BN / 64; c++) {
    uint32_t y[2][4];
#pragma unroll
    for (int j = 0; j < 4; j++) {
      const float* g = acc + 16 * c + 4 * j; const float* u = g + BN / 4;
      float p[4], q[4], o[4];
      lds128f(p, va + (4 * c + j) * 128 + (lane & 3) * 32); lds128f(q, va + (4 * c + j) * 128 + (lane & 3) * 32 + 16);
#pragma unroll
      for (int e = 0; e < 4; e++)
        o[e] = silu_mul(fmaf(rh[e >> 1], g[e], fmaf(nm[e >> 1], p[e & 1], p[2 + (e & 1)])), fmaf(rs[e >> 1], u[e], fmaf(nm[e >> 1], q[e & 1], q[2 + (e & 1)])));
      y[0][j] = pack2(o[0], o[1]); y[1][j] = pack2(o[2], o[3]);
    }
#pragma unroll
    for (int h = 0; h < 2; h++)
      *reinterpret_cast<uint4*>(ap + tile_off(c, h)) = make_uint4(y[h][0], y[h][1], y[h][2], y[h][3]);
    if (CH_FENCE1 && c + 1 < BN / 64) sched_fence(lane, 100);
  }
}

__global__ void __launch_bounds__(384, 1)
kernel_H(const __grid_constant__ CUtensorMap tmo, const __grid_constant__ CUtensorMap tm1, const __grid_constant__ CUtensorMap tm3,
         const __grid_constant__ CUtensorMap tm2, const __grid_constant__ CUtensorMap tmm, const __nv_bfloat16* __restrict__ x,
         const __nv_bfloat16* __restrict__ cvec, __nv_bfloat16* __restrict__ out, const __grid_constant__ HList list) {
  extern __shared__ __align__(1024) uint8_t smem[];
  constexpr uint32_t sb = 0x400, bars = sb + H_BAR;
  const int tid = threadIdx.x, lane = tid & 31;
  const int warp = __shfl_sync(0xffffffffu, tid >> 5, 0);
  if (tid == 0) {
    if (smem_u32(smem) != sb) __trap();
    for (int i = 0; i < H_NST; i++) { mbar_init(bars + HB_FULL + i * 8, 1); mbar_init(bars + HB_EMPTY + i * 8, 2); }
    for (int i = 0; i < 2; i++) { mbar_init(bars + HB_IFULL + i * 8, 1); mbar_init(bars + HB_IEMPTY + i * 8, 3); }
    fence_async_smem();
  }
  __syncthreads();
  if (warp >= 8) {
    asm volatile("setmaxnreg.dec.sync.aligned.u32 40;");
    if (warp == 8) {
      uint32_t st = 0, ph = 1;
#pragma unroll 1
      for (uint32_t n = 0;; n++) {
        uint32_t q = 0;
        if (lane == 0) q = atomicAdd(&g_flags[FL_HEAD], 1);
        q = __shfl_sync(0xffffffffu, q, 0);
        const uint32_t it = q < list.n ? list.it[q] : 0;
        const int type = it & 7, mt = (it >> 3) & 15, idx = (it >> 7) & 63, sz = (it >> 13) & 3, part = (it >> 15) & 3, lgp = (it >> 17) & 3;
        int f = FL_GO; uint32_t target = 0;
        if (type == IT_OUT) { f = lane == 0 ? FL_ATT + 8 * mt : lane == 1 ? FL_XT + 8 * mt : FL_MOD; target = lane == 0 ? 64 : lane == 1 ? 2 : 12; }
        else if (type == IT_F1) { f = lane == 0 ? FL_OUT + 8 * mt : FL_UV; target = lane == 0 ? 16 : 28; }
        else if (type == IT_F2) { f = lane == 0 ? FL_F1 + 8 * mt : FL_MODB; target = lane == 0 ? 56 : 4; }
        else if (type == IT_UV) { f = FL_MOD; target = 12; }
        else if (type == IT_MOD || (XT_GO && type == IT_XT)) target = 1;
        bool late = false;
        if (lane < 2 && (lane == 0 || type == IT_OUT)) wait_flag(&g_flags[f], target);
        else if (lane == 2) late = ld_acquire(&g_flags[f]) < target;
        late = __shfl_sync(0xffffffffu, late, 2);
        asm volatile("fence.proxy.async.global;" ::: "memory");
        mbar_wait(bars + HB_IEMPTY + (n & 1) * 8, ((n >> 1) & 1) ^ 1);
        if (elect_one()) {
          sts32(bars + HB_ITEM + (n & 1) * 4, it | (q << 19));
          mbar_arrive(bars + HB_IFULL + (n & 1) * 8);
        }
        if (type == IT_END) break;
        if (type != IT_XT) {
          const bool has_a = type == IT_OUT || type >= IT_F1;
          const uint8_t* ap = type == IT_OUT ? g_att + (size_t)mt * 64 * 16384 : type == IT_F1 ? g_h2 + (size_t)mt * 16 * 16384 : g_act + (size_t)mt * 56 * 16384;
          const int nkb = (type == IT_OUT ? 64 : type == IT_F2 ? 56 : 16) >> lgp;
          const uint32_t abytes = has_a ? (sz == 2 ? 32768 : 16384) : 0, bytes = (sz == 0 ? 32768 : 16384) + abytes;
          const int dk = sz == 2 ? 1 : 0;
#pragma unroll 1
          for (int kb = part * nkb; kb < (part + 1) * nkb; kb += 1 + dk) {
            const uint32_t d = sb + st * H_STAGE, fb = bars + HB_FULL + st * 8;
            mbar_wait(bars + HB_EMPTY + st * 8, ph);
            if (has_a && kb + 1 + dk >= (part + 1) * nkb) {
              if (late) {
                if (lane == 2) wait_flag(&g_flags[f], target);
                __syncwarp();
                asm volatile("fence.proxy.async.global;" ::: "memory");
              }
              if (elect_one()) {
                const bool f1 = type == IT_F1;
                const int c0 = f1 ? idx * (128 >> sz) : idx * (256 >> sz);
                const uint32_t v = sb + H_VEC + (n & 1) * 3072;
                const uint32_t n0 = (f1 ? 2048 : 512) >> sz, n1 = f1 ? 1024 : n0;
                asm volatile("mbarrier.expect_tx.relaxed.cta.shared::cta.b64 [%0], %1;" :: "r"(fb), "r"(n0 + n1) : "memory");
                bulk_g2s(v, f1 ? (const void*)(g_uv + c0 * 4) : (const void*)(g_mod + (type == IT_OUT ? 2 : 5) * D_ + c0), n0, fb);
                bulk_g2s(v + (f1 ? 2048 : 512), f1 ? (const void*)(g_stat + mt * 256) : (const void*)(g_mod + 4 * D_ + c0), n1, fb);
              }
            }
            if (elect_one()) {
              mbar_expect(fb, bytes);
              if (has_a) bulk_g2s(d, ap + (size_t)kb * 16384, abytes, fb);
            }
            if (++st == H_NST) { st = 0; ph ^= 1; }
          }
        }
      }
    } else if (warp >= 10) {
      const int hb = warp - 10;
      uint32_t st = 0, ph = 1;
#pragma unroll 1
      for (uint32_t n = 0;; n++) {
        mbar_wait(bars + HB_IFULL + (n & 1) * 8, (n >> 1) & 1);
        const uint32_t it = __shfl_sync(0xffffffffu, lds32(bars + HB_ITEM + (n & 1) * 4), 0);
        const int type = it & 7, idx = (it >> 7) & 63, sz = (it >> 13) & 3, part = (it >> 15) & 3, lgp = (it >> 17) & 3;
        if (type == IT_END) break;
        if (elect_one()) mbar_arrive(bars + HB_IEMPTY + (n & 1) * 8);
        if (type == IT_XT) continue;
        const bool ffn1 = type == IT_F1 || type == IT_UV;
        const int nkb = (type == IT_OUT ? 64 : type == IT_F2 ? 56 : 16) >> lgp;
        const CUtensorMap* tb = type == IT_OUT ? &tmo : ffn1 ? &tm1 : type == IT_F2 ? &tm2 : &tmm;
        const CUtensorMap* tc = ffn1 ? &tm3 : tb;
        const int c0 = ffn1 ? idx * (128 >> sz) : idx * (256 >> sz) + (type == IT_MOD ? 2048 : 0), c2 = ffn1 ? c0 : c0 + 128;
        const int dk = sz == 2 ? 1 : 0;
        const CUtensorMap* t0 = hb == 1 && sz == 1 ? tc : tb;
        const int ca = hb == 0 || sz == 2 || (sz == 1 && ffn1) ? c0 : c0 + 64;
        const uint32_t off = (sz == 2 ? 32768 : 16384) + hb * 8192;
        const uint32_t cold = type == IT_MOD ? D_MOD : type == IT_UV ? D_UV : H_NST;
#pragma unroll 1
        for (int kb = part * nkb; kb < (part + 1) * nkb; kb += 1 + dk) {
          const uint32_t d = sb + st * H_STAGE + off, fb = bars + HB_FULL + st * 8;
          mbar_wait(bars + HB_EMPTY + st * 8, ph);
          if (cold < H_NST) mbar_wait(bars + HB_FULL + ((st - cold) & 3) * 8, st >= cold ? ph ^ 1 : ph);
          if (elect_one()) {
            tma5d(d, t0, ca, kb + hb * dk, fb);
            if (sz == 0) tma5d(d + 16384, tc, c2 + hb * 64, kb, fb);
          }
          if (++st == H_NST) { st = 0; ph ^= 1; }
        }
      }
    } else if (warp == 9) {
#pragma unroll 1
      for (uint32_t n = 0;; n++) {
        mbar_wait(bars + HB_IFULL + (n & 1) * 8, (n >> 1) & 1);
        const uint32_t itq = lds32(bars + HB_ITEM + (n & 1) * 4);
        const int type = itq & 7, mt = (itq >> 3) & 15;
        if (type == IT_END) break;
        if (n & 1) bar_sync<3, 288>(); else bar_sync<2, 288>();
        if (lane == 0) {
          const uint32_t inc = lds32(bars + HB_INC + (n & 1) * 4);
          mbar_arrive(bars + HB_IEMPTY + (n & 1) * 8);
          if (inc) {
            fence_gpu();
            red_add_u32(&g_flags[type == IT_MOD ? (((itq >> 7) & 63) < 12 ? FL_MOD : FL_MODB) : type == IT_UV ? FL_UV : (type == IT_XT ? FL_XT : type == IT_OUT ? FL_OUT : FL_F1) + 8 * mt], inc);
          }
        }
        __syncwarp();
      }
      asm volatile("griddepcontrol.wait;" ::: "memory");
      uint32_t k = 0;
      if (lane == 0) { fence_gpu(); k = atomicAdd(&g_flags[FL_EXIT], 1); }
      k = __shfl_sync(0xffffffffu, k, 0);
      if (k == gridDim.x - 1) {
        fence_gpu();
        for (int i = lane; i < 1024; i += 32) g_flags[i] = 0;
      }
    }
  } else {
    asm volatile("setmaxnreg.inc.sync.aligned.u32 232;");
    const int wg = warp >> 2;
    const bool leader = (tid & 127) == 0;
    uint32_t st = 0, ph = 0;
#pragma unroll 1
    for (uint32_t n = 0;; n++) {
      mbar_wait(bars + HB_IFULL + (n & 1) * 8, (n >> 1) & 1);
      const uint32_t itq = __shfl_sync(0xffffffffu, lds32(bars + HB_ITEM + (n & 1) * 4), 0);
      const int type = itq & 7, mt = (itq >> 3) & 15, idx = (itq >> 7) & 63, sz = (itq >> 13) & 3, part = (itq >> 15) & 3, lgp = (itq >> 17) & 3;
      uint32_t inc = type == IT_OUT ? 4 >> sz : type == IT_F1 ? 2 >> sz : type != IT_F2;
      if (type == IT_END) break;
      HT(0);
      const uint32_t va = sb + H_VEC + (n & 1) * 3072;
      if (type == IT_OUT) {
        if (sz == 0) h_residual<256, false>(sb, va, mt, idx * 256, st, ph, warp, lane, out);
        else if (sz == 1) h_residual<128, false>(sb, va, mt, idx * 128, st, ph, warp, lane, out);
        else inc = h_residual<64, false>(sb, va, mt, idx * 64, st, ph, warp, lane, out, part, lgp);
      } else if (type == IT_F2) {
        if (sz == 0) h_residual<256, true>(sb, va, mt, idx * 256, st, ph, warp, lane, out);
        else if (sz == 1) h_residual<128, true>(sb, va, mt, idx * 128, st, ph, warp, lane, out);
        else h_residual<64, true>(sb, va, mt, idx * 64, st, ph, warp, lane, out, part, lgp);
      } else if (type == IT_XT) {
        const int rg = idx * 8 + warp;
        const uint32_t* xp = reinterpret_cast<const uint32_t*>(x + (size_t)(mt * 128 + rg * 8 + (lane >> 2)) * D_) + (lane & 3);
        uint8_t* tp = g_x1 + (size_t)mt * 262144 + rg * 512 + tile_lane(0, lane);
        if (lane < 16) g_stat[(mt * 128 + rg * 8) * 2 + lane] = 0.f;
#pragma unroll 1
        for (int b = 0; b < 2; b++) {
          uint32_t v[64];
#pragma unroll
          for (int i = 0; i < 64; i++) v[i] = __ldg(xp + 256 * b + 4 * i);
#pragma unroll
          for (int i = 0; i < 16; i++)
            *reinterpret_cast<uint4*>(tp + tile_off(16 * b + i, 0)) = make_uint4(v[4 * i], v[4 * i + 1], v[4 * i + 2], v[4 * i + 3]);
        }
      } else if (sz == 1) {
        float acc[64];
        h_mainloop<128, 0>(acc, sb, 16, st, ph, wg, leader, false, []() {});
        h_swiglu<128>(acc, va, mt, idx, warp, lane);
      } else {
        if (type != IT_F1) {
          bar_sync<1, 256>();
          for (int i = tid; i < D_; i += 256) {
            __nv_bfloat16* p = reinterpret_cast<__nv_bfloat16*>(smem + H_STG + (i >> 5) * 512 + ((i >> 1) & 3) * 16) + ((i >> 3) & 3) * 2 + (i & 1);
            if (type == IT_UV) {
              p[0] = __float2bfloat16(1.f); p[32] = __ldcg(g_mod + 4 * D_ + i); p[64 + ((i & 2) ? -8 : 8)] = __ldcg(g_mod + 3 * D_ + i);
            }
            else { const float c = __bfloat162float(cvec[i]); p[0] = __float2bfloat16(c / (1.f + __expf(-c))); }
          }
          fence_async_smem();
          bar_sync<1, 256>();
        }
        if (type != IT_F1 && wg == 1) {
          h_pass(sb, 16, st, ph, leader);
        } else {
          float acc[128];
          h_mainloop<256, 0>(acc, sb, 16, st, ph, wg, leader, type != IT_F1, []() {});
          if (type == IT_F1) {
            h_swiglu<256>(acc, va, mt, idx * 2, warp, lane);
          } else if (warp == 0) {
#pragma unroll
            for (int j = 0; j < 32; j++) {
              if (type == IT_MOD) {
                if (lane < 4) reinterpret_cast<uint32_t*>(g_mod + 2048 + idx * 256)[j * 4 + lane] = pack2(acc[4 * j], acc[4 * j + 1]);
              } else {
                const float a = acc[4 * j] + __shfl_down_sync(0xffffffffu, acc[4 * j], 4), b = acc[4 * j + 1] + __shfl_down_sync(0xffffffffu, acc[4 * j + 1], 4);
                float2* up = reinterpret_cast<float2*>(g_uv + idx * 512 + ((j & 15) * 4 + (lane & 3)) * 8 + (j >> 4) * 4);
                const float sc = j < 16 ? 0.5f : 1.f;
                if (lane < 4) up[0] = make_float2(sc * a, sc * b);
                else if ((lane >> 2) == 2) up[1] = make_float2(sc * acc[4 * j], sc * acc[4 * j + 1]);
              }
            }
          }
        }
      }
      if (tid == 0) sts32(bars + HB_INC + (n & 1) * 4, inc);
      if (n & 1) bar_arrive<3, 288>(); else bar_arrive<2, 288>();
    }
  }
}

#define T_FIRST 35.f
#define T_UV 43.f
#define T_UV2 55.f
#define T_OUT0 50.f
#define T_SLACK 2.f
#define T_PERIOD 13.4f
#define G_OUT "2211111111111124"
#define G_F1 "0000000000000001"
#define G_F2 "0000000011112233"
#define F2_LEAD 20.f
void build_list(HList& l) {
  int n = 0;
  auto add = [&](int type, int mt, int idx, int g) {
    const int sz = g > 2 ? 2 : g, lgp = g - sz;
    l.it[n++] = type | mt << 3 | (idx >> lgp) << 7 | sz << 13 | (idx & ((1 << lgp) - 1)) << 15 | lgp << 17;
  };
  const char* gran[3] = {G_OUT, G_F1, G_F2};
  if (XT_GO) for (int i = 0; i < 12; i++) add(IT_MOD, 0, i, 0);
  for (int i = 0; i < 32; i++) add(IT_XT, i >> 1, i & 1, 0);
  if (!XT_GO) for (int i = 0; i < 12; i++) add(IT_MOD, 0, i, 0);
  for (int i = 0; i < N_UV1; i++) add(IT_UV, 0, i, 0);
  for (int i = 0; i < 4 << (G_OUT[0] - '0'); i++) add(IT_OUT, 0, i, G_OUT[0] - '0');
  for (int i = N_UV1; i < 28; i++) add(IT_UV, 0, i, 0);
  for (int i = 12; i < 16; i++) add(IT_MOD, 0, i, 0);
  const float dur[3][5] = {{42.f, 22.f, 13.f, 9.f, 7.f}, {11.2f, 7.f, 0.f, 0.f, 0.f}, {37.f, 21.f, 11.5f, 8.f, 6.f}};
  const float t_end = T_FIRST + 15 * T_PERIOD - 1.5f;
  float fr[132];
  for (int i = 0; i < 132; i++) fr[i] = i < 36 - N_UV1 ? T_OUT0 : i < 36 - N_UV1 + 32 - N_UV1 ? T_UV2 : i < 36 ? T_UV : t_end + 1.2f;
  float rdy[3][16];
  int mt[3] = {1, 0, 0}, ix[3] = {0, 0, 0};
  for (int m = 0; m < 16; m++) { rdy[0][m] = m < 15 ? T_FIRST + m * T_PERIOD : t_end; rdy[1][m] = rdy[2][m] = 0.f; }
  rdy[1][0] = T_OUT0 + 0.5f;
  while (mt[2] < 16) {
    int w = 0;
    for (int i = 1; i < 132; i++) if (fr[i] < fr[w]) w = i;
    const float t = fr[w];
    int best = -1;
    float tb = 1e9f;
    const bool f2_first = gran[2][mt[2]] == '0' && t > t_end - F2_LEAD;
    const int order[3] = {0, f2_first ? 2 : 1, f2_first ? 1 : 2};
    for (int k = 0; k < 3; k++) {
      const int q = order[k];
      if (mt[q] >= 16 || (q > 0 && mt[q] >= mt[q - 1])) continue;
      const float ts = rdy[q][mt[q]] > t ? rdy[q][mt[q]] : t;
      if (ts < tb - T_SLACK) { tb = ts; best = q; }
    }
    const int m = mt[best], g = gran[best][m] - '0';
    add(best == 0 ? IT_OUT : best == 1 ? IT_F1 : IT_F2, m, ix[best], g);
    fr[w] = tb + dur[best][g];
    if (best < 2 && fr[w] + 0.5f > rdy[best + 1][m]) rdy[best + 1][m] = fr[w] + 0.5f;
    if (++ix[best] == (best == 1 ? 28 : 4) << g) { ix[best] = 0; mt[best]++; }
  }
  l.n = n;
}

typedef CUresult (*EncodeFn)(CUtensorMap*, CUtensorMapDataType, cuuint32_t, void*, const cuuint64_t*, const cuuint64_t*,
                             const cuuint32_t*, const cuuint32_t*, CUtensorMapInterleave, CUtensorMapSwizzle,
                             CUtensorMapL2promotion, CUtensorMapFloatOOBfill);

#define PROMO_W CU_TENSOR_MAP_L2_PROMOTION_L2_128B
#define PROMO_O CU_TENSOR_MAP_L2_PROMOTION_L2_128B
#define PROMO_M CU_TENSOR_MAP_L2_PROMOTION_L2_128B
#define PROMO_H CU_TENSOR_MAP_L2_PROMOTION_L2_128B
void make_map(EncodeFn fn, CUtensorMap* m, const void* p, uint64_t cols, uint64_t rows, uint32_t bc, uint32_t br, CUtensorMapSwizzle sw,
              CUtensorMapL2promotion promo) {
  cuuint64_t dims[2] = {cols, rows};
  cuuint64_t strides[1] = {cols * 2};
  cuuint32_t box[2] = {bc, br};
  cuuint32_t es[2] = {1, 1};
  fn(m, CU_TENSOR_MAP_DATA_TYPE_BFLOAT16, 2, const_cast<void*>(p), dims, strides, box, es, CU_TENSOR_MAP_INTERLEAVE_NONE, sw,
     promo, CU_TENSOR_MAP_FLOAT_OOB_FILL_NONE);
}

void make_map_perm(EncodeFn fn, CUtensorMap* m, const void* p, uint64_t cols, uint64_t rows, bool perm) {
  cuuint64_t dims[5] = {cols, 2, 4, 4, rows / 32};
  cuuint64_t strides[4] = {cols * 2, cols * 2 * (perm ? 8 : 2), cols * 2 * (perm ? 2 : 8), cols * 2 * 32};
  cuuint32_t box[5] = {64, 2, 4, 4, 2};
  cuuint32_t es[5] = {1, 1, 1, 1, 1};
  fn(m, CU_TENSOR_MAP_DATA_TYPE_BFLOAT16, 5, const_cast<void*>(p), dims, strides, box, es, CU_TENSOR_MAP_INTERLEAVE_NONE,
     CU_TENSOR_MAP_SWIZZLE_128B, PROMO_H, CU_TENSOR_MAP_FLOAT_OOB_FILL_NONE);
}

}

extern "C" void kernel_launch(void* const* d_in, const int* in_sizes, int n_in, void* d_out, int out_size) {
  const __nv_bfloat16* x = (const __nv_bfloat16*)d_in[0];
  const __nv_bfloat16* mem0 = (const __nv_bfloat16*)d_in[1];
  const __nv_bfloat16* cvec = (const __nv_bfloat16*)d_in[11];
  static EncodeFn enc = nullptr;
  if (!enc) {
    cudaDriverEntryPointQueryResult qr;
    void* fp = nullptr;
    cudaGetDriverEntryPoint("cuTensorMapEncodeTiled", &fp, cudaEnableDefault, &qr);
    enc = (EncodeFn)fp;
    cudaFuncSetAttribute(kernel_R, cudaFuncAttributeMaxDynamicSharedMemorySize, R_SMEM);
    cudaFuncSetAttribute(kernel_H, cudaFuncAttributeMaxDynamicSharedMemorySize, H_SMEM);
  }
  CUtensorMap tmq, tmk, tmv, tmo, tmm;
  make_map(enc, &tmm, d_in[12], 6144, 1024, 64, 64, CU_TENSOR_MAP_SWIZZLE_NONE, PROMO_M);
  make_map(enc, &tmq, d_in[2], 4096, 1024, 64, 64, CU_TENSOR_MAP_SWIZZLE_128B, PROMO_W);
  make_map(enc, &tmk, d_in[3], 4096, 1024, 64, 64, CU_TENSOR_MAP_SWIZZLE_128B, PROMO_W);
  make_map(enc, &tmv, d_in[4], 4096, 1024, 64, 64, CU_TENSOR_MAP_SWIZZLE_128B, PROMO_W);
  make_map(enc, &tmo, d_in[5], 1024, 4096, 16, 128, CU_TENSOR_MAP_SWIZZLE_32B, PROMO_O);
  RDesc dsc;
  for (int k = 0; k < 32; k++) {
    dsc.tok[k] = mkdesc(0x400 + (k < 16 ? R_GA : R_GB) + ((k & 15) >> 2) * 4096 + (k & 3) * 256, 128, 1024, 0);
    dsc.tail_a[k] = mkdesc(0x400 + R_TAIL + k * 2048, 1024, 1024, 1);
    if (k < 16) dsc.tail_b[k] = mkdesc(0x400 + R_GA + k * 256, 128, 4096, 0);
  }
  kernel_R<<<96, 256, R_SMEM, cudaStreamPerThread>>>(tmq, tmk, tmv, tmo, tmm, x, mem0, cvec, dsc);

  CUtensorMap ho, h1, h3, h2, hm;
  make_map_perm(enc, &ho, d_in[5], 1024, 4096, false);
  make_map_perm(enc, &h1, d_in[8], F_, 1024, true);
  make_map_perm(enc, &h3, d_in[9], F_, 1024, true);
  make_map_perm(enc, &h2, d_in[10], 1024, F_, true);
  make_map_perm(enc, &hm, d_in[12], 6144, 1024, true);
  HList list;
  build_list(list);
  cudaLaunchConfig_t cfg = {};
#define H_GRID 132
  cfg.gridDim = dim3(H_GRID); cfg.blockDim = dim3(384); cfg.dynamicSmemBytes = H_SMEM; cfg.stream = cudaStreamPerThread;
  cudaLaunchAttribute at[1];
  at[0].id = cudaLaunchAttributeProgrammaticStreamSerialization;
  at[0].val.programmaticStreamSerializationAllowed = 1;
  cfg.attrs = at;
  cfg.numAttrs = 1;
  cudaLaunchKernelEx(&cfg, kernel_H, ho, h1, h3, h2, hm, x, cvec, (__nv_bfloat16*)d_out, list);
}
```

```cpp
#include <cuda_runtime.h>
#include <cuda_bf16.h>
#include <cuda.h>
#include <stdint.h>
#include <type_traits>

namespace {

constexpr int S_ = 2048, D_ = 1024, NSEG = 64, F_ = 3584;

__device__ __align__(1024) uint8_t g_h[S_ * D_ * 2];
__device__ __align__(1024) uint8_t g_att[S_ * 4096 * 2];
__device__ __align__(1024) uint8_t g_x1[S_ * D_ * 2];
__device__ __align__(1024) uint8_t g_h2[S_ * D_ * 2];
__device__ __align__(1024) uint8_t g_act[S_ * F_ * 2];
__device__ __align__(1024) float g_ws[2 * 4 * 16 * 4 * 8192];
__device__ __align__(1024) float g_stat[S_ * 2];
__device__ __align__(1024) float g_uv[F_ * 4];
__device__ __align__(1024) float g_slot[4 * 3 * 8 * 4 * 32 * 4];
__device__ __align__(128) __nv_bfloat16 g_mod[6 * D_];
__device__ __align__(128) float g_modp[3 * 2 * D_];
__device__ __align__(128) uint32_t g_flags[1024];
constexpr int FL_S1 = 0, FL_S2 = 32, FL_MOD = 64, FL_HEAD = 96, FL_EXIT = 128, FL_UV = 160, FL_GO = 192, FL_MODB = 224, FL_ATT = 256, FL_XT = 384, FL_OUT = 512, FL_F1 = 640, FL_SPL = 768;

#define EVF 1
__device__ __forceinline__ uint32_t smem_u32(const void* p) { return (uint32_t)__cvta_generic_to_shared(p); }
__device__ __forceinline__ uint32_t mapa(uint32_t a, uint32_t r) { uint32_t o; asm("mapa.shared::cluster.u32 %0, %1, %2;" : "=r"(o) : "r"(a), "r"(r)); return o; }
__device__ __forceinline__ uint32_t pack2(float a, float b) { uint32_t r; asm("cvt.rn.bf16x2.f32 %0, %1, %2;" : "=r"(r) : "f"(b), "f"(a)); return r; }
__device__ __forceinline__ float bf_lo(uint32_t w) { return __uint_as_float(w << 16); }
__device__ __forceinline__ float bf_hi(uint32_t w) { return __uint_as_float(w & 0xffff0000u); }
__device__ __forceinline__ float ex2(float x) { float y; asm("ex2.approx.ftz.f32 %0, %1;" : "=f"(y) : "f"(x)); return y; }
__device__ __forceinline__ float rcp(float x) { float y; asm("rcp.approx.ftz.f32 %0, %1;" : "=f"(y) : "f"(x)); return y; }
__device__ __forceinline__ uint32_t clk32() { uint64_t c; asm volatile("mov.u64 %0, %%clock64;" : "=l"(c) :: "memory"); return (uint32_t)c; }

__device__ __forceinline__ void mbar_init(uint32_t b, uint32_t n) { asm volatile("mbarrier.init.shared::cta.b64 [%0], %1;" :: "r"(b), "r"(n) : "memory"); }
__device__ __forceinline__ void mbar_arrive(uint32_t b) { asm volatile("mbarrier.arrive.shared::cta.b64 _, [%0];" :: "r"(b) : "memory"); }
__device__ __forceinline__ void mbar_expect(uint32_t b, uint32_t n) { asm volatile("mbarrier.arrive.expect_tx.shared::cta.b64 _, [%0], %1;" :: "r"(b), "r"(n) : "memory"); }
__device__ __forceinline__ uint32_t mbar_try(uint32_t b, uint32_t par) {
  uint32_t ok;
  asm volatile("{\n.reg .pred p;\nmbarrier.try_wait.parity.shared::cta.b64 p, [%1], %2;\nselp.u32 %0, 1, 0, p;\n}" : "=r"(ok) : "r"(b), "r"(par) : "memory");
  return ok;
}
__device__ __forceinline__ void mbar_wait(uint32_t b, uint32_t par) {
  asm volatile("{\n.reg .pred p;\n"
               "LOOP:\n"
               "mbarrier.try_wait.parity.shared::cta.b64 p, [%0], %1;\n"
               "@!p bra.uni LOOP;\n}" :: "r"(b), "r"(par) : "memory");
}
__device__ __forceinline__ void mbar_wait_safe(uint32_t b, uint32_t par) {
  uint32_t c = 0;
  while (!mbar_try(b, par)) { if (++c > 4000000u) __trap(); }
}
__device__ __forceinline__ bool elect_one() {
  uint32_t p;
  asm volatile("{\n.reg .pred p;\nelect.sync _|p, 0xffffffff;\nselp.u32 %0, 1, 0, p;\n}" : "=r"(p));
  return p;
}
__device__ __forceinline__ void sched_fence(uint32_t x, uint32_t y) { asm volatile("{\n.reg .pred p;\nsetp.eq.u32 p, %0, %1;\n@p trap;\n}" :: "r"(x), "r"(y) : "memory"); }
template <class T> __device__ __forceinline__ T opaque32(T x) { asm volatile("" : "+r"(x)); return x; }
template <class T> __device__ __forceinline__ T opaque64(T x) { asm volatile("" : "+l"(x)); return x; }
template <int ID, int N> __device__ __forceinline__ void bar_sync() { asm volatile("bar.sync %0, %1;" :: "n"(ID), "n"(N) : "memory"); }
template <int ID, int N> __device__ __forceinline__ void bar_arrive() { asm volatile("bar.arrive %0, %1;" :: "n"(ID), "n"(N) : "memory"); }
__device__ __forceinline__ void fence_async_smem() { asm volatile("fence.proxy.async.shared::cta;" ::: "memory"); }
__device__ __forceinline__ void fence_async_all() { asm volatile("fence.proxy.async;" ::: "memory"); }
__device__ __forceinline__ void fence_gpu() { asm volatile("fence.acq_rel.gpu;" ::: "memory"); }
__device__ __forceinline__ void red_add_u32(uint32_t* p, uint32_t v) { asm volatile("red.relaxed.gpu.global.add.u32 [%0], %1;" :: "l"(p), "r"(v) : "memory"); }
__device__ __forceinline__ uint32_t ld_acquire(const uint32_t* p) { uint32_t v; asm volatile("ld.acquire.gpu.global.u32 %0, [%1];" : "=r"(v) : "l"(p) : "memory"); return v; }
__device__ __forceinline__ void wait_flag(const uint32_t* p, uint32_t target) {
  uint32_t c = 0;
  while (ld_acquire(p) < target) { if (++c > 20000000u) __trap(); __nanosleep(20); }
}

__device__ __forceinline__ void tma2d(uint32_t dst, const CUtensorMap* m, int c0, int c1, uint32_t bar) {
  asm volatile("cp.async.bulk.tensor.2d.shared::cluster.global.mbarrier::complete_tx::bytes [%0], [%1, {%3, %4}], [%2];"
               :: "r"(dst), "l"(m), "r"(bar), "r"(c0), "r"(c1) : "memory");
}
__device__ __forceinline__ void tma2d_once(uint32_t dst, const CUtensorMap* m, int c0, int c1, uint32_t bar) {
  asm volatile("{\n.reg .b64 pol;\ncreatepolicy.fractional.L2::evict_first.b64 pol, 1.0;\n"
               "cp.async.bulk.tensor.2d.shared::cluster.global.mbarrier::complete_tx::bytes.L2::cache_hint [%0], [%1, {%3, %4}], [%2], pol;\n}"
               :: "r"(dst), "l"(m), "r"(bar), "r"(c0), "r"(c1) : "memory");
}
__device__ __forceinline__ void tma5d(uint32_t dst, const CUtensorMap* m, int n0, int kb, uint32_t bar) {
  asm volatile("cp.async.bulk.tensor.5d.shared::cluster.global.mbarrier::complete_tx::bytes [%0], [%1, {%3, %5, %5, %5, %4}], [%2];"
               :: "r"(dst), "l"(m), "r"(bar), "r"(n0), "r"(2 * kb), "r"(0) : "memory");
}
__device__ __forceinline__ void tma2d_prefetch(const CUtensorMap* m, int c0, int c1) {
  asm volatile("cp.async.bulk.prefetch.tensor.2d.L2.global [%0, {%1, %2}];" :: "l"(m), "r"(c0), "r"(c1) : "memory");
}
__device__ __forceinline__ void bulk_g2s(uint32_t dst, const void* src, uint32_t bytes, uint32_t bar) {
  asm volatile("cp.async.bulk.shared::cluster.global.mbarrier::complete_tx::bytes [%0], [%1], %2, [%3];"
               :: "r"(dst), "l"(src), "r"(bytes), "r"(bar) : "memory");
}
__device__ __forceinline__ void bulk_s2s(uint32_t dst, uint32_t src, uint32_t bytes, uint32_t bar) {
  asm volatile("cp.async.bulk.shared::cluster.shared::cta.mbarrier::complete_tx::bytes [%0], [%1], %2, [%3];"
               :: "r"(dst), "r"(src), "r"(bytes), "r"(bar) : "memory");
}
__device__ __forceinline__ void st_async1(uint32_t dst, uint32_t a, uint32_t bar) {
  asm volatile("st.async.shared::cluster.mbarrier::complete_tx::bytes.b32 [%0], %1, [%2];" :: "r"(dst), "r"(a), "r"(bar) : "memory");
}
__device__ __forceinline__ void st_async2(uint32_t dst, uint32_t a, uint32_t b, uint32_t bar) {
  asm volatile("st.async.shared::cluster.mbarrier::complete_tx::bytes.v2.b32 [%0], {%1, %2}, [%3];" :: "r"(dst), "r"(a), "r"(b), "r"(bar) : "memory");
}
__device__ __forceinline__ void st_async4(uint32_t dst, const uint32_t* r, uint32_t bar) {
  asm volatile("st.async.shared::cluster.mbarrier::complete_tx::bytes.v4.b32 [%0], {%1, %2, %3, %4}, [%5];"
               :: "r"(dst), "r"(r[0]), "r"(r[1]), "r"(r[2]), "r"(r[3]), "r"(bar) : "memory");
}
__device__ __forceinline__ void sts32(uint32_t a, uint32_t v) { asm volatile("st.shared.b32 [%0], %1;" :: "r"(a), "r"(v) : "memory"); }
__device__ __forceinline__ void sts64(uint32_t a, uint32_t x, uint32_t y) { asm volatile("st.shared.v2.b32 [%0], {%1, %2};" :: "r"(a), "r"(x), "r"(y) : "memory"); }
__device__ __forceinline__ void sts128(uint32_t a, uint32_t x, uint32_t y, uint32_t z, uint32_t w) {
  asm volatile("st.shared.v4.b32 [%0], {%1, %2, %3, %4};" :: "r"(a), "r"(x), "r"(y), "r"(z), "r"(w) : "memory");
}
__device__ __forceinline__ void lds128(uint32_t* r, uint32_t a) {
  asm volatile("ld.shared.v4.b32 {%0, %1, %2, %3}, [%4];" : "=r"(r[0]), "=r"(r[1]), "=r"(r[2]), "=r"(r[3]) : "r"(a) : "memory");
}
__device__ __forceinline__ uint32_t lds32(uint32_t a) { uint32_t r; asm volatile("ld.shared.b32 %0, [%1];" : "=r"(r) : "r"(a) : "memory"); return r; }
__device__ __forceinline__ void lds64(uint32_t* r, uint32_t a) {
  asm volatile("ld.shared.v2.b32 {%0, %1}, [%2];" : "=r"(r[0]), "=r"(r[1]) : "r"(a) : "memory");
}
__device__ __forceinline__ void lds128f(float* r, uint32_t a) {
  asm volatile("ld.shared.v4.f32 {%0, %1, %2, %3}, [%4];" : "=f"(r[0]), "=f"(r[1]), "=f"(r[2]), "=f"(r[3]) : "r"(a) : "memory");
}
__device__ __forceinline__ void lds64f(float* r, uint32_t a) {
  asm volatile("ld.shared.v2.f32 {%0, %1}, [%2];" : "=f"(r[0]), "=f"(r[1]) : "r"(a) : "memory");
}
__device__ __forceinline__ void ldsm4(uint32_t* r, uint32_t a) {
  asm volatile("ldmatrix.sync.aligned.m8n8.x4.shared.b16 {%0, %1, %2, %3}, [%4];" : "=r"(r[0]), "=r"(r[1]), "=r"(r[2]), "=r"(r[3]) : "r"(a) : "memory");
}
__device__ __forceinline__ void ldsm4t(uint32_t* r, uint32_t a) {
  asm volatile("ldmatrix.sync.aligned.m8n8.x4.trans.shared.b16 {%0, %1, %2, %3}, [%4];" : "=r"(r[0]), "=r"(r[1]), "=r"(r[2]), "=r"(r[3]) : "r"(a) : "memory");
}
__device__ __forceinline__ void ldsm2(uint32_t* r, uint32_t a) {
  asm volatile("ldmatrix.sync.aligned.m8n8.x2.shared.b16 {%0, %1}, [%2];" : "=r"(r[0]), "=r"(r[1]) : "r"(a) : "memory");
}
__device__ __forceinline__ void stsm4(uint32_t a, const uint32_t* r) {
  asm volatile("stmatrix.sync.aligned.m8n8.x4.shared.b16 [%0], {%1, %2, %3, %4};" :: "r"(a), "r"(r[0]), "r"(r[1]), "r"(r[2]), "r"(r[3]) : "memory");
}
__device__ __forceinline__ uint32_t hadd2(uint32_t a, uint32_t b) { uint32_t t; asm("add.rn.bf16x2 %0, %1, %2;" : "=r"(t) : "r"(a), "r"(b)); return t; }
__device__ __forceinline__ uint32_t hmax2(uint32_t a, uint32_t b) { uint32_t t; asm("max.bf16x2 %0, %1, %2;" : "=r"(t) : "r"(a), "r"(b)); return t; }
__device__ __forceinline__ void ldsm2t(uint32_t* r, uint32_t a) {
  asm volatile("ldmatrix.sync.aligned.m8n8.x2.trans.shared.b16 {%0, %1}, [%2];" : "=r"(r[0]), "=r"(r[1]) : "r"(a) : "memory");
}
__device__ __forceinline__ uint32_t movm(uint32_t x) { uint32_t y; asm volatile("movmatrix.sync.aligned.m8n8.trans.b16 %0, %1;" : "=r"(y) : "r"(x)); return y; }
__device__ __forceinline__ void hmma(float* d, uint32_t a0, uint32_t a1, uint32_t a2, uint32_t a3, uint32_t b0, uint32_t b1) {
  asm volatile("mma.sync.aligned.m16n8k16.row.col.f32.bf16.bf16.f32 {%0,%1,%2,%3}, {%4,%5,%6,%7}, {%8,%9}, {%0,%1,%2,%3};"
               : "+f"(d[0]), "+f"(d[1]), "+f"(d[2]), "+f"(d[3]) : "r"(a0), "r"(a1), "r"(a2), "r"(a3), "r"(b0), "r"(b1));
}
__device__ __forceinline__ void hmma0(float* d, uint32_t a0, uint32_t a1, uint32_t a2, uint32_t a3, uint32_t b0, uint32_t b1) {
  asm volatile("mma.sync.aligned.m16n8k16.row.col.f32.bf16.bf16.f32 {%0,%1,%2,%3}, {%4,%5,%6,%7}, {%8,%9}, {%10,%10,%10,%10};"
               : "=f"(d[0]), "=f"(d[1]), "=f"(d[2]), "=f"(d[3]) : "r"(a0), "r"(a1), "r"(a2), "r"(a3), "r"(b0), "r"(b1), "f"(0.f));
}
__device__ __forceinline__ void hmma_k8(float* d, uint32_t a0, uint32_t a1, uint32_t b0) {
  asm volatile("mma.sync.aligned.m16n8k8.row.col.f32.bf16.bf16.f32 {%0,%1,%2,%3}, {%4,%5}, {%6}, {%0,%1,%2,%3};"
               : "+f"(d[0]), "+f"(d[1]), "+f"(d[2]), "+f"(d[3]) : "r"(a0), "r"(a1), "r"(b0));
}
__host__ __device__ constexpr uint64_t mkdesc(uint32_t addr, uint32_t lbo, uint32_t sbo, uint32_t sw) {
  return (uint64_t)((addr & 0x3FFFF) >> 4) | ((uint64_t)(lbo >> 4) << 16) | ((uint64_t)(sbo >> 4) << 32) | ((uint64_t)sw << 62);
}
#define WG_FENCE() asm volatile("wgmma.fence.sync.aligned;" ::: "memory")
#define WG_COMMIT() asm volatile("wgmma.commit_group.sync.aligned;" ::: "memory")
#define WG_WAIT(n) asm volatile("wgmma.wait_group.sync.aligned " #n ";" ::: "memory")
template <int N> __device__ __forceinline__ void reg_fence(float* d) {
#pragma unroll
  for (int i = 0; i < N; i++) asm volatile("" : "+f"(d[i]) :: "memory");
}
template <int N> __device__ __forceinline__ void zero_regs(float* d) {
#pragma unroll
  for (int i = 0; i < N; i++) asm volatile("mov.b32 %0, 0;" : "=f"(d[i]));
}
template <int SD>
__device__ __forceinline__ void wg_rs32(float* d, uint32_t a0, uint32_t a1, uint32_t a2, uint32_t a3, uint64_t b) {
  asm volatile("wgmma.mma_async.sync.aligned.m64n32k16.f32.bf16.bf16 {%0,%1,%2,%3,%4,%5,%6,%7,%8,%9,%10,%11,%12,%13,%14,%15}, {%16,%17,%18,%19}, %20, %21, 1, 1, 0;"
               : "+f"(d[0]), "+f"(d[1]), "+f"(d[2]), "+f"(d[3]), "+f"(d[4]), "+f"(d[5]), "+f"(d[6]), "+f"(d[7]),
                 "+f"(d[8]), "+f"(d[9]), "+f"(d[10]), "+f"(d[11]), "+f"(d[12]), "+f"(d[13]), "+f"(d[14]), "+f"(d[15])
               : "r"(a0), "r"(a1), "r"(a2), "r"(a3), "l"(b), "n"(SD));
}
template <int TB>
__device__ __forceinline__ void wg_ss40(float* d, uint64_t a, uint64_t b) {
  asm volatile("wgmma.mma_async.sync.aligned.m64n40k16.f32.bf16.bf16 {%0,%1,%2,%3,%4,%5,%6,%7,%8,%9,%10,%11,%12,%13,%14,%15,%16,%17,%18,%19}, %20, %21, 1, 1, 1, 1, %22;"
               : "+f"(d[0]), "+f"(d[1]), "+f"(d[2]), "+f"(d[3]), "+f"(d[4]), "+f"(d[5]), "+f"(d[6]), "+f"(d[7]),
                 "+f"(d[8]), "+f"(d[9]), "+f"(d[10]), "+f"(d[11]), "+f"(d[12]), "+f"(d[13]), "+f"(d[14]), "+f"(d[15]),
                 "+f"(d[16]), "+f"(d[17]), "+f"(d[18]), "+f"(d[19])
               : "l"(a), "l"(b), "n"(TB));
}
template <int T>
__device__ __forceinline__ void wg_ss32(float* d, uint64_t a, uint64_t b) {
  asm volatile("wgmma.mma_async.sync.aligned.m64n32k16.f32.bf16.bf16 {%0,%1,%2,%3,%4,%5,%6,%7,%8,%9,%10,%11,%12,%13,%14,%15}, %16, %17, 1, 1, 1, %18, %18;"
               : "+f"(d[0]), "+f"(d[1]), "+f"(d[2]), "+f"(d[3]), "+f"(d[4]), "+f"(d[5]), "+f"(d[6]), "+f"(d[7]),
                 "+f"(d[8]), "+f"(d[9]), "+f"(d[10]), "+f"(d[11]), "+f"(d[12]), "+f"(d[13]), "+f"(d[14]), "+f"(d[15])
               : "l"(a), "l"(b), "n"(T));
}

constexpr int R_TAIL = 0;
constexpr int R_WO = 65536;
constexpr int R_QK = R_WO + 86016;
constexpr int R_P = R_QK + 10240;
constexpr int R_GA = R_P + 6400;
constexpr int R_M2 = R_GA + 16384;
constexpr int R_M1 = R_M2 + 7168;
constexpr int R_GB = R_M1 + 9216;
constexpr int R_VT = R_GB + 16384;
constexpr int R_VM = R_VT + 8192;
constexpr int R_XS = R_VM + 2048;
constexpr int R_OX = R_XS + 1280;
constexpr int R_BAR = R_OX + 2048;
constexpr int R_TRC = R_BAR + 256;
constexpr int R_SMEM = R_TRC + 1024;
constexpr int B_MB = 0, B_XS = 32, B_VM = 40, B_VT = 48, B_TS = 56, B_FA = 64, B_FB = 72, B_TAIL = 80, B_WO = 88, B_STG = 96, B_WM = 128, B_X = 136;
constexpr int NB_A = 1, NB_B = 2, NB_X = 3, NB_C = 4, NB_D = 5, NB_E = 6, NB_F = 7, NB_G = 8, NB_H = 9, NB_S = 10, NB_E2 = 11, NB_P = 12, NB_W0 = 13;

#define POLL_DELAY 750
#define POLL_DELAY1 700
#define POLL_STAG 150
#define POLL_K0 20
#define PF1 2
#define PF2 2
#define PF3 2
#define PF4 0
#define CLR_D 2
#define PADN 0
#define PFD 0
#define GO_EARLY 0
#define RF_FIRST 1
#define BX_I 5
#define NCH 4
#define TOP2 0
#define CX_I 13
#define ATT_LATE 0
#define V_FENCE 1
#define SELF_STAS 1
#define Q_FENCE 1
#define ND_K 3
#define TRACE(i)
#define TS(i)

__device__ __forceinline__ int rot_chunk(int c, int rank) {
  int G = c;
  if (c < 9) { G = c + 3 * rank; if (G >= 9) G -= 9; }
  return G;
}
__device__ __forceinline__ int wo_tile(int i, int rank) {
  if (i < 12) return 12 * rank + i;
  const int r = i - 12 + 9 * rank;
  return r < 16 ? 48 + r : 20 + r;
}
__device__ __forceinline__ void load_chunk(uint32_t dst, int seg, int G, uint32_t bar) {
  mbar_expect(bar, 4096);
  bulk_g2s(dst, g_h + (size_t)(seg * 16 + G) * 4096, 4096, bar);
}
__device__ __forceinline__ void load_red(uint32_t* v, const float* p) {
#pragma unroll
  for (int j = 0; j < 2; j++)
    asm volatile("ld.relaxed.gpu.global.v4.u32 {%0, %1, %2, %3}, [%4];"
                 : "=r"(v[4 * j]), "=r"(v[4 * j + 1]), "=r"(v[4 * j + 2]), "=r"(v[4 * j + 3]) : "l"(p + j * 256) : "memory");
}
__device__ __forceinline__ bool red_done(const uint32_t* v) { return __all_sync(0xffffffffu, (v[3] & v[7]) == 0x42000000u); }
__device__ __forceinline__ uint32_t finish_red(uint32_t* v, const float* p) {
  uint32_t tries = 0;
  if (__builtin_expect(!red_done(v), 0)) {
    do { if (++tries > 20000000u) __trap(); load_red(v, p); } while (!red_done(v));
  }
  return tries;
}
__device__ __forceinline__ void exp10(float* sv, const uint32_t* x) {
  constexpr float SC = 0.08838834764831845f * 1.4426950408889634f;
  uint32_t m2 = hmax2(hmax2(hmax2(x[0], x[1]), hmax2(x[2], x[3])), x[4]);
  m2 = hmax2(m2, __shfl_xor_sync(0xffffffffu, m2, 1));
  m2 = hmax2(m2, __shfl_xor_sync(0xffffffffu, m2, 2));
  const float nm = -fmaxf(bf_lo(m2), bf_hi(m2)) * SC;
#pragma unroll
  for (int j = 0; j < 5; j++) { sv[2 * j] = ex2(fmaf(bf_lo(x[j]), SC, nm)); sv[2 * j + 1] = ex2(fmaf(bf_hi(x[j]), SC, nm)); }
}

__device__ __forceinline__ uint32_t arm_size(int w, bool isC) {
  return w == 0 ? (isC ? 1280 : 640) : w == 1 ? (isC ? 0 : 2048) : w == 2 ? (isC ? 0 : 8192) : (isC ? 0 : 1792);
}
struct RDesc { uint64_t tok[32], tail_b[16], tail_a[32]; };

template <int WG>
__device__ __forceinline__ void r_main(const uint32_t (&W)[48][4], const RDesc& dsc, int head, uint32_t rank, int lane_, int w) {
  const uint32_t sb = (rank << 24) + 0x400, bars = sb + R_BAR;
  const uint32_t to1 = rank == 0 ? 2u << 24 : 0u - (1u << 24), to2 = rank == 2 ? 0u - (2u << 24) : 1u << 24;
  const bool isC = rank == 2;
  const int lane = opaque32(lane_), warp = WG * 4 + w;
  const int gl = rot_chunk(4 * (lane & 3) + w, rank);
  const int g0 = __shfl_sync(0xffffffffu, gl, 0), g1 = __shfl_sync(0xffffffffu, gl, 1), g2 = __shfl_sync(0xffffffffu, gl, 2);
  const uint32_t arm_bytes = arm_size(w, isC);

#define L16 opaque32(sb + opaque32(lane) * 16)
#define L8 opaque32(sb + opaque32(lane) * 8)
#define L4 opaque32(sb + opaque32(lane) * 4)
#define LV opaque32(sb + R_VT + ((opaque32(lane) >> 3) & 1) * 512 + (opaque32(lane) >> 4) * 128 + (opaque32(lane) & 7) * 16)
#define SLOT(st) opaque64(slot0 + ((st) & 3) * 12288 + ((st) & 4) * 32)
  float* const slot0 = opaque64(g_slot + (rank * 1024 + warp * 128 + lane) * 4);
  const uint32_t woa = opaque32(sb + R_WO + warp * 12288 + ((lane >> 4) * 8 + (lane & 7)) * 32 + ((((lane >> 3) ^ (lane >> 2)) & 1) << 4));
  const bool has_wo = WG == 0 || isC || w < 3;
  float acc[20];
  uint32_t pk[8] = {0u, 0u, 0u, 0u, 0u, 0u, 0u, 0u};

  auto forward = [&](auto rd, const uint32_t* v, int st, uint32_t tries) {
    constexpr int RD = decltype(rd)::value;
    uint32_t u[6];
#pragma unroll
    for (int j = 0; j < 6; j++) u[j] = movm(v[4 * (j / 3) + j % 3]);
    const bool all3 = RD == 0 || w < 3;
    if (RD == 0) {
      const uint32_t a = L16 + R_M1 + w * 768, a2 = L8 + R_M1 + 512 + w * 768;
      st_async4(a + to1 + 3072, u, bars + to1 + B_MB + 8); st_async2(a2 + to1 + 3072, u[4], u[5], bars + to1 + B_MB + 8);
      sts128(a, u[0], u[1], u[2], u[3]); sts64(a2, u[4], u[5]);
      __syncwarp();
      if (elect_one()) mbar_arrive(bars + B_MB);
      st_async4(a + to2 + 6144, u, bars + to2 + B_MB + 16); st_async2(a2 + to2 + 6144, u[4], u[5], bars + to2 + B_MB + 16);
    } else {
      const uint32_t a = L4 + R_M2 + rank * 2304 + w * 768;
#pragma unroll
      for (int j = 0; j < 6; j++) if (j < 2 || all3) st_async1(a + to1 + j * 128, u[j], bars + to1 + B_MB + 24);
#pragma unroll
      for (int j = 0; j < 6; j++) if (j < 2 || all3) st_async1(a + to2 + j * 128, u[j], bars + to2 + B_MB + 24);
      if (SELF_STAS) {
#pragma unroll
        for (int j = 0; j < 6; j++) if (j < 2 || all3) st_async1(a + j * 128, u[j], bars + B_MB + 24);
      } else {
#pragma unroll
        for (int j = 0; j < 6; j++) if (j < 2 || all3) sts32(a + j * 128, u[j]);
        __syncwarp();
        if (elect_one()) mbar_arrive(bars + B_MB + 24);
      }
    }
  };

  auto send_vt = [&]() {
    if (elect_one()) {
      const uint32_t src = sb + R_VT + warp * 1024;
      bulk_s2s(src + to1, src, 1024, bars + to1 + B_VT);
      bulk_s2s(src + to2, src, 1024, bars + to2 + B_VT);
    }
  };
  auto store_att = [&](int sg) {
    uint32_t* op = reinterpret_cast<uint32_t*>(g_att + (size_t)((sg >> 2) * 64 + head * 2 + rank) * 16384 + (2 * w * 16 + (sg & 3) * 4) * 128) + opaque32(lane);
#pragma unroll
    for (int j = 0; j < 8; j++) op[(j & 1) * 512 + (j >> 1) * 32] = pk[j];
  };

  if (WG == 0) bar_arrive<NB_G, 256>();
#pragma unroll 1
  for (int s = -1; s < NSEG; s++) {
    const uint32_t par = (s + 1) & 1;
    const uint32_t last = s == NSEG - 1;
    TRACE(0);
    {
      float c[NCH][4];
      uint32_t b[3][6];
      const uint32_t ma = L16, m8 = L8;
#pragma unroll
      for (int i = 0; i < 18; i++) {
        if (i < 16) {
          if (i % 4 == 0 && !(i == 4 && TOP2)) mbar_wait(bars + B_MB + (i / 4) * 8, par ^ 1);
          if (i == 0 && TOP2) mbar_wait(bars + B_MB + 8, par ^ 1);
          if (i % 4 == 0) TRACE(1 + i / 4);
          if (i < 12) { lds128(b[i % 3], ma + R_M1 + i * 768); lds64(b[i % 3] + 4, m8 + R_M1 + 512 + i * 768); }
          else { ldsm4(b[i % 3], ma + R_M2 + 4096 + (i - 12) * 768); ldsm2(b[i % 3] + 4, ma + R_M2 + 4096 + 512 + (i - 12) * 768); }
          if (WG == 1 && i == BX_I) {
            bar_sync<NB_G, 256>();
            if (!last && elect_one()) load_chunk(sb + R_GB + w * 4096, s + 1, g0, bars + B_FB);
          }
          if (i == CX_I) {
            if (isC && s >= 0) send_vt();
            if (WG == 1 && ATT_LATE && !isC && s > 0) store_att(s - 1);
          }
          __syncwarp();
        }
        if (i >= 2) {
          const int j = i - 2;
#pragma unroll
          for (int q = 0; q < 3; q++) {
            const uint32_t* f = W[3 * j + q];
            if (3 * j + q < NCH) hmma0(c[3 * j + q], f[0], f[1], f[2], f[3], b[j % 3][2 * q], b[j % 3][2 * q + 1]);
            else hmma(c[(3 * j + q) % NCH], f[0], f[1], f[2], f[3], b[j % 3][2 * q], b[j % 3][2 * q + 1]);
          }
        }
        if (i == 14) zero_regs<16>(acc);
        if (i == 16) mbar_wait(bars + B_FA, last);
      }
#pragma unroll
      for (int j = 0; j < 4; j++) acc[16 + j] = NCH == 3 ? (c[0][j] + c[1][j]) + c[2][j] : (c[0][j] + c[1][j]) + (c[2][j] + c[NCH - 1][j]);
    }
    TRACE(5);
    bar_sync<NB_H, 256>();
    WG_FENCE();
#pragma unroll
    for (int k = 0; k < 16; k++) wg_ss40<0>(acc, dsc.tail_a[WG * 16 + k], dsc.tail_b[k]);
    WG_COMMIT();
    uint32_t vt[4][4];
    {
      const uint32_t a = opaque32(L4 + w * 256 + (isC ? WG * 1024 + R_VM : R_QK + 4096 + WG * 5120));
      const uint32_t qa = L16 + R_QK, xa = opaque32(LV + w * 2048 + (WG == 0 ? 0 : (opaque32(lane) & 8) * 64 + R_QK + 5120 - R_VT));
      const uint32_t d = opaque32(L4 + R_XS + rank * 640 + w * 256);
      if (s == 0) {
        mbar_wait_safe(bars + B_WO, 0);
        if (!GO_EARLY && WG == 1 && head == 0 && rank == 0 && w == 0 && elect_one()) red_add_u32(&g_flags[FL_GO], 1);
      }
      mbar_wait(bars + B_FB, last);
      if (WG == 0) mbar_wait(bars + B_VT, par);
      WG_WAIT(0);
      reg_fence<20>(acc);
      TRACE(6);
      const uint32_t p0 = pack2(acc[16], acc[17]), p1 = pack2(acc[18], acc[19]);
      sts32(a, p0); sts32(a + 128, p1);
      if (isC) {
        st_async1(a + to1, p0, bars + B_VM + to1); st_async1(a + to1 + 128, p1, bars + B_VM + to1);
        st_async1(a + to2, p0, bars + B_VM + to2); st_async1(a + to2 + 128, p1, bars + B_VM + to2);
      }
      if (WG == 0) {
        bar_arrive<NB_A, 256>();
        if (Q_FENCE && !isC) fence_async_smem();
#pragma unroll
        for (int i = 0; i < 4; i++) ldsm4(vt[i], xa + (i >> 1) * 1024 + (i & 1) * 256);
        bar_sync<NB_S, 256>();
      } else {
        bar_sync<NB_A, 256>();
        if (!isC) {
          if (w < 3) {
            uint32_t q[8], k[4][4];
            ldsm4t(q, qa + 4096); ldsm4t(k[0], xa); ldsm4t(k[1], xa + 256);
            ldsm4t(q + 4, qa + 4096 + 512); ldsm4t(k[2], xa + 512); ldsm4t(k[3], xa + 768);
            float x[4], y[4];
            hmma0(x, k[0][0], k[0][1], k[0][2], k[0][3], q[0], q[1]); hmma0(y, k[1][0], k[1][1], k[1][2], k[1][3], q[2], q[3]);
            hmma(x, k[2][0], k[2][1], k[2][2], k[2][3], q[4], q[5]); hmma(y, k[3][0], k[3][1], k[3][2], k[3][3], q[6], q[7]);
            const uint32_t s0 = pack2(x[0] + y[0], x[1] + y[1]), s1 = pack2(x[2] + y[2], x[3] + y[3]);
            st_async1(d + to1, s0, bars + B_XS + to1);
            st_async1(d + to2, s0, bars + B_XS + to2);
            if (w < 2) { st_async1(d + to1 + 128, s1, bars + B_XS + to1); st_async1(d + to2 + 128, s1, bars + B_XS + to2); sts32(d + 128, s1); }
            sts32(d, s0);
          }
        }
        bar_arrive<NB_S, 256>();
      }
    }
    if (WG == 1) {
      if (!last && elect_one()) load_chunk(sb + R_GA + w * 4096, s + 1, g1, bars + B_FA);
      {
        if (w > 0 && elect_one()) mbar_expect(bars + B_MB + 8 * w, w < 3 ? 3072 : SELF_STAS ? 28 * 256 : isC ? 18 * 256 : 19 * 256);
      }
      fence_async_smem();
      bar_sync<NB_B, 256>();
    }
    TRACE(7);
    WG_FENCE();
#pragma unroll
    for (int k = 0; k < 16; k++) wg_rs32<1>(acc, W[k][0], W[k][1], W[k][2], W[k][3], dsc.tok[16 + k]);
    WG_COMMIT();
    uint32_t wa[3][4];
    const uint32_t oxa = L16 + R_OX;
    if (WG == 0) {
      const uint32_t vma = oxa - (R_OX - R_VM) + w * 512, oa = opaque32(L4 + w * 512 + R_OX);
      TRACE(8);
      mbar_wait(bars + B_XS, par);
      TRACE(9);
      float sv[10];
      {
        uint32_t x[10];
        ldsm4t(x, oxa - (R_OX - R_XS)); ldsm4t(x + 4, oxa - (R_OX - R_XS) + 512); ldsm2t(x + 8, oxa - (R_OX - R_XS) + 1024);
        bar_arrive<NB_B, 256>();
#pragma unroll
        for (int j = 0; j < 5; j++) x[j] = hadd2(x[j], x[j + 5]);
        exp10(sv, x);
      }
      WG_WAIT(0);
      bar_arrive<NB_X, 256>();
      mbar_wait(bars + B_VM, par);
      uint32_t vm[4];
      ldsm4(vm, vma);
      uint32_t pb[5];
#pragma unroll
      for (int j = 0; j < 5; j++) pb[j] = pack2(sv[2 * j], sv[2 * j + 1]);
      TRACE(10);
      float o0[4], o1[4], sm[4];
      const uint32_t ONE = 0x3f803f80u;
      hmma0(o0, vt[0][0], vt[0][1], vt[0][2], vt[0][3], pb[0], pb[1]);
      hmma0(o1, vt[2][0], vt[2][1], vt[2][2], vt[2][3], pb[0], pb[1]);
      hmma0(sm, ONE, ONE, ONE, ONE, pb[0], pb[1]);
      hmma(sm, ONE, ONE, ONE, ONE, pb[2], pb[3]);
      hmma(o0, vt[1][0], vt[1][1], vt[1][2], vt[1][3], pb[2], pb[3]);
      hmma(o1, vt[3][0], vt[3][1], vt[3][2], vt[3][3], pb[2], pb[3]);
      hmma_k8(sm, ONE, ONE, pb[4]);
      hmma_k8(o0, vm[0], vm[1], pb[4]);
      hmma_k8(o1, vm[2], vm[3], pb[4]);
#pragma unroll
      for (int i = 0; i < 3; i++) ldsm4t(wa[i], woa + i * 4096);
      __syncwarp();
      const float i0 = rcp(sm[0]), i1 = rcp(sm[1]);
      sts32(oa, pack2(o0[0] * i0, o0[1] * i1)); sts32(oa + 128, pack2(o0[2] * i0, o0[3] * i1));
      sts32(oa + 256, pack2(o1[0] * i0, o1[1] * i1)); sts32(oa + 384, pack2(o1[2] * i0, o1[3] * i1));
      TRACE(11);
      bar_sync<NB_C, 128>();
    } else {
      if (!isC) {
        constexpr uint64_t dQ = mkdesc(0x400 + R_QK, 128, 1024, 0), dK = mkdesc(0x400 + R_QK + 5120, 128, 1024, 0);
        float sc[16];
        zero_regs<16>(sc);
        WG_FENCE();
#pragma unroll
        for (int k = 0; k < 4; k++) wg_ss32<1>(sc, dK + k * 16, dQ + k * 16);
        WG_COMMIT();
        const uint32_t top = rank == 0 ? to2 : to1, e = L4 + R_P + w * 256;
        WG_WAIT(0);
        bar_sync<NB_X, 256>();
        if (!last && elect_one()) load_chunk(sb + R_GB + w * 4096, s + 1, g2, bars + B_FB);
        reg_fence<16>(sc);
        if (w < 3) {
#pragma unroll
          for (int j = 0; j < 8; j++) {
            if ((j & 1) ? (j > 1 && (w == 0 || (w == 1 && j == 7))) : (j >= 4 || w != 1)) {
              const uint32_t t = pack2(sc[2 * j], sc[2 * j + 1]), o = (j >> 1) * 768 + (j & 1) * 128;
              st_async1(e + top + 3072 + o, t, bars + top + B_TS);
              sts32(e + o, t);
            }
          }
          __syncwarp();
          if (elect_one()) mbar_arrive(bars + B_TS);
        }
      } else {
        WG_WAIT(0);
        bar_sync<NB_X, 256>();
        if (!last && elect_one()) load_chunk(sb + R_GB + w * 4096, s + 1, g2, bars + B_FB);
      }
      TRACE(8);
      mbar_wait(bars + B_FA, 1);
      TRACE(11);
    }
    if (has_wo) {
      float* rslot = SLOT(s);
      uint32_t ob[4][4];
      float c[3][4];
      if (WG == 1) {
#pragma unroll
        for (int i = 0; i < 3; i++) ldsm4t(wa[i], woa + i * 4096);
        bar_sync<NB_D, 256>();
      }
      ldsm4t(ob[0], oxa);
      __syncwarp();
#pragma unroll
      for (int k = 0; k < 8; k++) {
        uint32_t nx[3][4];
        if ((k & 1) == 0 && k < 6) { ldsm4t(ob[(k >> 1) + 1], oxa + ((k >> 1) + 1) * 512); __syncwarp(); }
#pragma unroll
        for (int i = 0; i < 3; i++) {
          const uint32_t* o = ob[k >> 1] + (k & 1) * 2;
          if (k < 7) { ldsm4t(nx[i], woa + i * 4096 + (k + 1) * 512); if (i == 2) __syncwarp(); }
          if (k == 0) hmma0(c[i], wa[i][0], wa[i][1], wa[i][2], wa[i][3], o[0], o[1]);
          else hmma(c[i], wa[i][0], wa[i][1], wa[i][2], wa[i][3], o[0], o[1]);
#pragma unroll
          for (int q = 0; q < 4; q++) if (k < 7) wa[i][q] = nx[i][q];
        }
        if (k == ND_K && WG == 0) bar_arrive<NB_D, 256>();
      }
      const float* cv = &c[0][0];
      uint32_t r[6];
#pragma unroll
      for (int j = 0; j < 6; j++) r[j] = pack2(cv[2 * j], cv[2 * j + 1]);
      asm volatile("{\n.reg .pred p;\nsetp.lt.s32 p, %8, 0;\n@p bra.uni SKIP;\n"
                   "red.relaxed.gpu.global.add.noftz.v4.bf16x2 [%0], {%1, %2, %3, %7};\n"
                   "red.relaxed.gpu.global.add.noftz.v4.bf16x2 [%0+1024], {%4, %5, %6, %7};\nSKIP:\n}"
                   :: "l"(rslot), "r"(r[0]), "r"(r[1]), "r"(r[2]), "r"(r[3]), "r"(r[4]), "r"(r[5]), "r"(0x3f800000), "r"(s) : "memory");
    } else {
      bar_arrive<NB_D, 256>();
      if ((s & 3) == 0) {
        fence_gpu();
        if (s > 0 && elect_one()) red_add_u32(&g_flags[FL_ATT + 2 * (s - 4)], 1);
      }
      if (PFD && head < 8 && (PFD > 90 || s + PFD < NSEG) && elect_one())
        asm volatile("cp.async.bulk.prefetch.L2.global [%0], 4096;" :: "l"(g_h + (size_t)((PFD > 90 ? 0 : s + PFD) * 16 + head * 2 + rank) * 4096) : "memory");
      if (rank == 0 || head < 16)
        reinterpret_cast<uint4*>(g_slot)[((s + CLR_D) & 3) * 3072 + ((s + CLR_D) & 4) * 8 + rank * 2048 + head * 64 + opaque32(lane)] = make_uint4(0, 0, 0, 0);
    }
    const uint32_t t_red = clk32();
    uint32_t v[8];
    const float* slot = SLOT(s);
    TRACE(13);
    if (WG == 0) {
      if (!isC) {
        const int ln = opaque32(lane), kg = w - (ln >> 3);
        const uint32_t r16 = sb + R_P + w * 768 + (ln & 7) * 16;
        const uint32_t ta = r16 + (kg >= 0 ? kg * 128 : 640);
        const int dg = (ln >> 2) - 2 * (ln & 3);
        const uint32_t keep = dg > 0 ? 0xffffffffu : dg == 0 ? 0x0000ffffu : 0u;
        mbar_wait(bars + B_TS, par);
        uint32_t x[6], y[4];
        ldsm4t(x, ta); ldsm4t(y, ta + 3072); ldsm2t(x + 4, r16 + 512 + ((ln >> 3) & 1) * 3072);
#pragma unroll
        for (int j = 0; j < 5; j++) x[j] = hadd2(x[j], j < 4 ? y[j] : x[5]);
        x[0] = (x[0] & keep) | (0xff80ff80u & ~keep);
        float sv[10];
        exp10(sv, x);
        float sum = (((sv[0] + sv[1]) + (sv[2] + sv[3])) + ((sv[4] + sv[5]) + (sv[6] + sv[7]))) + (sv[8] + sv[9]);
        sum += __shfl_xor_sync(0xffffffffu, sum, 1);
        sum += __shfl_xor_sync(0xffffffffu, sum, 2);
        const float inv = rcp(sum);
#pragma unroll
        for (int j = 0; j < 5; j++) x[j] = pack2(sv[2 * j] * inv, sv[2 * j + 1] * inv);
        stsm4(r16 + (kg & 3) * 128, x);
        sts32(sb + ln * 4 + w * 768 + R_P + 512, x[4]);
        fence_async_smem();
        bar_arrive<NB_P, 256>();
      }
      while (clk32() - t_red < POLL_DELAY) {}
      load_red(v, slot);
      bar_sync<NB_E, 256>();
    } else {
      mbar_wait(bars + B_FB, 1);
    }
    TRACE(14);
    float ao[16];
    if (WG == 1) zero_regs<16>(ao);
    WG_FENCE();
#pragma unroll
    for (int k = 0; k < 32; k++) {
      if (WG == 0 && k == 16) WG_COMMIT();
      wg_rs32<1>(acc, W[16 + k][0], W[16 + k][1], W[16 + k][2], W[16 + k][3], dsc.tok[k]);
    }
    WG_COMMIT();
    TRACE(12);
    if (WG == 1) {
      if (!isC) {
        constexpr uint64_t dP = mkdesc(0x400 + R_P, 128, 768, 0);
        const uint64_t dV = mkdesc(0x400 + R_VT, 128, 512, 0) + rank * 256, dM = mkdesc(0x400 + R_VM, 0, 128, 0) + rank * 64;
        bar_sync<NB_P, 256>();
        WG_FENCE();
        wg_ss32<0>(ao, dV, dP); wg_ss32<0>(ao, dV + 16, dP + 16); wg_ss32<0>(ao, dM, dP + 32);
        WG_COMMIT();
      }
      bar_arrive<NB_E, 256>();
      if (elect_one()) mbar_expect(bars + B_XS + 8 * w, arm_bytes);
      while (clk32() - t_red < POLL_DELAY1) {}
      load_red(v, slot);
      bar_arrive<NB_W0, 128>();
    } else {
      WG_WAIT(1);
      bar_arrive<NB_F, 256>();
      sched_fence(head, 100);
      v[3] = opaque32(v[3]);
      const uint32_t tries = finish_red(v, slot);
      forward(std::integral_constant<int, 0>(), v, s, tries);
      TRACE(16);
    }
    WG_WAIT(0);
    reg_fence<16>(acc);
    if (WG == 0) bar_arrive<NB_G, 256>();
    TRACE(15);
    {
      uint32_t pq[8];
#pragma unroll
      for (int j = 0; j < 8; j++) pq[j] = pack2(acc[2 * j], acc[2 * j + 1]);
      if (WG == 1) {
        reg_fence<16>(ao);
#pragma unroll
        for (int j = 0; j < 8; j++) pk[j] = pack2(ao[2 * j], ao[2 * j + 1]);
      }
      if (!isC) {
        const uint32_t q = L4 + w * 256 + R_QK + WG * 5120;
#pragma unroll
        for (int j = 0; j < 8; j++) sts32(q + (j >> 1) * 1024 + (j & 1) * 128, pq[j]);
        if (WG == 1 && !ATT_LATE && s >= 0) store_att(s);
      } else {
        const uint32_t a = LV + warp * 1024;
        stsm4(a, pq); stsm4(a + 256, pq + 4);
      }
    }
    TRACE(17);
    if (WG == 1) {
      auto refill = [&]() {
        bar_sync<NB_F, 256>();
        if (s < NSEG - 2 && elect_one()) load_chunk(sb + R_GA + w * 4096, s + 2, 12 + w, bars + B_FA);
      };
      if (RF_FIRST) refill();
      if (has_wo) { v[3] = opaque32(v[3]); const uint32_t tries = finish_red(v, slot); forward(std::integral_constant<int, 1>(), v, s, tries); }
      if (!RF_FIRST) refill();
      TRACE(16);
    }
    if (isC && V_FENCE) { fence_async_smem(); __syncwarp(); }
    TRACE(18);
  }
  if (WG == 1 && ATT_LATE && !isC) store_att(NSEG - 1);
  if (WG == 1) bar_sync<NB_G, 256>();
  mbar_wait_safe(bars + B_MB + 8, 0); mbar_wait_safe(bars + B_MB + 16, 0); mbar_wait_safe(bars + B_MB + 24, 0);
#undef L16
#undef L8
#undef L4
#undef SLOT
#undef LV
}

__global__ void __cluster_dims__(3, 1, 1) __launch_bounds__(256, 1)
kernel_R(const __grid_constant__ CUtensorMap tmq, const __grid_constant__ CUtensorMap tmk, const __grid_constant__ CUtensorMap tmv,
         const __grid_constant__ CUtensorMap tmo, const __grid_constant__ CUtensorMap tmm, const __nv_bfloat16* __restrict__ x,
         const __nv_bfloat16* __restrict__ mem0, const __nv_bfloat16* __restrict__ cvec, const __grid_constant__ RDesc dsc) {
  extern __shared__ __align__(1024) uint8_t smem[];
  const uint32_t sb = smem_u32(smem);
  uint32_t rank; asm("mov.u32 %0, %%cluster_ctarank;" : "=r"(rank));
  rank = __shfl_sync(0xffffffffu, rank, 0);
  const int cta = blockIdx.x, head = __shfl_sync(0xffffffffu, cta / 3, 0);
  const int tid = threadIdx.x, lane = tid & 31;
  const int warp = __shfl_sync(0xffffffffu, tid >> 5, 0);
  const int wg = warp >> 2, w = warp & 3;
  const uint32_t bars = sb + R_BAR;
  const CUtensorMap* tmw = rank == 2 ? &tmv : (wg == 0 ? &tmq : &tmk);
  const int fcol = head * 128 + (rank == 2 ? wg * 64 : (int)rank * 64);

  asm volatile("griddepcontrol.launch_dependents;");
  uint32_t W[48][4];
  {
    if (sb != (rank << 24) + 0x400) __trap();
    if (tid == 0) {
      sts64(bars + 248, rank, head);
      mbar_init(bars + B_MB, 4); mbar_init(bars + B_MB + 8, 1); mbar_init(bars + B_MB + 16, 1); mbar_init(bars + B_MB + 24, SELF_STAS ? 1 : rank == 2 ? 5 : 4);
      for (int i = B_XS; i <= B_X; i += 8) mbar_init(bars + i, i == B_FA || i == B_FB || (i == B_TS && rank < 2) ? 4 : 1);
      asm volatile("fence.mbarrier_init.release.cluster;" ::: "memory");
      fence_async_smem();
    }
    __syncthreads();
    asm volatile("barrier.cluster.arrive.relaxed.aligned;" ::: "memory");
    TS(0);
    const int nwm = rank == 0 ? 6 : 5, wm0 = rank == 0 ? 0 : 5 * rank + 1, nrg = cta < 64 ? 3 : 2;
    if (elect_one()) {
      if (warp == 0) { mbar_expect(bars + B_WM, nwm * 8192); mbar_expect(bars + B_X, nrg * 16384); }
      if (warp < nwm) tma2d_once(sb + R_GA + warp * 8192, &tmm, head * 64, (wm0 + warp) * 64, bars + B_WM);
#pragma unroll 1
      for (int r = 0; r < nrg; r++) bulk_g2s(sb + R_TAIL + (r * 8 + warp) * 2064, x + (size_t)((cta + 96 * r) * 8 + warp) * D_, 2048, bars + B_X);
      if (w == 0) mbar_expect(bars + B_STG + wg * 16, 49152);
      if (w < 2) tma2d_once(sb + R_WO + wg * 49152 + w * 8192, tmw, fcol, rot_chunk(w, rank) * 64, bars + B_STG + wg * 16);
    }
    float* scr = reinterpret_cast<float*>(smem + R_VT);
#pragma unroll 1
    for (int i = tid; i < nwm * 64; i += 256) {
      const float c = __bfloat162float(cvec[wm0 * 64 + i]);
      scr[i] = __bfloat162float(__float2bfloat16(c / (1.f + __expf(-c))));
    }
    if (tid < 128) {
      uint32_t e[4] = {0u, 0u, 0u, 0u};
      if (cta >= 72 && (tid & 32)) {
        const uint16_t* mp = reinterpret_cast<const uint16_t*>(mem0) + 2 * (lane & 3) * D_ + (lane >> 2);
#pragma unroll
        for (int q = 0; q < 3; q++) {
          const int n = 3 * (tid >> 6) + q, col = wo_tile(3 * (cta & 7) + (n >> 1), (cta - 72) >> 3) * 16 + 8 * (n & 1);
          e[q] = mp[col] | (uint32_t)mp[col + D_] << 16;
        }
        e[3] = 0x42000000u;
      }
      reinterpret_cast<uint4*>(g_slot)[cta * 128 + tid] = make_uint4(e[0], e[1], e[2], e[3]);
    }
    __syncthreads();
    TS(1);
    mbar_wait_safe(bars + B_WM, 0);
    if (elect_one()) tma2d_once(sb + R_WO + wg * 49152 + (2 + w) * 8192, tmw, fcol, rot_chunk(2 + w, rank) * 64, bars + B_STG + wg * 16);
    {
      float a[8];
#pragma unroll
      for (int j = 0; j < 8; j++) a[j] = 0.f;
#pragma unroll 2
      for (int i = 0; i < 2 * nwm; i++) {
        uint32_t u[4];
        lds128(u, sb + R_GA + i * 4096 + tid * 16);
        const float sc = scr[i * 32 + (tid >> 3)];
#pragma unroll
        for (int j = 0; j < 4; j++) { a[2 * j] += sc * bf_lo(u[j]); a[2 * j + 1] += sc * bf_hi(u[j]); }
      }
#pragma unroll
      for (int j = 0; j < 8; j++) { a[j] += __shfl_xor_sync(0xffffffffu, a[j], 8); a[j] += __shfl_xor_sync(0xffffffffu, a[j], 16); }
      if (lane < 8) {
        sts128(sb + R_VT + 1536 + warp * 256 + lane * 32, __float_as_uint(a[0]), __float_as_uint(a[1]), __float_as_uint(a[2]), __float_as_uint(a[3]));
        sts128(sb + R_VT + 1552 + warp * 256 + lane * 32, __float_as_uint(a[4]), __float_as_uint(a[5]), __float_as_uint(a[6]), __float_as_uint(a[7]));
      }
    }
    __syncthreads();
    TS(2);
    if (warp == 7) {
      float t0 = 0.f, t1 = 0.f;
#pragma unroll
      for (int i = 0; i < 8; i++) { float t[2]; lds64f(t, sb + R_VT + 1536 + i * 256 + lane * 8); t0 += t[0]; t1 += t[1]; }
      reinterpret_cast<float2*>(g_modp + rank * 2048 + head * 64)[lane] = make_float2(t0, t1);
      fence_gpu();
      __syncwarp();
      if (lane == 0) red_add_u32(&g_flags[FL_S1], 1);
      __syncwarp();
    }
    mbar_wait_safe(bars + B_X, 0);
#pragma unroll 1
    for (int r = 0; r < nrg; r++) {
      float f[32];
#pragma unroll
      for (int i = 0; i < 4; i++) {
        uint32_t u[4];
        lds128(u, sb + R_TAIL + (r * 8 + warp) * 2064 + i * 512 + lane * 16);
#pragma unroll
        for (int j = 0; j < 4; j++) { f[8 * i + 2 * j] = bf_lo(u[j]); f[8 * i + 2 * j + 1] = bf_hi(u[j]); }
      }
      float t = 0.f;
#pragma unroll
      for (int i = 0; i < 32; i++) t += f[i];
#pragma unroll
      for (int o = 1; o < 32; o <<= 1) t += __shfl_xor_sync(0xffffffffu, t, o);
      const float mean = t * (1.f / D_);
      t = 0.f;
#pragma unroll
      for (int i = 0; i < 32; i++) t = fmaf(f[i] - mean, f[i] - mean, t);
#pragma unroll
      for (int o = 1; o < 32; o <<= 1) t += __shfl_xor_sync(0xffffffffu, t, o);
      const float rstd = rsqrtf(t * (1.f / D_) + 1e-5f);
      if (lane == 0) sts64(sb + R_VT + 3584 + (r * 8 + warp) * 8, __float_as_uint(rstd), __float_as_uint(-mean * rstd));
    }
    TS(3);
    if (w < PF1 && elect_one()) tma2d_prefetch(tmw, fcol, rot_chunk(6 + w, rank) * 64);
    if (tid == 0) wait_flag(&g_flags[FL_S1], 96);
    __syncthreads();
    TS(4);
    {
      float4 p[6];
#pragma unroll
      for (int i = 0; i < 6; i++) p[i] = __ldcg(reinterpret_cast<const float4*>(g_modp + (i >> 1) * 2048) + 2 * tid + (i & 1));
      if (w < PF2 && elect_one()) tma2d_prefetch(tmw, fcol, (9 + w) * 64);
      sts128(sb + R_VT + 5120 + tid * 16, pack2(p[0].x + p[2].x + p[4].x, p[0].y + p[2].y + p[4].y), pack2(p[0].z + p[2].z + p[4].z, p[0].w + p[2].w + p[4].w),
             pack2(p[1].x + p[3].x + p[5].x, p[1].y + p[3].y + p[5].y), pack2(p[1].z + p[3].z + p[5].z, p[1].w + p[3].w + p[5].w));
    }
    __syncthreads();
#pragma unroll 2
    for (int it = 0; it < 4 * nrg; it++) {
      const int r = it >> 2, rg = cta + 96 * r, c = 16 * warp + (lane >> 3) + 4 * (it & 3);
      uint32_t a[4], b[4], u[4], o[4];
      float t[2];
      lds128(u, sb + R_TAIL + (r * 8 + (lane & 7)) * 2064 + c * 16);
      lds128(a, sb + R_VT + 5120 + c * 16); lds128(b, sb + R_VT + 7168 + c * 16);
      lds64f(t, sb + R_VT + 3584 + (r * 8 + (lane & 7)) * 8);
#pragma unroll
      for (int j = 0; j < 4; j++)
        o[j] = pack2(fmaf(fmaf(bf_lo(u[j]), t[0], t[1]), 1.f + bf_lo(b[j]), bf_lo(a[j])), fmaf(fmaf(bf_hi(u[j]), t[0], t[1]), 1.f + bf_hi(b[j]), bf_hi(a[j])));
      *reinterpret_cast<uint4*>(g_h + (size_t)(rg >> 2) * 65536 + (lane & 7) * 16 + (c & 7) * 128 +
                                (c < 96 ? (c >> 3) * 4096 + (rg & 3) * 1024 : 49152 + (rg & 3) * 4096 + ((c >> 3) - 12) * 1024)) =
          make_uint4(o[0], o[1], o[2], o[3]);
    }
    TS(5);
    __syncthreads();
    TS(6);
    if (w < PF3 && elect_one()) tma2d_once(sb + R_TAIL + warp * 8192, tmw, fcol, 768 + w * 64, bars + B_TAIL);
    if (warp == 3 && lane == 0) { fence_gpu(); red_add_u32(&g_flags[FL_S2], 1); }
    __syncwarp();

    const uint32_t a0 = opaque32(sb + R_WO + wg * 49152 + ((lane >> 4) * 8 + (lane & 7)) * 128 + (((2 * w + ((lane >> 3) & 1)) ^ (lane & 7)) << 4));
    mbar_wait_safe(bars + B_STG + wg * 16, 0);
    TS(7);
#pragma unroll
    for (int i = 0; i < 24; i++) ldsm4t(W[i], a0 + i * 2048);
    if (tid == 0) wait_flag(&g_flags[FL_S2], 96);
    __syncthreads();
    asm volatile("fence.proxy.async.global;" ::: "memory");
    if (elect_one()) {
      if (wg == 0) load_chunk(sb + R_GA + w * 4096, 0, 12 + w, bars + B_FA);
      if (w == 0) mbar_expect(bars + B_STG + wg * 16 + 8, 49152);
#pragma unroll 1
      for (int c = w; c < 6; c += 4) tma2d_once(sb + R_WO + wg * 49152 + c * 8192, tmw, fcol, rot_chunk(6 + c, rank) * 64, bars + B_STG + wg * 16 + 8);
      if (warp == 0) mbar_expect(bars + B_TAIL, 65536);
      if (w >= PF3) tma2d_once(sb + R_TAIL + warp * 8192, tmw, fcol, 768 + w * 64, bars + B_TAIL);
      if (wg == 1) mbar_expect(bars + B_XS + 8 * w, w == 2 ? 0 : arm_size(w, rank == 2));
#pragma unroll 1
      for (int i = warp; i < PF4; i += 8) tma2d_prefetch(&tmo, 16 * wo_tile(i, rank), head * 128);
    }
    TS(8);
    mbar_wait_safe(bars + B_STG + wg * 16 + 8, 0);
    TS(9);
#pragma unroll
    for (int i = 0; i < 24; i++) ldsm4t(W[24 + i], a0 + i * 2048);
    __syncthreads();
    if (elect_one()) {
      const int n = rank == 2 ? 22 : 21;
      if (warp == 0) mbar_expect(bars + B_WO, n * 4096);
#pragma unroll 1
      for (int i = warp; i < n; i += 8) tma2d(sb + R_WO + i * 4096, &tmo, 16 * wo_tile(i, rank), head * 128, bars + B_WO);
    }
    sts32(sb + R_P + warp * 768 + 640 + lane * 4, wg == 0 ? 0u : 0xff80ff80u);
    mbar_wait_safe(bars + B_TAIL, 0);
    if (GO_EARLY && cta == GO_EARLY - 1 && tid == 0) red_add_u32(&g_flags[FL_GO], 1);
    asm volatile("barrier.cluster.wait.aligned;\nbarrier.cluster.arrive.relaxed.aligned;\nbarrier.cluster.wait.aligned;" ::: "memory");
  }
  uint32_t rh[2];
  lds64(rh, bars + 248);
  rh[0] = __shfl_sync(0xffffffffu, rh[0], 0); rh[1] = __shfl_sync(0xffffffffu, rh[1], 0);
  if (wg == 0) r_main<0>(W, dsc, rh[1], rh[0], lane, w);
  else r_main<1>(W, dsc, rh[1], rh[0], lane, w);
  __syncthreads();
  if (rank < 2 && threadIdx.x == 0) { fence_gpu(); red_add_u32(&g_flags[FL_ATT + 8 * 15], 1); }
  asm volatile("barrier.cluster.arrive.release.aligned;\nbarrier.cluster.wait.acquire.aligned;" ::: "memory");
}

template <int TA, bool FIRST> __device__ __forceinline__ void wg_ss256(float* d, uint64_t a, uint64_t b) {
  if (FIRST)
    asm volatile("wgmma.mma_async.sync.aligned.m64n256k16.f32.bf16.bf16 {%0,%1,%2,%3,%4,%5,%6,%7,%8,%9,%10,%11,%12,%13,%14,%15,%16,%17,%18,%19,%20,%21,%22,%23,%24,%25,%26,%27,%28,%29,%30,%31,%32,%33,%34,%35,%36,%37,%38,%39,%40,%41,%42,%43,%44,%45,%46,%47,%48,%49,%50,%51,%52,%53,%54,%55,%56,%57,%58,%59,%60,%61,%62,%63,%64,%65,%66,%67,%68,%69,%70,%71,%72,%73,%74,%75,%76,%77,%78,%79,%80,%81,%82,%83,%84,%85,%86,%87,%88,%89,%90,%91,%92,%93,%94,%95,%96,%97,%98,%99,%100,%101,%102,%103,%104,%105,%106,%107,%108,%109,%110,%111,%112,%113,%114,%115,%116,%117,%118,%119,%120,%121,%122,%123,%124,%125,%126,%127}, %128, %129, 0, 1, 1, %130, 1;"
               : "=f"(d[0]), "=f"(d[1]), "=f"(d[2]), "=f"(d[3]), "=f"(d[4]), "=f"(d[5]), "=f"(d[6]), "=f"(d[7]),
                 "=f"(d[8]), "=f"(d[9]), "=f"(d[10]), "=f"(d[11]), "=f"(d[12]), "=f"(d[13]), "=f"(d[14]), "=f"(d[15]),
                 "=f"(d[16]), "=f"(d[17]), "=f"(d[18]), "=f"(d[19]), "=f"(d[20]), "=f"(d[21]), "=f"(d[22]), "=f"(d[23]),
                 "=f"(d[24]), "=f"(d[25]), "=f"(d[26]), "=f"(d[27]), "=f"(d[28]), "=f"(d[29]), "=f"(d[30]), "=f"(d[31]),
                 "=f"(d[32]), "=f"(d[33]), "=f"(d[34]), "=f"(d[35]), "=f"(d[36]), "=f"(d[37]), "=f"(d[38]), "=f"(d[39]),
                 "=f"(d[40]), "=f"(d[41]), "=f"(d[42]), "=f"(d[43]), "=f"(d[44]), "=f"(d[45]), "=f"(d[46]), "=f"(d[47]),
                 "=f"(d[48]), "=f"(d[49]), "=f"(d[50]), "=f"(d[51]), "=f"(d[52]), "=f"(d[53]), "=f"(d[54]), "=f"(d[55]),
                 "=f"(d[56]), "=f"(d[57]), "=f"(d[58]), "=f"(d[59]), "=f"(d[60]), "=f"(d[61]), "=f"(d[62]), "=f"(d[63]),
                 "=f"(d[64]), "=f"(d[65]), "=f"(d[66]), "=f"(d[67]), "=f"(d[68]), "=f"(d[69]), "=f"(d[70]), "=f"(d[71]),
                 "=f"(d[72]), "=f"(d[73]), "=f"(d[74]), "=f"(d[75]), "=f"(d[76]), "=f"(d[77]), "=f"(d[78]), "=f"(d[79]),
                 "=f"(d[80]), "=f"(d[81]), "=f"(d[82]), "=f"(d[83]), "=f"(d[84]), "=f"(d[85]), "=f"(d[86]), "=f"(d[87]),
                 "=f"(d[88]), "=f"(d[89]), "=f"(d[90]), "=f"(d[91]), "=f"(d[92]), "=f"(d[93]), "=f"(d[94]), "=f"(d[95]),
                 "=f"(d[96]), "=f"(d[97]), "=f"(d[98]), "=f"(d[99]), "=f"(d[100]), "=f"(d[101]), "=f"(d[102]), "=f"(d[103]),
                 "=f"(d[104]), "=f"(d[105]), "=f"(d[106]), "=f"(d[107]), "=f"(d[108]), "=f"(d[109]), "=f"(d[110]), "=f"(d[111]),
                 "=f"(d[112]), "=f"(d[113]), "=f"(d[114]), "=f"(d[115]), "=f"(d[116]), "=f"(d[117]), "=f"(d[118]), "=f"(d[119]),
                 "=f"(d[120]), "=f"(d[121]), "=f"(d[122]), "=f"(d[123]), "=f"(d[124]), "=f"(d[125]), "=f"(d[126]), "=f"(d[127])
               : "l"(a), "l"(b), "n"(TA));
  else
    asm volatile("wgmma.mma_async.sync.aligned.m64n256k16.f32.bf16.bf16 {%0,%1,%2,%3,%4,%5,%6,%7,%8,%9,%10,%11,%12,%13,%14,%15,%16,%17,%18,%19,%20,%21,%22,%23,%24,%25,%26,%27,%28,%29,%30,%31,%32,%33,%34,%35,%36,%37,%38,%39,%40,%41,%42,%43,%44,%45,%46,%47,%48,%49,%50,%51,%52,%53,%54,%55,%56,%57,%58,%59,%60,%61,%62,%63,%64,%65,%66,%67,%68,%69,%70,%71,%72,%73,%74,%75,%76,%77,%78,%79,%80,%81,%82,%83,%84,%85,%86,%87,%88,%89,%90,%91,%92,%93,%94,%95,%96,%97,%98,%99,%100,%101,%102,%103,%104,%105,%106,%107,%108,%109,%110,%111,%112,%113,%114,%115,%116,%117,%118,%119,%120,%121,%122,%123,%124,%125,%126,%127}, %128, %129, 1, 1, 1, %130, 1;"
               : "+f"(d[0]), "+f"(d[1]), "+f"(d[2]), "+f"(d[3]), "+f"(d[4]), "+f"(d[5]), "+f"(d[6]), "+f"(d[7]),
                 "+f"(d[8]), "+f"(d[9]), "+f"(d[10]), "+f"(d[11]), "+f"(d[12]), "+f"(d[13]), "+f"(d[14]), "+f"(d[15]),
                 "+f"(d[16]), "+f"(d[17]), "+f"(d[18]), "+f"(d[19]), "+f"(d[20]), "+f"(d[21]), "+f"(d[22]), "+f"(d[23]),
                 "+f"(d[24]), "+f"(d[25]), "+f"(d[26]), "+f"(d[27]), "+f"(d[28]), "+f"(d[29]), "+f"(d[30]), "+f"(d[31]),
                 "+f"(d[32]), "+f"(d[33]), "+f"(d[34]), "+f"(d[35]), "+f"(d[36]), "+f"(d[37]), "+f"(d[38]), "+f"(d[39]),
                 "+f"(d[40]), "+f"(d[41]), "+f"(d[42]), "+f"(d[43]), "+f"(d[44]), "+f"(d[45]), "+f"(d[46]), "+f"(d[47]),
                 "+f"(d[48]), "+f"(d[49]), "+f"(d[50]), "+f"(d[51]), "+f"(d[52]), "+f"(d[53]), "+f"(d[54]), "+f"(d[55]),
                 "+f"(d[56]), "+f"(d[57]), "+f"(d[58]), "+f"(d[59]), "+f"(d[60]), "+f"(d[61]), "+f"(d[62]), "+f"(d[63]),
                 "+f"(d[64]), "+f"(d[65]), "+f"(d[66]), "+f"(d[67]), "+f"(d[68]), "+f"(d[69]), "+f"(d[70]), "+f"(d[71]),
                 "+f"(d[72]), "+f"(d[73]), "+f"(d[74]), "+f"(d[75]), "+f"(d[76]), "+f"(d[77]), "+f"(d[78]), "+f"(d[79]),
                 "+f"(d[80]), "+f"(d[81]), "+f"(d[82]), "+f"(d[83]), "+f"(d[84]), "+f"(d[85]), "+f"(d[86]), "+f"(d[87]),
                 "+f"(d[88]), "+f"(d[89]), "+f"(d[90]), "+f"(d[91]), "+f"(d[92]), "+f"(d[93]), "+f"(d[94]), "+f"(d[95]),
                 "+f"(d[96]), "+f"(d[97]), "+f"(d[98]), "+f"(d[99]), "+f"(d[100]), "+f"(d[101]), "+f"(d[102]), "+f"(d[103]),
                 "+f"(d[104]), "+f"(d[105]), "+f"(d[106]), "+f"(d[107]), "+f"(d[108]), "+f"(d[109]), "+f"(d[110]), "+f"(d[111]),
                 "+f"(d[112]), "+f"(d[113]), "+f"(d[114]), "+f"(d[115]), "+f"(d[116]), "+f"(d[117]), "+f"(d[118]), "+f"(d[119]),
                 "+f"(d[120]), "+f"(d[121]), "+f"(d[122]), "+f"(d[123]), "+f"(d[124]), "+f"(d[125]), "+f"(d[126]), "+f"(d[127])
               : "l"(a), "l"(b), "n"(TA));
}
template <int TA, bool FIRST> __device__ __forceinline__ void wg_ss128(float* d, uint64_t a, uint64_t b) {
  if (FIRST)
    asm volatile("wgmma.mma_async.sync.aligned.m64n128k16.f32.bf16.bf16 {%0,%1,%2,%3,%4,%5,%6,%7,%8,%9,%10,%11,%12,%13,%14,%15,%16,%17,%18,%19,%20,%21,%22,%23,%24,%25,%26,%27,%28,%29,%30,%31,%32,%33,%34,%35,%36,%37,%38,%39,%40,%41,%42,%43,%44,%45,%46,%47,%48,%49,%50,%51,%52,%53,%54,%55,%56,%57,%58,%59,%60,%61,%62,%63}, %64, %65, 0, 1, 1, %66, 1;"
               : "=f"(d[0]), "=f"(d[1]), "=f"(d[2]), "=f"(d[3]), "=f"(d[4]), "=f"(d[5]), "=f"(d[6]), "=f"(d[7]),
                 "=f"(d[8]), "=f"(d[9]), "=f"(d[10]), "=f"(d[11]), "=f"(d[12]), "=f"(d[13]), "=f"(d[14]), "=f"(d[15]),
                 "=f"(d[16]), "=f"(d[17]), "=f"(d[18]), "=f"(d[19]), "=f"(d[20]), "=f"(d[21]), "=f"(d[22]), "=f"(d[23]),
                 "=f"(d[24]), "=f"(d[25]), "=f"(d[26]), "=f"(d[27]), "=f"(d[28]), "=f"(d[29]), "=f"(d[30]), "=f"(d[31]),
                 "=f"(d[32]), "=f"(d[33]), "=f"(d[34]), "=f"(d[35]), "=f"(d[36]), "=f"(d[37]), "=f"(d[38]), "=f"(d[39]),
                 "=f"(d[40]), "=f"(d[41]), "=f"(d[42]), "=f"(d[43]), "=f"(d[44]), "=f"(d[45]), "=f"(d[46]), "=f"(d[47]),
                 "=f"(d[48]), "=f"(d[49]), "=f"(d[50]), "=f"(d[51]), "=f"(d[52]), "=f"(d[53]), "=f"(d[54]), "=f"(d[55]),
                 "=f"(d[56]), "=f"(d[57]), "=f"(d[58]), "=f"(d[59]), "=f"(d[60]), "=f"(d[61]), "=f"(d[62]), "=f"(d[63])
               : "l"(a), "l"(b), "n"(TA));
  else
    asm volatile("wgmma.mma_async.sync.aligned.m64n128k16.f32.bf16.bf16 {%0,%1,%2,%3,%4,%5,%6,%7,%8,%9,%10,%11,%12,%13,%14,%15,%16,%17,%18,%19,%20,%21,%22,%23,%24,%25,%26,%27,%28,%29,%30,%31,%32,%33,%34,%35,%36,%37,%38,%39,%40,%41,%42,%43,%44,%45,%46,%47,%48,%49,%50,%51,%52,%53,%54,%55,%56,%57,%58,%59,%60,%61,%62,%63}, %64, %65, 1, 1, 1, %66, 1;"
               : "+f"(d[0]), "+f"(d[1]), "+f"(d[2]), "+f"(d[3]), "+f"(d[4]), "+f"(d[5]), "+f"(d[6]), "+f"(d[7]),
                 "+f"(d[8]), "+f"(d[9]), "+f"(d[10]), "+f"(d[11]), "+f"(d[12]), "+f"(d[13]), "+f"(d[14]), "+f"(d[15]),
                 "+f"(d[16]), "+f"(d[17]), "+f"(d[18]), "+f"(d[19]), "+f"(d[20]), "+f"(d[21]), "+f"(d[22]), "+f"(d[23]),
                 "+f"(d[24]), "+f"(d[25]), "+f"(d[26]), "+f"(d[27]), "+f"(d[28]), "+f"(d[29]), "+f"(d[30]), "+f"(d[31]),
                 "+f"(d[32]), "+f"(d[33]), "+f"(d[34]), "+f"(d[35]), "+f"(d[36]), "+f"(d[37]), "+f"(d[38]), "+f"(d[39]),
                 "+f"(d[40]), "+f"(d[41]), "+f"(d[42]), "+f"(d[43]), "+f"(d[44]), "+f"(d[45]), "+f"(d[46]), "+f"(d[47]),
                 "+f"(d[48]), "+f"(d[49]), "+f"(d[50]), "+f"(d[51]), "+f"(d[52]), "+f"(d[53]), "+f"(d[54]), "+f"(d[55]),
                 "+f"(d[56]), "+f"(d[57]), "+f"(d[58]), "+f"(d[59]), "+f"(d[60]), "+f"(d[61]), "+f"(d[62]), "+f"(d[63])
               : "l"(a), "l"(b), "n"(TA));
}
template <int TA, bool FIRST> __device__ __forceinline__ void wg_ss64(float* d, uint64_t a, uint64_t b) {
  if (FIRST)
    asm volatile("wgmma.mma_async.sync.aligned.m64n64k16.f32.bf16.bf16 {%0,%1,%2,%3,%4,%5,%6,%7,%8,%9,%10,%11,%12,%13,%14,%15,%16,%17,%18,%19,%20,%21,%22,%23,%24,%25,%26,%27,%28,%29,%30,%31}, %32, %33, 0, 1, 1, %34, 1;"
               : "=f"(d[0]), "=f"(d[1]), "=f"(d[2]), "=f"(d[3]), "=f"(d[4]), "=f"(d[5]), "=f"(d[6]), "=f"(d[7]),
                 "=f"(d[8]), "=f"(d[9]), "=f"(d[10]), "=f"(d[11]), "=f"(d[12]), "=f"(d[13]), "=f"(d[14]), "=f"(d[15]),
                 "=f"(d[16]), "=f"(d[17]), "=f"(d[18]), "=f"(d[19]), "=f"(d[20]), "=f"(d[21]), "=f"(d[22]), "=f"(d[23]),
                 "=f"(d[24]), "=f"(d[25]), "=f"(d[26]), "=f"(d[27]), "=f"(d[28]), "=f"(d[29]), "=f"(d[30]), "=f"(d[31])
               : "l"(a), "l"(b), "n"(TA));
  else
    asm volatile("wgmma.mma_async.sync.aligned.m64n64k16.f32.bf16.bf16 {%0,%1,%2,%3,%4,%5,%6,%7,%8,%9,%10,%11,%12,%13,%14,%15,%16,%17,%18,%19,%20,%21,%22,%23,%24,%25,%26,%27,%28,%29,%30,%31}, %32, %33, 1, 1, 1, %34, 1;"
               : "+f"(d[0]), "+f"(d[1]), "+f"(d[2]), "+f"(d[3]), "+f"(d[4]), "+f"(d[5]), "+f"(d[6]), "+f"(d[7]),
                 "+f"(d[8]), "+f"(d[9]), "+f"(d[10]), "+f"(d[11]), "+f"(d[12]), "+f"(d[13]), "+f"(d[14]), "+f"(d[15]),
                 "+f"(d[16]), "+f"(d[17]), "+f"(d[18]), "+f"(d[19]), "+f"(d[20]), "+f"(d[21]), "+f"(d[22]), "+f"(d[23]),
                 "+f"(d[24]), "+f"(d[25]), "+f"(d[26]), "+f"(d[27]), "+f"(d[28]), "+f"(d[29]), "+f"(d[30]), "+f"(d[31])
               : "l"(a), "l"(b), "n"(TA));
}

constexpr int H_STAGE = 49152, H_NST = 4;
constexpr int H_STG = H_NST * H_STAGE;
constexpr int H_VEC = H_STG + 16384;
constexpr int H_BAR = H_VEC + 6144;
constexpr int H_SMEM = H_BAR + 256;
constexpr int HB_FULL = 0, HB_EMPTY = 32, HB_IFULL = 64, HB_IEMPTY = 80, HB_ITEM = 96, HB_INC = 104;
enum { IT_END = 0, IT_MOD = 1, IT_XT = 2, IT_OUT = 3, IT_UV = 4, IT_F1 = 5, IT_F2 = 6 };
constexpr int MAX_ITEMS = 1400;
#define D_MOD 4
#define D_UV 2
#define R_LATE 1
#define CH_FENCE 1
#define CH_FENCE1 1
#define N_UV1 20
#define XT_GO 0
struct HList { uint32_t n; uint32_t it[MAX_ITEMS]; };
#define HT(i)

__device__ __forceinline__ uint32_t tile_lane(int warp, int lane) { return warp * 1024 + (lane >> 2) * 64 + (((lane & 3) ^ (lane >> 3)) << 4); }
__device__ __forceinline__ constexpr uint32_t tile_off(int c, int h) { return (c >> 1) * 16384 + (c & 1) * 8192 + h * 512; }

__device__ __forceinline__ void h_pass(uint32_t sb, int nst, uint32_t& st, uint32_t& ph, bool leader) {
#pragma unroll 1
  for (int i = 0; i < nst; i++) {
    mbar_wait(sb + H_BAR + HB_FULL + st * 8, ph);
    if (leader) mbar_arrive(sb + H_BAR + HB_EMPTY + st * 8);
    if (++st == H_NST) { st = 0; ph ^= 1; }
  }
}
template <int BN, int TA, class PRE>
__device__ __forceinline__ void h_mainloop(float* acc, uint32_t sb, int nst, uint32_t& st, uint32_t& ph, int wg, bool leader, bool fixed_a, PRE pre) {
  constexpr int KS = BN == 64 ? 8 : 4;
  constexpr uint32_t BOFF = BN == 64 ? 32768 : 16384;
  const uint64_t da0 = fixed_a ? mkdesc(sb + H_STG, 16, 0, 2) : TA ? mkdesc(sb + wg * 1024, 2048, 128, 0) : mkdesc(sb + wg * 4096, 16, 512, 2);
  const uint64_t db0 = mkdesc(sb + BOFF, 8192, 1024, 1);
  const uint32_t kh = fixed_a ? 32 : 512;
  uint32_t prev = 0;
  auto stage = [&](auto first, int i) {
    constexpr bool FIRST = decltype(first)::value;
    mbar_wait(sb + H_BAR + HB_FULL + st * 8, ph);
    if (FIRST) HT(1);
    const uint64_t da = da0 + (fixed_a ? i * 64 : st * (H_STAGE >> 4)), db = db0 + st * (H_STAGE >> 4);
    WG_FENCE();
#pragma unroll
    for (int k = 0; k < KS; k++) {
      const uint64_t a = da + (k >> 2) * 1024 + (TA ? (k & 3) * 256 : ((k >> 1) & 1) * kh + (k & 1) * 2), b = db + k * 128;
      if (FIRST && k == 0) { if (BN == 256) wg_ss256<TA, true>(acc, a, b); else if (BN == 128) wg_ss128<TA, true>(acc, a, b); else wg_ss64<TA, true>(acc, a, b); }
      else { if (BN == 256) wg_ss256<TA, false>(acc, a, b); else if (BN == 128) wg_ss128<TA, false>(acc, a, b); else wg_ss64<TA, false>(acc, a, b); }
    }
    WG_COMMIT();
  };
  stage(std::true_type(), 0);
  pre();
  prev = st;
  if (++st == H_NST) { st = 0; ph ^= 1; }
#pragma unroll 1
  for (int i = 1; i < nst; i++) {
    stage(std::false_type(), i);
    WG_WAIT(1);
    if (leader) mbar_arrive(sb + H_BAR + HB_EMPTY + prev * 8);
    prev = st;
    if (++st == H_NST) { st = 0; ph ^= 1; }
  }
  WG_WAIT(0);
  HT(2);
  reg_fence<BN / 2>(acc);
  if (leader) mbar_arrive(sb + H_BAR + HB_EMPTY + prev * 8);
}

template <int BN, bool FINAL>
__device__ __forceinline__ bool h_residual(uint32_t sb, uint32_t va, int mt, int n0, uint32_t& st, uint32_t& ph, int warp, int lane, __nv_bfloat16* out,
                                           int part = 0, int lgp = 0) {
  const size_t toff = (size_t)(mt * 16 + (n0 >> 6)) * 16384 + tile_lane(warp, lane);
  uint4 r[BN / 16];
  auto load_r = [&]() {
#pragma unroll
    for (int i = 0; i < BN / 16; i++) r[i] = __ldcg(reinterpret_cast<const uint4*>(g_x1 + toff + tile_off(i >> 1, i & 1)));
  };
  if (!R_LATE) load_r();
  float acc[BN / 2];
  h_mainloop<BN, FINAL ? 0 : 1>(acc, sb, ((FINAL ? 56 : 64) / (BN == 64 ? 2 : 1)) >> lgp, st, ph, warp >> 2, (warp & 3) == 0 && lane == 0, false,
                                [&]() { if (R_LATE) load_r(); });
  if (BN == 64 && lgp > 0) {
    const int tile = (FINAL * 4 + (mt & 3)) * 16 + (n0 >> 6);
    float4* ws = reinterpret_cast<float4*>(g_ws) + (size_t)tile * 8192 + warp * 32 + lane;
#pragma unroll
    for (int i = 0; i < 8; i++) ws[part * 2048 + i * 256] = make_float4(acc[4 * i], acc[4 * i + 1], acc[4 * i + 2], acc[4 * i + 3]);
    bar_sync<1, 256>();
    if (warp == 0 && lane == 0) { fence_gpu(); const uint32_t t = atomicAdd(&g_flags[FL_SPL + tile], 1); fence_gpu(); sts32(sb + H_BAR + HB_INC + 8, t); }
    bar_sync<1, 256>();
    if (lds32(sb + H_BAR + HB_INC + 8) != (1u << lgp) - 1) return false;
#pragma unroll 1
    for (int p = 1; p < (1 << lgp); p++) {
      float4 o[8];
#pragma unroll
      for (int i = 0; i < 8; i++) o[i] = __ldcg(ws + (part ^ p) * 2048 + i * 256);
#pragma unroll
      for (int i = 0; i < 8; i++) { acc[4 * i] += o[i].x; acc[4 * i + 1] += o[i].y; acc[4 * i + 2] += o[i].z; acc[4 * i + 3] += o[i].w; }
    }
  }
  float sm[4] = {0.f, 0.f, 0.f, 0.f};
  const uint32_t stg = sb + H_STG + warp * 2048;
#pragma unroll
  for (int c = 0; c < BN / 32; c++) {
    uint32_t y[2][4] = {{r[2 * c].x, r[2 * c].y, r[2 * c].z, r[2 * c].w}, {r[2 * c + 1].x, r[2 * c + 1].y, r[2 * c + 1].z, r[2 * c + 1].w}}, z[2][4];
#pragma unroll
    for (int j = 0; j < 4; j++) {
      const uint32_t gt = lds32(va + c * 64 + j * 16 + (lane & 3) * 4);
      const uint32_t cb = FINAL ? 0 : lds32(va + 512 + c * 64 + j * 16 + (lane & 3) * 4);
#pragma unroll
      for (int h = 0; h < 2; h++) {
        const float* a = acc + c * 16 + j * 4 + h * 2;
        y[h][j] = pack2(fmaf(bf_lo(gt), a[0], bf_lo(y[h][j])), fmaf(bf_hi(gt), a[1], bf_hi(y[h][j])));
        if (!FINAL) {
          const float p = bf_lo(y[h][j]), q = bf_hi(y[h][j]);
          sm[2 * h] += p + q;
          sm[2 * h + 1] = fmaf(p, p, fmaf(q, q, sm[2 * h + 1]));
          z[h][j] = pack2(fmaf(p, bf_lo(cb), p), fmaf(q, bf_hi(cb), q));
        }
      }
    }
    if (!FINAL) {
#pragma unroll
      for (int h = 0; h < 2; h++) {
        const size_t o = toff + tile_off(c, h);
        *reinterpret_cast<uint4*>(g_x1 + o) = make_uint4(y[h][0], y[h][1], y[h][2], y[h][3]);
        *reinterpret_cast<uint4*>(g_h2 + o) = make_uint4(z[h][0], z[h][1], z[h][2], z[h][3]);
      }
    } else {
#pragma unroll
      for (int h = 0; h < 2; h++) stsm4(stg + (h * 8 + (lane & 7)) * 128 + ((((c & 1) * 4 + (lane >> 3)) ^ (lane & 7)) << 4), y[h]);
      if (c & 1) {
        __syncwarp();
#pragma unroll
        for (int j = 0; j < 4; j++) {
          const int rr = 4 * j + (lane >> 3);
          uint32_t v[4];
          lds128(v, stg + rr * 128 + (((lane & 7) ^ (rr & 7)) << 4));
          *reinterpret_cast<uint4*>(out + (size_t)(mt * 128 + warp * 16 + rr) * D_ + n0 + (c >> 1) * 64 + (lane & 7) * 8) = make_uint4(v[0], v[1], v[2], v[3]);
        }
        __syncwarp();
      }
    }
    if (CH_FENCE && c + 1 < BN / 32) sched_fence(lane, 100);
  }
  if (!FINAL) {
#pragma unroll
    for (int j = 0; j < 4; j++) { sm[j] += __shfl_xor_sync(0xffffffffu, sm[j], 1); sm[j] += __shfl_xor_sync(0xffffffffu, sm[j], 2); }
    const int t = lane & 3;
    const float sv = t == 0 ? sm[0] : t == 1 ? sm[1] : t == 2 ? sm[2] : sm[3];
    asm volatile("red.relaxed.gpu.global.add.f32 [%0], %1;" :: "l"(g_stat + (mt * 128 + warp * 16 + (t >> 1) * 8 + (lane >> 2)) * 2 + (t & 1)), "f"(sv) : "memory");
  }
  return true;
}

__device__ __forceinline__ float silu_mul(float hg, float u) {
  float t; asm("tanh.approx.f32 %0, %1;" : "=f"(t) : "f"(hg));
  const float h = hg * u;
  return fmaf(h, t, h);
}

template <int BN>
__device__ __forceinline__ void h_swiglu(const float* acc, uint32_t va, int mt, int kb0, int warp, int lane) {
  uint8_t* ap = g_act + (size_t)(mt * 56 + kb0) * 16384 + tile_lane(warp, lane);
  float rs[2], nm[2], rh[2];
#pragma unroll
  for (int h = 0; h < 2; h++) {
    float t[2];
    lds64f(t, va + 2048 + (warp * 16 + h * 8 + (lane >> 2)) * 8);
    const float mean = t[0] * (1.f / D_);
    rs[h] = rsqrtf(fmaxf(t[1] * (1.f / D_) - mean * mean, 0.f) + 1e-5f);
    nm[h] = -mean * rs[h];
    rh[h] = 0.5f * rs[h];
  }
#pragma unroll
  for (int c = 0; c < BN / 64; c++) {
    uint32_t y[2][4];
#pragma unroll
    for (int j = 0; j < 4; j++) {
      const float* g = acc + 16 * c + 4 * j; const float* u = g + BN / 4;
      float p[4], q[4], o[4];
      lds128f(p, va + (4 * c + j) * 128 + (lane & 3) * 32); lds128f(q, va + (4 * c + j) * 128 + (lane & 3) * 32 + 16);
#pragma unroll
      for (int e = 0; e < 4; e++)
        o[e] = silu_mul(fmaf(rh[e >> 1], g[e], fmaf(nm[e >> 1], p[e & 1], p[2 + (e & 1)])), fmaf(rs[e >> 1], u[e], fmaf(nm[e >> 1], q[e & 1], q[2 + (e & 1)])));
      y[0][j] = pack2(o[0], o[1]); y[1][j] = pack2(o[2], o[3]);
    }
#pragma unroll
    for (int h = 0; h < 2; h++)
      *reinterpret_cast<uint4*>(ap + tile_off(c, h)) = make_uint4(y[h][0], y[h][1], y[h][2], y[h][3]);
    if (CH_FENCE1 && c + 1 < BN / 64) sched_fence(lane, 100);
  }
}

__global__ void __launch_bounds__(384, 1)
kernel_H(const __grid_constant__ CUtensorMap tmo, const __grid_constant__ CUtensorMap tm1, const __grid_constant__ CUtensorMap tm3,
         const __grid_constant__ CUtensorMap tm2, const __grid_constant__ CUtensorMap tmm, const __nv_bfloat16* __restrict__ x,
         const __nv_bfloat16* __restrict__ cvec, __nv_bfloat16* __restrict__ out, const __grid_constant__ HList list) {
  extern __shared__ __align__(1024) uint8_t smem[];
  constexpr uint32_t sb = 0x400, bars = sb + H_BAR;
  const int tid = threadIdx.x, lane = tid & 31;
  const int warp = __shfl_sync(0xffffffffu, tid >> 5, 0);
  if (tid == 0) {
    if (smem_u32(smem) != sb) __trap();
    for (int i = 0; i < H_NST; i++) { mbar_init(bars + HB_FULL + i * 8, 1); mbar_init(bars + HB_EMPTY + i * 8, 2); }
    for (int i = 0; i < 2; i++) { mbar_init(bars + HB_IFULL + i * 8, 1); mbar_init(bars + HB_IEMPTY + i * 8, 3); }
    fence_async_smem();
  }
  __syncthreads();
  if (warp >= 8) {
    asm volatile("setmaxnreg.dec.sync.aligned.u32 40;");
    if (warp == 8) {
      uint32_t st = 0, ph = 1;
#pragma unroll 1
      for (uint32_t n = 0;; n++) {
        uint32_t q = 0;
        if (lane == 0) q = atomicAdd(&g_flags[FL_HEAD], 1);
        q = __shfl_sync(0xffffffffu, q, 0);
        const uint32_t it = q < list.n ? list.it[q] : 0;
        const int type = it & 7, mt = (it >> 3) & 15, idx = (it >> 7) & 63, sz = (it >> 13) & 3, part = (it >> 15) & 3, lgp = (it >> 17) & 3;
        int f = FL_GO; uint32_t target = 0;
        if (type == IT_OUT) { f = lane == 0 ? FL_ATT + 8 * mt : lane == 1 ? FL_XT + 8 * mt : FL_MOD; target = lane == 0 ? 64 : lane == 1 ? 2 : 12; }
        else if (type == IT_F1) { f = lane == 0 ? FL_OUT + 8 * mt : FL_UV; target = lane == 0 ? 16 : 28; }
        else if (type == IT_F2) { f = lane == 0 ? FL_F1 + 8 * mt : FL_MODB; target = lane == 0 ? 56 : 4; }
        else if (type == IT_UV) { f = FL_MOD; target = 12; }
        else if (type == IT_MOD || (XT_GO && type == IT_XT)) target = 1;
        bool late = false;
        if (lane < 2 && (lane == 0 || type == IT_OUT)) wait_flag(&g_flags[f], target);
        else if (lane == 2) late = ld_acquire(&g_flags[f]) < target;
        late = __shfl_sync(0xffffffffu, late, 2);
        asm volatile("fence.proxy.async.global;" ::: "memory");
        mbar_wait(bars + HB_IEMPTY + (n & 1) * 8, ((n >> 1) & 1) ^ 1);
        if (elect_one()) {
          sts32(bars + HB_ITEM + (n & 1) * 4, it | (q << 19));
          mbar_arrive(bars + HB_IFULL + (n & 1) * 8);
        }
        if (type == IT_END) break;
        if (type != IT_XT) {
          const bool has_a = type == IT_OUT || type >= IT_F1;
          const uint8_t* ap = type == IT_OUT ? g_att + (size_t)mt * 64 * 16384 : type == IT_F1 ? g_h2 + (size_t)mt * 16 * 16384 : g_act + (size_t)mt * 56 * 16384;
          const int nkb = (type == IT_OUT ? 64 : type == IT_F2 ? 56 : 16) >> lgp;
          const uint32_t abytes = has_a ? (sz == 2 ? 32768 : 16384) : 0, bytes = (sz == 0 ? 32768 : 16384) + abytes;
          const int dk = sz == 2 ? 1 : 0;
#pragma unroll 1
          for (int kb = part * nkb; kb < (part + 1) * nkb; kb += 1 + dk) {
            const uint32_t d = sb + st * H_STAGE, fb = bars + HB_FULL + st * 8;
            mbar_wait(bars + HB_EMPTY + st * 8, ph);
            if (has_a && kb + 1 + dk >= (part + 1) * nkb) {
              if (late) {
                if (lane == 2) wait_flag(&g_flags[f], target);
                __syncwarp();
                asm volatile("fence.proxy.async.global;" ::: "memory");
              }
              if (elect_one()) {
                const bool f1 = type == IT_F1;
                const int c0 = f1 ? idx * (128 >> sz) : idx * (256 >> sz);
                const uint32_t v = sb + H_VEC + (n & 1) * 3072;
                const uint32_t n0 = (f1 ? 2048 : 512) >> sz, n1 = f1 ? 1024 : n0;
                asm volatile("mbarrier.expect_tx.relaxed.cta.shared::cta.b64 [%0], %1;" :: "r"(fb), "r"(n0 + n1) : "memory");
                bulk_g2s(v, f1 ? (const void*)(g_uv + c0 * 4) : (const void*)(g_mod + (type == IT_OUT ? 2 : 5) * D_ + c0), n0, fb);
                bulk_g2s(v + (f1 ? 2048 : 512), f1 ? (const void*)(g_stat + mt * 256) : (const void*)(g_mod + 4 * D_ + c0), n1, fb);
              }
            }
            if (elect_one()) {
              mbar_expect(fb, bytes);
              if (has_a) bulk_g2s(d, ap + (size_t)kb * 16384, abytes, fb);
            }
            if (++st == H_NST) { st = 0; ph ^= 1; }
          }
        }
      }
    } else if (warp >= 10) {
      const int hb = warp - 10;
      uint32_t st = 0, ph = 1;
#pragma unroll 1
      for (uint32_t n = 0;; n++) {
        mbar_wait(bars + HB_IFULL + (n & 1) * 8, (n >> 1) & 1);
        const uint32_t it = __shfl_sync(0xffffffffu, lds32(bars + HB_ITEM + (n & 1) * 4), 0);
        const int type = it & 7, idx = (it >> 7) & 63, sz = (it >> 13) & 3, part = (it >> 15) & 3, lgp = (it >> 17) & 3;
        if (type == IT_END) break;
        if (elect_one()) mbar_arrive(bars + HB_IEMPTY + (n & 1) * 8);
        if (type == IT_XT) continue;
        const bool ffn1 = type == IT_F1 || type == IT_UV;
        const int nkb = (type == IT_OUT ? 64 : type == IT_F2 ? 56 : 16) >> lgp;
        const CUtensorMap* tb = type == IT_OUT ? &tmo : ffn1 ? &tm1 : type == IT_F2 ? &tm2 : &tmm;
        const CUtensorMap* tc = ffn1 ? &tm3 : tb;
        const int c0 = ffn1 ? idx * (128 >> sz) : idx * (256 >> sz) + (type == IT_MOD ? 2048 : 0), c2 = ffn1 ? c0 : c0 + 128;
        const int dk = sz == 2 ? 1 : 0;
        const CUtensorMap* t0 = hb == 1 && sz == 1 ? tc : tb;
        const int ca = hb == 0 || sz == 2 || (sz == 1 && ffn1) ? c0 : c0 + 64;
        const uint32_t off = (sz == 2 ? 32768 : 16384) + hb * 8192;
        const uint32_t cold = type == IT_MOD ? D_MOD : type == IT_UV ? D_UV : H_NST;
#pragma unroll 1
        for (int kb = part * nkb; kb < (part + 1) * nkb; kb += 1 + dk) {
          const uint32_t d = sb + st * H_STAGE + off, fb = bars + HB_FULL + st * 8;
          mbar_wait(bars + HB_EMPTY + st * 8, ph);
          if (cold < H_NST) mbar_wait(bars + HB_FULL + ((st - cold) & 3) * 8, st >= cold ? ph ^ 1 : ph);
          if (elect_one()) {
            tma5d(d, t0, ca, kb + hb * dk, fb);
            if (sz == 0) tma5d(d + 16384, tc, c2 + hb * 64, kb, fb);
          }
          if (++st == H_NST) { st = 0; ph ^= 1; }
        }
      }
    } else if (warp == 9) {
#pragma unroll 1
      for (uint32_t n = 0;; n++) {
        mbar_wait(bars + HB_IFULL + (n & 1) * 8, (n >> 1) & 1);
        const uint32_t itq = lds32(bars + HB_ITEM + (n & 1) * 4);
        const int type = itq & 7, mt = (itq >> 3) & 15;
        if (type == IT_END) break;
        if (n & 1) bar_sync<3, 288>(); else bar_sync<2, 288>();
        if (lane == 0) {
          const uint32_t inc = lds32(bars + HB_INC + (n & 1) * 4);
          mbar_arrive(bars + HB_IEMPTY + (n & 1) * 8);
          if (inc) {
            fence_gpu();
            red_add_u32(&g_flags[type == IT_MOD ? (((itq >> 7) & 63) < 12 ? FL_MOD : FL_MODB) : type == IT_UV ? FL_UV : (type == IT_XT ? FL_XT : type == IT_OUT ? FL_OUT : FL_F1) + 8 * mt], inc);
          }
        }
        __syncwarp();
      }
      asm volatile("griddepcontrol.wait;" ::: "memory");
      uint32_t k = 0;
      if (lane == 0) { fence_gpu(); k = atomicAdd(&g_flags[FL_EXIT], 1); }
      k = __shfl_sync(0xffffffffu, k, 0);
      if (k == gridDim.x - 1) {
        fence_gpu();
        for (int i = lane; i < 1024; i += 32) g_flags[i] = 0;
      }
    }
  } else {
    asm volatile("setmaxnreg.inc.sync.aligned.u32 232;");
    const int wg = warp >> 2;
    const bool leader = (tid & 127) == 0;
    uint32_t st = 0, ph = 0;
#pragma unroll 1
    for (uint32_t n = 0;; n++) {
      mbar_wait(bars + HB_IFULL + (n & 1) * 8, (n >> 1) & 1);
      const uint32_t itq = __shfl_sync(0xffffffffu, lds32(bars + HB_ITEM + (n & 1) * 4), 0);
      const int type = itq & 7, mt = (itq >> 3) & 15, idx = (itq >> 7) & 63, sz = (itq >> 13) & 3, part = (itq >> 15) & 3, lgp = (itq >> 17) & 3;
      uint32_t inc = type == IT_OUT ? 4 >> sz : type == IT_F1 ? 2 >> sz : type != IT_F2;
      if (type == IT_END) break;
      HT(0);
      const uint32_t va = sb + H_VEC + (n & 1) * 3072;
      if (type == IT_OUT) {
        if (sz == 0) h_residual<256, false>(sb, va, mt, idx * 256, st, ph, warp, lane, out);
        else if (sz == 1) h_residual<128, false>(sb, va, mt, idx * 128, st, ph, warp, lane, out);
        else inc = h_residual<64, false>(sb, va, mt, idx * 64, st, ph, warp, lane, out, part, lgp);
      } else if (type == IT_F2) {
        if (sz == 0) h_residual<256, true>(sb, va, mt, idx * 256, st, ph, warp, lane, out);
        else if (sz == 1) h_residual<128, true>(sb, va, mt, idx * 128, st, ph, warp, lane, out);
        else h_residual<64, true>(sb, va, mt, idx * 64, st, ph, warp, lane, out, part, lgp);
      } else if (type == IT_XT) {
        const int rg = idx * 8 + warp;
        const uint32_t* xp = reinterpret_cast<const uint32_t*>(x + (size_t)(mt * 128 + rg * 8 + (lane >> 2)) * D_) + (lane & 3);
        uint8_t* tp = g_x1 + (size_t)mt * 262144 + rg * 512 + tile_lane(0, lane);
        if (lane < 16) g_stat[(mt * 128 + rg * 8) * 2 + lane] = 0.f;
#pragma unroll 1
        for (int b = 0; b < 2; b++) {
          uint32_t v[64];
#pragma unroll
          for (int i = 0; i < 64; i++) v[i] = __ldg(xp + 256 * b + 4 * i);
#pragma unroll
          for (int i = 0; i < 16; i++)
            *reinterpret_cast<uint4*>(tp + tile_off(16 * b + i, 0)) = make_uint4(v[4 * i], v[4 * i + 1], v[4 * i + 2], v[4 * i + 3]);
        }
      } else if (sz == 1) {
        float acc[64];
        h_mainloop<128, 0>(acc, sb, 16, st, ph, wg, leader, false, []() {});
        h_swiglu<128>(acc, va, mt, idx, warp, lane);
      } else {
        if (type != IT_F1) {
          bar_sync<1, 256>();
          for (int i = tid; i < D_; i += 256) {
            __nv_bfloat16* p = reinterpret_cast<__nv_bfloat16*>(smem + H_STG + (i >> 5) * 512 + ((i >> 1) & 3) * 16) + ((i >> 3) & 3) * 2 + (i & 1);
            if (type == IT_UV) {
              p[0] = __float2bfloat16(1.f); p[32] = __ldcg(g_mod + 4 * D_ + i); p[64 + ((i & 2) ? -8 : 8)] = __ldcg(g_mod + 3 * D_ + i);
            }
            else { const float c = __bfloat162float(cvec[i]); p[0] = __float2bfloat16(c / (1.f + __expf(-c))); }
          }
          fence_async_smem();
          bar_sync<1, 256>();
        }
        if (type != IT_F1 && wg == 1) {
          h_pass(sb, 16, st, ph, leader);
        } else {
          float acc[128];
          h_mainloop<256, 0>(acc, sb, 16, st, ph, wg, leader, type != IT_F1, []() {});
          if (type == IT_F1) {
            h_swiglu<256>(acc, va, mt, idx * 2, warp, lane);
          } else if (warp == 0) {
#pragma unroll
            for (int j = 0; j < 32; j++) {
              if (type == IT_MOD) {
                if (lane < 4) reinterpret_cast<uint32_t*>(g_mod + 2048 + idx * 256)[j * 4 + lane] = pack2(acc[4 * j], acc[4 * j + 1]);
              } else {
                const float a = acc[4 * j] + __shfl_down_sync(0xffffffffu, acc[4 * j], 4), b = acc[4 * j + 1] + __shfl_down_sync(0xffffffffu, acc[4 * j + 1], 4);
                float2* up = reinterpret_cast<float2*>(g_uv + idx * 512 + ((j & 15) * 4 + (lane & 3)) * 8 + (j >> 4) * 4);
                const float sc = j < 16 ? 0.5f : 1.f;
                if (lane < 4) up[0] = make_float2(sc * a, sc * b);
                else if ((lane >> 2) == 2) up[1] = make_float2(sc * acc[4 * j], sc * acc[4 * j + 1]);
              }
            }
          }
        }
      }
      if (tid == 0) sts32(bars + HB_INC + (n & 1) * 4, inc);
      if (n & 1) bar_arrive<3, 288>(); else bar_arrive<2, 288>();
    }
  }
}

const uint32_t h_items[] = {
  2, 130, 10, 138, 18, 146, 26, 154, 34, 162, 42, 170, 50, 178, 58, 186, 66, 194, 74, 202, 82, 210, 90, 218,
  98, 226, 106, 234, 114, 242, 122, 250, 1, 129, 257, 385, 513, 641, 769, 897, 1025, 1153, 1281, 1409, 4, 132, 260, 388,
  516, 644, 772, 900, 1028, 1156, 1284, 1412, 1540, 1668, 1796, 1924, 2052, 2180, 2308, 16387, 2436, 16515, 16643, 16771, 16899, 17027, 17155, 17283,
  17411, 17539, 17667, 17795, 17923, 18051, 18179, 18307, 2564, 2692, 2820, 2948, 3076, 3204, 3332, 1537, 3460, 1665, 1793, 1921, 16395, 16523, 16651, 16779,
  16907, 17035, 17163, 17291, 17419, 17547, 17675, 17803, 17931, 18059, 18187, 18315, 8211, 8339, 8467, 8595, 8723, 5, 133, 261, 389, 517, 645, 773,
  901, 1029, 1157, 1285, 1413, 1541, 1669, 1797, 1925, 2053, 2181, 2309, 2437, 8851, 8979, 9107, 2565, 2693, 2821, 2949, 3077, 3205, 3333, 3461,
  13, 141, 269, 781, 909, 1037, 1165, 1293, 1421, 1549, 1677, 1805, 1933, 2061, 2189, 2317, 2445, 397, 8219, 525, 8347, 653, 8475, 2573,
  2701, 2829, 8603, 2957, 3085, 8731, 3213, 3341, 17691, 3469, 8198, 8326, 8454, 8582, 17819, 2837, 8710, 8838, 17947, 8966, 18075, 9094, 3093, 18203,
  21, 3221, 18331, 16419, 3349, 16547, 16675, 3477, 16803, 1173, 16931, 1301, 17059, 1429, 2965, 1557, 17187, 1685, 17315, 2197, 17443, 1813, 17571, 2325,
  17699, 1941, 149, 2453, 277, 2069, 405, 2581, 533, 2709, 661, 29, 789, 157, 917, 285, 1045, 413, 17827, 541, 17955, 669, 18083, 797,
  18211, 925, 18339, 1053, 14, 1181, 142, 1309, 270, 1437, 398, 1565, 1693, 1821, 8235, 8363, 8491, 8619, 8747, 8875, 1949, 9003, 9131, 2077,
  2205, 2333, 3229, 2461, 3357, 2589, 3485, 2717, 8243, 2845, 8371, 2973, 8499, 3101, 8627, 8755, 8883, 9011, 9139, 37, 165, 293, 421, 549,
  677, 805, 933, 1061, 1189, 1317, 1445, 1573, 1701, 1829, 1957, 8251, 8379, 8507, 8635, 8763, 8891, 9019, 9147, 2085, 2213, 2341, 2469, 2597,
  2725, 2853, 2981, 3109, 3237, 3365, 3493, 45, 173, 301, 429, 557, 685, 813, 941, 1069, 1453, 1197, 1581, 1325, 9027, 1709, 1837, 1965,
  8259, 8387, 8515, 8643, 8771, 8899, 693, 9155, 2093, 2221, 2349, 2477, 2605, 2733, 2861, 2989, 3117, 3245, 9163, 2101, 2229, 3373, 3501, 53,
  181, 309, 437, 565, 821, 949, 1077, 1205, 1333, 1461, 1589, 1717, 1845, 1973, 8267, 8395, 8523, 8651, 8779, 8907, 9035, 2357, 2485, 2613,
  2741, 2869, 2997, 3125, 3253, 3381, 3509, 61, 189, 317, 445, 573, 701, 829, 957, 1085, 1213, 1341, 1469, 1597, 1725, 2493, 8275, 1853,
  8403, 1981, 8531, 2109, 8659, 2237, 8787, 2365, 8915, 9043, 9171, 2621, 2749, 2877, 3005, 3133, 3261, 3389, 3517, 1733, 69, 453, 197, 1861,
  325, 581, 709, 837, 1477, 965, 1605, 1093, 1989, 10565, 10693, 12357, 12485, 10821, 10949, 12869, 12997, 2245, 2501, 8283, 8411, 8539, 2629, 8667,
  2757, 8795, 2885, 8923, 9179, 3269, 3397, 1229, 3525, 10061, 77, 10189, 205, 333, 461, 589, 10829, 717, 10957, 845, 1101, 3013, 9051, 3141,
  11085, 11213, 11341, 11469, 11597, 11725, 11853, 11981, 12109, 12237, 8675, 8291, 8803, 8419, 8931, 8547, 9059, 341, 3277, 85, 22, 469, 3405, 597,
  3533, 725, 853, 981, 1109, 1237, 1365, 1493, 9187, 12365, 12493, 12621, 12749, 13901, 14029, 2381, 2509, 3021, 213, 2637, 3149, 2765, 1621, 1749,
  1877, 2005, 2133, 2261, 8427, 8299, 2389, 8555, 2517, 8683, 2645, 8811, 2773, 8939, 2901, 9067, 3029, 9195, 150, 278, 406, 30, 158, 430,
  286, 414, 38, 46, 166, 174, 294, 302, 422, 54, 182, 310, 438, 8307, 8435, 8563, 8691, 8819, 8947, 9075, 9203, 278651, 311419, 344187,
  376955, 278779, 311547, 344315, 377083, 180987, 312315, 148347, 345083, 181115, 148731, 181499, 148859, 3157, 62, 148987, 149243, 278907, 3285, 190, 318, 149115, 311675, 148219,
  344443, 279547, 181627, 1757, 377211, 181755, 181883, 1885, 147963, 2013, 180731, 2141, 2269, 2397, 101, 2525, 182011, 148091, 180859, 3165, 149371, 182139, 280571, 313339,
  346107, 279675, 377851, 378875, 312443, 345211, 377979, 446, 2653, 2781, 2909, 3037, 3293, 3421, 3549, 3413, 733, 229, 989, 741, 1117, 1245, 869, 997,
  1373, 1125, 1501, 1253, 1509, 3541, 93, 1629, 221, 349, 477, 1381, 605, 357, 485, 861, 613, 1637, 1893, 2021, 2149, 2277, 2405, 2533,
  2661, 2789, 12269, 2917, 3045, 12397, 3173, 12525, 3301, 12653, 3429, 12781, 12909, 3557, 13037, 8301, 8429, 13165, 13293, 1765, 8557, 8685, 13421, 13549,
  8813, 13677, 9069, 13805, 9197, 13933, 8941, 14061, 9325, 9453, 14189, 14317, 9581, 9709, 14445, 14573, 9837, 10861, 10989, 11117, 11245, 11373, 11501, 11629,
  9965, 14701, 14829, 10093, 10221, 14957, 15213, 15341, 10605, 10733, 15085, 11757, 10349, 8573, 11885, 10477, 8701, 12013, 2549, 12141, 2677, 8317, 2805, 2933,
  8262, 8390, 8518, 8646, 8774, 9030, 9158, 8902, 9038, 9166, 8270, 8398, 8526, 8654, 8782, 3061, 8910, 3189, 3317, 117, 245, 373, 501, 629,
  757, 3445, 3573, 1269, 1397, 1525, 8445, 8829, 8957, 9085, 9213, 9341, 9469, 9597, 9725, 9853, 10621, 9981, 10109, 10749, 11645, 10237, 11773, 12029,
  10365, 11901, 12157, 12285, 10493, 885, 12413, 1653, 1781, 1013, 1909, 1141, 12541, 2037, 12669, 2165, 12797, 2293, 12925, 2421, 13053, 13181, 13309, 13565,
  13437, 13693, 13821, 10877, 11005, 11133, 11517, 13949, 14077, 14205, 14333, 14461, 14589, 14717, 14845, 14973, 8278, 8406, 8534, 15101, 8662, 15229, 8790, 15357,
  9174, 8918, 11261, 8286, 9046, 8542, 11389, 8414, 8670, 8798, 8926, 9054, 9182, 147558, 180326, 147686, 180454, 147814, 180582, 16870, 16998, 17126, 17254, 17382,
  17510, 17638, 17766, 17894, 18022, 18150, 18278, 18406, 16494, 16622, 16750, 16878, 17006, 17134, 17390, 17518, 17646, 17774, 17902, 18030, 18158, 278774, 17262, 18414,
  311542, 18286, 344310, 147574, 377078, 180342, 147830, 180598, 148470, 181238, 16894, 17022, 182006, 149366, 17150, 182134, 148598, 17278, 181366, 148726, 148854, 17534, 181494, 17662,
  181622, 17790, 147958, 180726, 18046, 148086, 180854, 18174, 148214, 180982, 148342, 181110, 148982, 181750, 149110, 181878, 149238, 149494, 182262, 16510, 16638, 16766, 18302, 18430,
  17918, 17406,
};
void build_list(HList& l) {
  l.n = sizeof(h_items) / sizeof(h_items[0]);
  for (uint32_t i = 0; i < l.n; i++) l.it[i] = h_items[i];
}

typedef CUresult (*EncodeFn)(CUtensorMap*, CUtensorMapDataType, cuuint32_t, void*, const cuuint64_t*, const cuuint64_t*,
                             const cuuint32_t*, const cuuint32_t*, CUtensorMapInterleave, CUtensorMapSwizzle,
                             CUtensorMapL2promotion, CUtensorMapFloatOOBfill);

#define PROMO_W CU_TENSOR_MAP_L2_PROMOTION_L2_128B
#define PROMO_O CU_TENSOR_MAP_L2_PROMOTION_L2_128B
#define PROMO_M CU_TENSOR_MAP_L2_PROMOTION_L2_128B
#define PROMO_H CU_TENSOR_MAP_L2_PROMOTION_L2_128B
void make_map(EncodeFn fn, CUtensorMap* m, const void* p, uint64_t cols, uint64_t rows, uint32_t bc, uint32_t br, CUtensorMapSwizzle sw,
              CUtensorMapL2promotion promo) {
  cuuint64_t dims[2] = {cols, rows};
  cuuint64_t strides[1] = {cols * 2};
  cuuint32_t box[2] = {bc, br};
  cuuint32_t es[2] = {1, 1};
  fn(m, CU_TENSOR_MAP_DATA_TYPE_BFLOAT16, 2, const_cast<void*>(p), dims, strides, box, es, CU_TENSOR_MAP_INTERLEAVE_NONE, sw,
     promo, CU_TENSOR_MAP_FLOAT_OOB_FILL_NONE);
}

void make_map_perm(EncodeFn fn, CUtensorMap* m, const void* p, uint64_t cols, uint64_t rows, bool perm) {
  cuuint64_t dims[5] = {cols, 2, 4, 4, rows / 32};
  cuuint64_t strides[4] = {cols * 2, cols * 2 * (perm ? 8 : 2), cols * 2 * (perm ? 2 : 8), cols * 2 * 32};
  cuuint32_t box[5] = {64, 2, 4, 4, 2};
  cuuint32_t es[5] = {1, 1, 1, 1, 1};
  fn(m, CU_TENSOR_MAP_DATA_TYPE_BFLOAT16, 5, const_cast<void*>(p), dims, strides, box, es, CU_TENSOR_MAP_INTERLEAVE_NONE,
     CU_TENSOR_MAP_SWIZZLE_128B, PROMO_H, CU_TENSOR_MAP_FLOAT_OOB_FILL_NONE);
}

}

extern "C" void kernel_launch(void* const* d_in, const int* in_sizes, int n_in, void* d_out, int out_size) {
  const __nv_bfloat16* x = (const __nv_bfloat16*)d_in[0];
  const __nv_bfloat16* mem0 = (const __nv_bfloat16*)d_in[1];
  const __nv_bfloat16* cvec = (const __nv_bfloat16*)d_in[11];
  static EncodeFn enc = nullptr;
  if (!enc) {
    cudaDriverEntryPointQueryResult qr;
    void* fp = nullptr;
    cudaGetDriverEntryPoint("cuTensorMapEncodeTiled", &fp, cudaEnableDefault, &qr);
    enc = (EncodeFn)fp;
    cudaFuncSetAttribute(kernel_R, cudaFuncAttributeMaxDynamicSharedMemorySize, R_SMEM);
    cudaFuncSetAttribute(kernel_H, cudaFuncAttributeMaxDynamicSharedMemorySize, H_SMEM);
  }
  CUtensorMap tmq, tmk, tmv, tmo, tmm;
  make_map(enc, &tmm, d_in[12], 6144, 1024, 64, 64, CU_TENSOR_MAP_SWIZZLE_NONE, PROMO_M);
  make_map(enc, &tmq, d_in[2], 4096, 1024, 64, 64, CU_TENSOR_MAP_SWIZZLE_128B, PROMO_W);
  make_map(enc, &tmk, d_in[3], 4096, 1024, 64, 64, CU_TENSOR_MAP_SWIZZLE_128B, PROMO_W);
  make_map(enc, &tmv, d_in[4], 4096, 1024, 64, 64, CU_TENSOR_MAP_SWIZZLE_128B, PROMO_W);
  make_map(enc, &tmo, d_in[5], 1024, 4096, 16, 128, CU_TENSOR_MAP_SWIZZLE_32B, PROMO_O);
  RDesc dsc;
  for (int k = 0; k < 32; k++) {
    dsc.tok[k] = mkdesc(0x400 + (k < 16 ? R_GA : R_GB) + ((k & 15) >> 2) * 4096 + (k & 3) * 256, 128, 1024, 0);
    dsc.tail_a[k] = mkdesc(0x400 + R_TAIL + k * 2048, 1024, 1024, 1);
    if (k < 16) dsc.tail_b[k] = mkdesc(0x400 + R_GA + k * 256, 128, 4096, 0);
  }
  kernel_R<<<96, 256, R_SMEM, cudaStreamPerThread>>>(tmq, tmk, tmv, tmo, tmm, x, mem0, cvec, dsc);

  CUtensorMap ho, h1, h3, h2, hm;
  make_map_perm(enc, &ho, d_in[5], 1024, 4096, false);
  make_map_perm(enc, &h1, d_in[8], F_, 1024, true);
  make_map_perm(enc, &h3, d_in[9], F_, 1024, true);
  make_map_perm(enc, &h2, d_in[10], 1024, F_, true);
  make_map_perm(enc, &hm, d_in[12], 6144, 1024, true);
  HList list;
  build_list(list);
  cudaLaunchConfig_t cfg = {};
#define H_GRID 132
  cfg.gridDim = dim3(H_GRID); cfg.blockDim = dim3(384); cfg.dynamicSmemBytes = H_SMEM; cfg.stream = cudaStreamPerThread;
  cudaLaunchAttribute at[1];
  at[0].id = cudaLaunchAttributeProgrammaticStreamSerialization;
  at[0].val.programmaticStreamSerializationAllowed = 1;
  cfg.attrs = at;
  cfg.numAttrs = 1;
  cudaLaunchKernelEx(&cfg, kernel_H, ho, h1, h3, h2, hm, x, cvec, (__nv_bfloat16*)d_out, list);
}
```

```cpp
#include <cuda_runtime.h>
#include <cuda_bf16.h>
#include <cuda.h>
#include <stdint.h>
#include <type_traits>

namespace {

constexpr int S_ = 2048, D_ = 1024, NSEG = 64, F_ = 3584;

__device__ __align__(1024) uint8_t g_h[S_ * D_ * 2];
__device__ __align__(1024) uint8_t g_att[S_ * 4096 * 2];
__device__ __align__(1024) uint8_t g_x1[S_ * D_ * 2];
__device__ __align__(1024) uint8_t g_h2[S_ * D_ * 2];
__device__ __align__(1024) uint8_t g_act[S_ * F_ * 2];
__device__ __align__(1024) float g_ws[2 * 4 * 16 * 4 * 8192];
__device__ __align__(1024) float g_stat[S_ * 2];
__device__ __align__(1024) float g_uv[F_ * 4];
__device__ __align__(1024) float g_slot[4 * 3 * 8 * 4 * 32 * 4];
__device__ __align__(128) __nv_bfloat16 g_mod[6 * D_];
__device__ __align__(128) float g_modp[3 * 2 * D_];
__device__ __align__(128) uint32_t g_flags[1024];
constexpr int FL_S1 = 0, FL_S2 = 32, FL_MOD = 64, FL_HEAD = 96, FL_EXIT = 128, FL_UV = 160, FL_GO = 192, FL_MODB = 224, FL_ATT = 256, FL_XT = 384, FL_OUT = 512, FL_F1 = 640, FL_SPL = 768;

#define EVF 1
__device__ __forceinline__ uint32_t smem_u32(const void* p) { return (uint32_t)__cvta_generic_to_shared(p); }
__device__ __forceinline__ uint32_t mapa(uint32_t a, uint32_t r) { uint32_t o; asm("mapa.shared::cluster.u32 %0, %1, %2;" : "=r"(o) : "r"(a), "r"(r)); return o; }
__device__ __forceinline__ uint32_t pack2(float a, float b) { uint32_t r; asm("cvt.rn.bf16x2.f32 %0, %1, %2;" : "=r"(r) : "f"(b), "f"(a)); return r; }
__device__ __forceinline__ float bf_lo(uint32_t w) { return __uint_as_float(w << 16); }
__device__ __forceinline__ float bf_hi(uint32_t w) { return __uint_as_float(w & 0xffff0000u); }
__device__ __forceinline__ float ex2(float x) { float y; asm("ex2.approx.ftz.f32 %0, %1;" : "=f"(y) : "f"(x)); return y; }
__device__ __forceinline__ float rcp(float x) { float y; asm("rcp.approx.ftz.f32 %0, %1;" : "=f"(y) : "f"(x)); return y; }
__device__ __forceinline__ uint32_t clk32() { uint64_t c; asm volatile("mov.u64 %0, %%clock64;" : "=l"(c) :: "memory"); return (uint32_t)c; }

__device__ __forceinline__ void mbar_init(uint32_t b, uint32_t n) { asm volatile("mbarrier.init.shared::cta.b64 [%0], %1;" :: "r"(b), "r"(n) : "memory"); }
__device__ __forceinline__ void mbar_arrive(uint32_t b) { asm volatile("mbarrier.arrive.shared::cta.b64 _, [%0];" :: "r"(b) : "memory"); }
__device__ __forceinline__ void mbar_expect(uint32_t b, uint32_t n) { asm volatile("mbarrier.arrive.expect_tx.shared::cta.b64 _, [%0], %1;" :: "r"(b), "r"(n) : "memory"); }
__device__ __forceinline__ uint32_t mbar_try(uint32_t b, uint32_t par) {
  uint32_t ok;
  asm volatile("{\n.reg .pred p;\nmbarrier.try_wait.parity.shared::cta.b64 p, [%1], %2;\nselp.u32 %0, 1, 0, p;\n}" : "=r"(ok) : "r"(b), "r"(par) : "memory");
  return ok;
}
__device__ __forceinline__ void mbar_wait(uint32_t b, uint32_t par) {
  asm volatile("{\n.reg .pred p;\n"
               "LOOP:\n"
               "mbarrier.try_wait.parity.shared::cta.b64 p, [%0], %1;\n"
               "@!p bra.uni LOOP;\n}" :: "r"(b), "r"(par) : "memory");
}
__device__ __forceinline__ void mbar_wait_safe(uint32_t b, uint32_t par) {
  uint32_t c = 0;
  while (!mbar_try(b, par)) { if (++c > 4000000u) __trap(); }
}
__device__ __forceinline__ bool elect_one() {
  uint32_t p;
  asm volatile("{\n.reg .pred p;\nelect.sync _|p, 0xffffffff;\nselp.u32 %0, 1, 0, p;\n}" : "=r"(p));
  return p;
}
__device__ __forceinline__ void sched_fence(uint32_t x, uint32_t y) { asm volatile("{\n.reg .pred p;\nsetp.eq.u32 p, %0, %1;\n@p trap;\n}" :: "r"(x), "r"(y) : "memory"); }
template <class T> __device__ __forceinline__ T opaque32(T x) { asm volatile("" : "+r"(x)); return x; }
template <class T> __device__ __forceinline__ T opaque64(T x) { asm volatile("" : "+l"(x)); return x; }
template <int ID, int N> __device__ __forceinline__ void bar_sync() { asm volatile("bar.sync %0, %1;" :: "n"(ID), "n"(N) : "memory"); }
template <int ID, int N> __device__ __forceinline__ void bar_arrive() { asm volatile("bar.arrive %0, %1;" :: "n"(ID), "n"(N) : "memory"); }
__device__ __forceinline__ void fence_async_smem() { asm volatile("fence.proxy.async.shared::cta;" ::: "memory"); }
__device__ __forceinline__ void fence_async_all() { asm volatile("fence.proxy.async;" ::: "memory"); }
__device__ __forceinline__ void fence_gpu() { asm volatile("fence.acq_rel.gpu;" ::: "memory"); }
__device__ __forceinline__ void red_add_u32(uint32_t* p, uint32_t v) { asm volatile("red.relaxed.gpu.global.add.u32 [%0], %1;" :: "l"(p), "r"(v) : "memory"); }
__device__ __forceinline__ uint32_t ld_acquire(const uint32_t* p) { uint32_t v; asm volatile("ld.acquire.gpu.global.u32 %0, [%1];" : "=r"(v) : "l"(p) : "memory"); return v; }
__device__ __forceinline__ void wait_flag(const uint32_t* p, uint32_t target) {
  uint32_t c = 0;
  while (ld_acquire(p) < target) { if (++c > 20000000u) __trap(); __nanosleep(20); }
}

__device__ __forceinline__ void tma2d(uint32_t dst, const CUtensorMap* m, int c0, int c1, uint32_t bar) {
  asm volatile("cp.async.bulk.tensor.2d.shared::cluster.global.mbarrier::complete_tx::bytes [%0], [%1, {%3, %4}], [%2];"
               :: "r"(dst), "l"(m), "r"(bar), "r"(c0), "r"(c1) : "memory");
}
__device__ __forceinline__ void tma2d_once(uint32_t dst, const CUtensorMap* m, int c0, int c1, uint32_t bar) {
  asm volatile("{\n.reg .b64 pol;\ncreatepolicy.fractional.L2::evict_first.b64 pol, 1.0;\n"
               "cp.async.bulk.tensor.2d.shared::cluster.global.mbarrier::complete_tx::bytes.L2::cache_hint [%0], [%1, {%3, %4}], [%2], pol;\n}"
               :: "r"(dst), "l"(m), "r"(bar), "r"(c0), "r"(c1) : "memory");
}
__device__ __forceinline__ void tma5d(uint32_t dst, const CUtensorMap* m, int n0, int kb, uint32_t bar) {
  asm volatile("cp.async.bulk.tensor.5d.shared::cluster.global.mbarrier::complete_tx::bytes [%0], [%1, {%3, %5, %5, %5, %4}], [%2];"
               :: "r"(dst), "l"(m), "r"(bar), "r"(n0), "r"(2 * kb), "r"(0) : "memory");
}
__device__ __forceinline__ void tma2d_prefetch(const CUtensorMap* m, int c0, int c1) {
  asm volatile("cp.async.bulk.prefetch.tensor.2d.L2.global [%0, {%1, %2}];" :: "l"(m), "r"(c0), "r"(c1) : "memory");
}
__device__ __forceinline__ void bulk_g2s(uint32_t dst, const void* src, uint32_t bytes, uint32_t bar) {
  asm volatile("cp.async.bulk.shared::cluster.global.mbarrier::complete_tx::bytes [%0], [%1], %2, [%3];"
               :: "r"(dst), "l"(src), "r"(bytes), "r"(bar) : "memory");
}
__device__ __forceinline__ void bulk_s2s(uint32_t dst, uint32_t src, uint32_t bytes, uint32_t bar) {
  asm volatile("cp.async.bulk.shared::cluster.shared::cta.mbarrier::complete_tx::bytes [%0], [%1], %2, [%3];"
               :: "r"(dst), "r"(src), "r"(bytes), "r"(bar) : "memory");
}
__device__ __forceinline__ void st_async1(uint32_t dst, uint32_t a, uint32_t bar) {
  asm volatile("st.async.shared::cluster.mbarrier::complete_tx::bytes.b32 [%0], %1, [%2];" :: "r"(dst), "r"(a), "r"(bar) : "memory");
}
__device__ __forceinline__ void st_async2(uint32_t dst, uint32_t a, uint32_t b, uint32_t bar) {
  asm volatile("st.async.shared::cluster.mbarrier::complete_tx::bytes.v2.b32 [%0], {%1, %2}, [%3];" :: "r"(dst), "r"(a), "r"(b), "r"(bar) : "memory");
}
__device__ __forceinline__ void st_async4(uint32_t dst, const uint32_t* r, uint32_t bar) {
  asm volatile("st.async.shared::cluster.mbarrier::complete_tx::bytes.v4.b32 [%0], {%1, %2, %3, %4}, [%5];"
               :: "r"(dst), "r"(r[0]), "r"(r[1]), "r"(r[2]), "r"(r[3]), "r"(bar) : "memory");
}
__device__ __forceinline__ void sts32(uint32_t a, uint32_t v) { asm volatile("st.shared.b32 [%0], %1;" :: "r"(a), "r"(v) : "memory"); }
__device__ __forceinline__ void sts64(uint32_t a, uint32_t x, uint32_t y) { asm volatile("st.shared.v2.b32 [%0], {%1, %2};" :: "r"(a), "r"(x), "r"(y) : "memory"); }
__device__ __forceinline__ void sts128(uint32_t a, uint32_t x, uint32_t y, uint32_t z, uint32_t w) {
  asm volatile("st.shared.v4.b32 [%0], {%1, %2, %3, %4};" :: "r"(a), "r"(x), "r"(y), "r"(z), "r"(w) : "memory");
}
__device__ __forceinline__ void lds128(uint32_t* r, uint32_t a) {
  asm volatile("ld.shared.v4.b32 {%0, %1, %2, %3}, [%4];" : "=r"(r[0]), "=r"(r[1]), "=r"(r[2]), "=r"(r[3]) : "r"(a) : "memory");
}
__device__ __forceinline__ uint32_t lds32(uint32_t a) { uint32_t r; asm volatile("ld.shared.b32 %0, [%1];" : "=r"(r) : "r"(a) : "memory"); return r; }
__device__ __forceinline__ void lds64(uint32_t* r, uint32_t a) {
  asm volatile("ld.shared.v2.b32 {%0, %1}, [%2];" : "=r"(r[0]), "=r"(r[1]) : "r"(a) : "memory");
}
__device__ __forceinline__ void lds128f(float* r, uint32_t a) {
  asm volatile("ld.shared.v4.f32 {%0, %1, %2, %3}, [%4];" : "=f"(r[0]), "=f"(r[1]), "=f"(r[2]), "=f"(r[3]) : "r"(a) : "memory");
}
__device__ __forceinline__ void lds64f(float* r, uint32_t a) {
  asm volatile("ld.shared.v2.f32 {%0, %1}, [%2];" : "=f"(r[0]), "=f"(r[1]) : "r"(a) : "memory");
}
__device__ __forceinline__ void ldsm4(uint32_t* r, uint32_t a) {
  asm volatile("ldmatrix.sync.aligned.m8n8.x4.shared.b16 {%0, %1, %2, %3}, [%4];" : "=r"(r[0]), "=r"(r[1]), "=r"(r[2]), "=r"(r[3]) : "r"(a) : "memory");
}
__device__ __forceinline__ void ldsm4t(uint32_t* r, uint32_t a) {
  asm volatile("ldmatrix.sync.aligned.m8n8.x4.trans.shared.b16 {%0, %1, %2, %3}, [%4];" : "=r"(r[0]), "=r"(r[1]), "=r"(r[2]), "=r"(r[3]) : "r"(a) : "memory");
}
__device__ __forceinline__ void ldsm2(uint32_t* r, uint32_t a) {
  asm volatile("ldmatrix.sync.aligned.m8n8.x2.shared.b16 {%0, %1}, [%2];" : "=r"(r[0]), "=r"(r[1]) : "r"(a) : "memory");
}
__device__ __forceinline__ void stsm4(uint32_t a, const uint32_t* r) {
  asm volatile("stmatrix.sync.aligned.m8n8.x4.shared.b16 [%0], {%1, %2, %3, %4};" :: "r"(a), "r"(r[0]), "r"(r[1]), "r"(r[2]), "r"(r[3]) : "memory");
}
__device__ __forceinline__ uint32_t hadd2(uint32_t a, uint32_t b) { uint32_t t; asm("add.rn.bf16x2 %0, %1, %2;" : "=r"(t) : "r"(a), "r"(b)); return t; }
__device__ __forceinline__ uint32_t hmax2(uint32_t a, uint32_t b) { uint32_t t; asm("max.bf16x2 %0, %1, %2;" : "=r"(t) : "r"(a), "r"(b)); return t; }
__device__ __forceinline__ void ldsm2t(uint32_t* r, uint32_t a) {
  asm volatile("ldmatrix.sync.aligned.m8n8.x2.trans.shared.b16 {%0, %1}, [%2];" : "=r"(r[0]), "=r"(r[1]) : "r"(a) : "memory");
}
__device__ __forceinline__ uint32_t movm(uint32_t x) { uint32_t y; asm volatile("movmatrix.sync.aligned.m8n8.trans.b16 %0, %1;" : "=r"(y) : "r"(x)); return y; }
__device__ __forceinline__ void hmma(float* d, uint32_t a0, uint32_t a1, uint32_t a2, uint32_t a3, uint32_t b0, uint32_t b1) {
  asm volatile("mma.sync.aligned.m16n8k16.row.col.f32.bf16.bf16.f32 {%0,%1,%2,%3}, {%4,%5,%6,%7}, {%8,%9}, {%0,%1,%2,%3};"
               : "+f"(d[0]), "+f"(d[1]), "+f"(d[2]), "+f"(d[3]) : "r"(a0), "r"(a1), "r"(a2), "r"(a3), "r"(b0), "r"(b1));
}
__device__ __forceinline__ void hmma0(float* d, uint32_t a0, uint32_t a1, uint32_t a2, uint32_t a3, uint32_t b0, uint32_t b1) {
  asm volatile("mma.sync.aligned.m16n8k16.row.col.f32.bf16.bf16.f32 {%0,%1,%2,%3}, {%4,%5,%6,%7}, {%8,%9}, {%10,%10,%10,%10};"
               : "=f"(d[0]), "=f"(d[1]), "=f"(d[2]), "=f"(d[3]) : "r"(a0), "r"(a1), "r"(a2), "r"(a3), "r"(b0), "r"(b1), "f"(0.f));
}
__device__ __forceinline__ void hmma_k8(float* d, uint32_t a0, uint32_t a1, uint32_t b0) {
  asm volatile("mma.sync.aligned.m16n8k8.row.col.f32.bf16.bf16.f32 {%0,%1,%2,%3}, {%4,%5}, {%6}, {%0,%1,%2,%3};"
               : "+f"(d[0]), "+f"(d[1]), "+f"(d[2]), "+f"(d[3]) : "r"(a0), "r"(a1), "r"(b0));
}
__host__ __device__ constexpr uint64_t mkdesc(uint32_t addr, uint32_t lbo, uint32_t sbo, uint32_t sw) {
  return (uint64_t)((addr & 0x3FFFF) >> 4) | ((uint64_t)(lbo >> 4) << 16) | ((uint64_t)(sbo >> 4) << 32) | ((uint64_t)sw << 62);
}
#define WG_FENCE() asm volatile("wgmma.fence.sync.aligned;" ::: "memory")
#define WG_COMMIT() asm volatile("wgmma.commit_group.sync.aligned;" ::: "memory")
#define WG_WAIT(n) asm volatile("wgmma.wait_group.sync.aligned " #n ";" ::: "memory")
template <int N> __device__ __forceinline__ void reg_fence(float* d) {
#pragma unroll
  for (int i = 0; i < N; i++) asm volatile("" : "+f"(d[i]) :: "memory");
}
template <int N> __device__ __forceinline__ void zero_regs(float* d) {
#pragma unroll
  for (int i = 0; i < N; i++) asm volatile("mov.b32 %0, 0;" : "=f"(d[i]));
}
template <int SD>
__device__ __forceinline__ void wg_rs32(float* d, uint32_t a0, uint32_t a1, uint32_t a2, uint32_t a3, uint64_t b) {
  asm volatile("wgmma.mma_async.sync.aligned.m64n32k16.f32.bf16.bf16 {%0,%1,%2,%3,%4,%5,%6,%7,%8,%9,%10,%11,%12,%13,%14,%15}, {%16,%17,%18,%19}, %20, %21, 1, 1, 0;"
               : "+f"(d[0]), "+f"(d[1]), "+f"(d[2]), "+f"(d[3]), "+f"(d[4]), "+f"(d[5]), "+f"(d[6]), "+f"(d[7]),
                 "+f"(d[8]), "+f"(d[9]), "+f"(d[10]), "+f"(d[11]), "+f"(d[12]), "+f"(d[13]), "+f"(d[14]), "+f"(d[15])
               : "r"(a0), "r"(a1), "r"(a2), "r"(a3), "l"(b), "n"(SD));
}
template <int TB>
__device__ __forceinline__ void wg_ss40(float* d, uint64_t a, uint64_t b) {
  asm volatile("wgmma.mma_async.sync.aligned.m64n40k16.f32.bf16.bf16 {%0,%1,%2,%3,%4,%5,%6,%7,%8,%9,%10,%11,%12,%13,%14,%15,%16,%17,%18,%19}, %20, %21, 1, 1, 1, 1, %22;"
               : "+f"(d[0]), "+f"(d[1]), "+f"(d[2]), "+f"(d[3]), "+f"(d[4]), "+f"(d[5]), "+f"(d[6]), "+f"(d[7]),
                 "+f"(d[8]), "+f"(d[9]), "+f"(d[10]), "+f"(d[11]), "+f"(d[12]), "+f"(d[13]), "+f"(d[14]), "+f"(d[15]),
                 "+f"(d[16]), "+f"(d[17]), "+f"(d[18]), "+f"(d[19])
               : "l"(a), "l"(b), "n"(TB));
}
__device__ __forceinline__ void wg_ss8(float* d, uint64_t a, uint64_t b) {
  asm volatile("wgmma.mma_async.sync.aligned.m64n8k16.f32.bf16.bf16 {%0,%1,%2,%3}, %4, %5, 1, 1, 1, 1, 0;"
               : "+f"(d[0]), "+f"(d[1]), "+f"(d[2]), "+f"(d[3]) : "l"(a), "l"(b));
}
template <int T>
__device__ __forceinline__ void wg_ss32(float* d, uint64_t a, uint64_t b) {
  asm volatile("wgmma.mma_async.sync.aligned.m64n32k16.f32.bf16.bf16 {%0,%1,%2,%3,%4,%5,%6,%7,%8,%9,%10,%11,%12,%13,%14,%15}, %16, %17, 1, 1, 1, %18, %18;"
               : "+f"(d[0]), "+f"(d[1]), "+f"(d[2]), "+f"(d[3]), "+f"(d[4]), "+f"(d[5]), "+f"(d[6]), "+f"(d[7]),
                 "+f"(d[8]), "+f"(d[9]), "+f"(d[10]), "+f"(d[11]), "+f"(d[12]), "+f"(d[13]), "+f"(d[14]), "+f"(d[15])
               : "l"(a), "l"(b), "n"(T));
}

constexpr int R_TAIL = 0;
constexpr int R_WO = 65536;
constexpr int R_QK = R_WO + 86016;
constexpr int R_P = R_QK + 10240;
constexpr int R_GA = R_P + 6400;
constexpr int R_M2 = R_GA + 16384;
constexpr int R_M1 = R_M2 + 7168;
constexpr int R_GB = R_M1 + 9216;
constexpr int R_VT = R_GB + 16384;
constexpr int R_VM = R_VT + 8192;
constexpr int R_XS = R_VM + 2048;
constexpr int R_OX = R_XS + 1280;
constexpr int R_BAR = R_OX + 2048;
constexpr int R_TRC = R_BAR + 256;
constexpr int R_SMEM = R_TRC + 1024;
constexpr int B_MB = 0, B_XS = 32, B_VM = 40, B_VT = 48, B_TS = 56, B_FA = 64, B_FB = 72, B_TAIL = 80, B_WO = 88, B_STG = 96, B_WM = 128, B_X = 136;
constexpr int NB_A = 1, NB_B = 2, NB_X = 3, NB_C = 4, NB_D = 5, NB_E = 6, NB_F = 7, NB_G = 8, NB_H = 9, NB_S = 10, NB_E2 = 11, NB_P = 12, NB_W0 = 13;

#define FIN 1
#define POLL_DELAY 750
#define POLL_DELAY1 700
#define POLL_STAG 150
#define POLL_K0 20
#define PF1 2
#define PF2 2
#define PF3 2
#define PF4 0
#define CLR_D 2
#define PADN 0
#define PFD 0
#define GO_EARLY 0
#define RF_FIRST 1
#define BX_I 5
#define NCH 4
#define TOP2 0
#define CX_I 13
#define ATT_LATE 0
#define V_FENCE 1
#define SELF_STAS 1
#define Q_FENCE 1
#define ND_K 3
#define TRACE(i)
#define TS(i)

__device__ __forceinline__ int rot_chunk(int c, int rank) {
  int G = c;
  if (c < 9) { G = c + 3 * rank; if (G >= 9) G -= 9; }
  return G;
}
__device__ __forceinline__ int wo_tile(int i, int rank) {
  if (i < 12) return 12 * rank + i;
  const int r = i - 12 + 9 * rank;
  return r < 16 ? 48 + r : 20 + r;
}
__device__ __forceinline__ void load_chunk(uint32_t dst, int seg, int G, uint32_t bar) {
  mbar_expect(bar, 4096);
  bulk_g2s(dst, g_h + (size_t)(seg * 16 + G) * 4096, 4096, bar);
}
__device__ __forceinline__ void load_red(uint32_t* v, const float* p) {
#pragma unroll
  for (int j = 0; j < 2; j++)
    asm volatile("ld.relaxed.gpu.global.v4.u32 {%0, %1, %2, %3}, [%4];"
                 : "=r"(v[4 * j]), "=r"(v[4 * j + 1]), "=r"(v[4 * j + 2]), "=r"(v[4 * j + 3]) : "l"(p + j * 256) : "memory");
}
__device__ __forceinline__ bool red_done(const uint32_t* v) { return __all_sync(0xffffffffu, (v[3] & v[7]) == 0x42000000u); }
__device__ __forceinline__ uint32_t finish_red(uint32_t* v, const float* p) {
  uint32_t tries = 0;
  if (__builtin_expect(!red_done(v), 0)) {
    do { if (++tries > 20000000u) __trap(); load_red(v, p); } while (!red_done(v));
  }
  return tries;
}
__device__ __forceinline__ void exp10(float* sv, const uint32_t* x) {
  constexpr float SC = 0.08838834764831845f * 1.4426950408889634f;
  uint32_t m2 = hmax2(hmax2(hmax2(x[0], x[1]), hmax2(x[2], x[3])), x[4]);
  m2 = hmax2(m2, __shfl_xor_sync(0xffffffffu, m2, 1));
  m2 = hmax2(m2, __shfl_xor_sync(0xffffffffu, m2, 2));
  const float nm = -fmaxf(bf_lo(m2), bf_hi(m2)) * SC;
#pragma unroll
  for (int j = 0; j < 5; j++) { sv[2 * j] = ex2(fmaf(bf_lo(x[j]), SC, nm)); sv[2 * j + 1] = ex2(fmaf(bf_hi(x[j]), SC, nm)); }
}

__device__ __forceinline__ uint32_t arm_size(int w, bool isC) {
  return w == 0 ? (isC ? 1280 : 640) : w == 1 ? (isC ? 0 : 2048) : w == 2 ? (isC ? 0 : 8192) : (isC ? 0 : 1792);
}
struct RDesc { uint64_t tok[32], tail_b[16], tail_a[32]; };

template <int WG>
__device__ __forceinline__ void r_main(const uint32_t (&W)[48][4], const RDesc& dsc, int head, uint32_t rank, int lane_, int w) {
  const uint32_t sb = (rank << 24) + 0x400, bars = sb + R_BAR;
  const uint32_t to1 = rank == 0 ? 2u << 24 : 0u - (1u << 24), to2 = rank == 2 ? 0u - (2u << 24) : 1u << 24;
  const bool isC = rank == 2;
  const int lane = opaque32(lane_), warp = WG * 4 + w;
  const int gl = rot_chunk(4 * (lane & 3) + w, rank);
  const int g0 = __shfl_sync(0xffffffffu, gl, 0), g1 = __shfl_sync(0xffffffffu, gl, 1), g2 = __shfl_sync(0xffffffffu, gl, 2);
  const uint32_t arm_bytes = arm_size(w, isC);

#define L16 opaque32(sb + opaque32(lane) * 16)
#define L8 opaque32(sb + opaque32(lane) * 8)
#define L4 opaque32(sb + opaque32(lane) * 4)
#define LV opaque32(sb + R_VT + ((opaque32(lane) >> 3) & 1) * 512 + (opaque32(lane) >> 4) * 128 + (opaque32(lane) & 7) * 16)
#define SLOT(st) opaque64(slot0 + ((st) & 3) * 12288 + ((st) & 4) * 32)
  float* const slot0 = opaque64(g_slot + (rank * 1024 + warp * 128 + lane) * 4);
  const uint32_t woa = opaque32(sb + R_WO + warp * 12288 + ((lane >> 4) * 8 + (lane & 7)) * 32 + ((((lane >> 3) ^ (lane >> 2)) & 1) << 4));
  const bool has_wo = WG == 0 || isC || w < 3;
  float acc[20];
  uint32_t pk[8] = {0u, 0u, 0u, 0u, 0u, 0u, 0u, 0u};

  auto forward = [&](auto rd, const uint32_t* v, int st, uint32_t tries) {
    constexpr int RD = decltype(rd)::value;
    uint32_t u[6];
#pragma unroll
    for (int j = 0; j < 6; j++) u[j] = movm(v[4 * (j / 3) + j % 3]);
    const bool all3 = RD == 0 || w < 3;
    if (RD == 0) {
      const uint32_t a = L16 + R_M1 + w * 768, a2 = L8 + R_M1 + 512 + w * 768;
      st_async4(a + to1 + 3072, u, bars + to1 + B_MB + 8); st_async2(a2 + to1 + 3072, u[4], u[5], bars + to1 + B_MB + 8);
      sts128(a, u[0], u[1], u[2], u[3]); sts64(a2, u[4], u[5]);
      __syncwarp();
      if (elect_one()) mbar_arrive(bars + B_MB);
      st_async4(a + to2 + 6144, u, bars + to2 + B_MB + 16); st_async2(a2 + to2 + 6144, u[4], u[5], bars + to2 + B_MB + 16);
    } else {
      const uint32_t a = L4 + R_M2 + rank * 2304 + w * 768;
#pragma unroll
      for (int j = 0; j < 6; j++) if (j < 2 || all3) st_async1(a + to1 + j * 128, u[j], bars + to1 + B_MB + 24);
#pragma unroll
      for (int j = 0; j < 6; j++) if (j < 2 || all3) st_async1(a + to2 + j * 128, u[j], bars + to2 + B_MB + 24);
      if (SELF_STAS) {
#pragma unroll
        for (int j = 0; j < 6; j++) if (j < 2 || all3) st_async1(a + j * 128, u[j], bars + B_MB + 24);
      } else {
#pragma unroll
        for (int j = 0; j < 6; j++) if (j < 2 || all3) sts32(a + j * 128, u[j]);
        __syncwarp();
        if (elect_one()) mbar_arrive(bars + B_MB + 24);
      }
    }
  };

  auto send_vt = [&]() {
    if (elect_one()) {
      const uint32_t src = sb + R_VT + warp * 1024;
      bulk_s2s(src + to1, src, 1024, bars + to1 + B_VT);
      bulk_s2s(src + to2, src, 1024, bars + to2 + B_VT);
    }
  };
  auto store_att = [&](int sg) {
    uint32_t* op = reinterpret_cast<uint32_t*>(g_att + (size_t)((sg >> 2) * 64 + head * 2 + rank) * 16384 + (2 * w * 16 + (sg & 3) * 4) * 128) + opaque32(lane);
#pragma unroll
    for (int j = 0; j < 8; j++) op[(j & 1) * 512 + (j >> 1) * 32] = pk[j];
  };

  if (WG == 0) bar_arrive<NB_G, 256>();
#pragma unroll 1
  for (int s = -1; s < NSEG - FIN; s++) {
    const uint32_t par = (s + 1) & 1;
    const uint32_t last = !FIN && s == NSEG - 1;
    TRACE(0);
    {
      float c[NCH][4];
      uint32_t b[3][6];
      const uint32_t ma = L16, m8 = L8;
#pragma unroll
      for (int i = 0; i < 18; i++) {
        if (i < 16) {
          if (i % 4 == 0 && !(i == 4 && TOP2)) mbar_wait(bars + B_MB + (i / 4) * 8, par ^ 1);
          if (i == 0 && TOP2) mbar_wait(bars + B_MB + 8, par ^ 1);
          if (i % 4 == 0) TRACE(1 + i / 4);
          if (i < 12) { lds128(b[i % 3], ma + R_M1 + i * 768); lds64(b[i % 3] + 4, m8 + R_M1 + 512 + i * 768); }
          else { ldsm4(b[i % 3], ma + R_M2 + 4096 + (i - 12) * 768); ldsm2(b[i % 3] + 4, ma + R_M2 + 4096 + 512 + (i - 12) * 768); }
          if (WG == 1 && i == BX_I) {
            bar_sync<NB_G, 256>();
            if (!last && elect_one()) load_chunk(sb + R_GB + w * 4096, s + 1, g0, bars + B_FB);
          }
          if (i == CX_I) {
            if (isC && s >= 0) send_vt();
            if (WG == 1 && ATT_LATE && !isC && s > 0) store_att(s - 1);
          }
          __syncwarp();
        }
        if (i >= 2) {
          const int j = i - 2;
#pragma unroll
          for (int q = 0; q < 3; q++) {
            const uint32_t* f = W[3 * j + q];
            if (3 * j + q < NCH) hmma0(c[3 * j + q], f[0], f[1], f[2], f[3], b[j % 3][2 * q], b[j % 3][2 * q + 1]);
            else hmma(c[(3 * j + q) % NCH], f[0], f[1], f[2], f[3], b[j % 3][2 * q], b[j % 3][2 * q + 1]);
          }
        }
        if (i == 14) zero_regs<16>(acc);
        if (i == 16) mbar_wait(bars + B_FA, last);
      }
#pragma unroll
      for (int j = 0; j < 4; j++) acc[16 + j] = NCH == 3 ? (c[0][j] + c[1][j]) + c[2][j] : (c[0][j] + c[1][j]) + (c[2][j] + c[NCH - 1][j]);
    }
    TRACE(5);
    bar_sync<NB_H, 256>();
    WG_FENCE();
#pragma unroll
    for (int k = 0; k < 16; k++) wg_ss40<0>(acc, dsc.tail_a[WG * 16 + k], dsc.tail_b[k]);
    WG_COMMIT();
    uint32_t vt[4][4];
    {
      const uint32_t a = opaque32(L4 + w * 256 + (isC ? WG * 1024 + R_VM : R_QK + 4096 + WG * 5120));
      const uint32_t qa = L16 + R_QK, xa = opaque32(LV + w * 2048 + (WG == 0 ? 0 : (opaque32(lane) & 8) * 64 + R_QK + 5120 - R_VT));
      const uint32_t d = opaque32(L4 + R_XS + rank * 640 + w * 256);
      if (s == 0) {
        mbar_wait_safe(bars + B_WO, 0);
        if (!GO_EARLY && WG == 1 && head == 0 && rank == 0 && w == 0 && elect_one()) red_add_u32(&g_flags[FL_GO], 1);
      }
      mbar_wait(bars + B_FB, last);
      if (WG == 0) mbar_wait(bars + B_VT, par);
      WG_WAIT(0);
      reg_fence<20>(acc);
      TRACE(6);
      const uint32_t p0 = pack2(acc[16], acc[17]), p1 = pack2(acc[18], acc[19]);
      sts32(a, p0); sts32(a + 128, p1);
      if (isC) {
        st_async1(a + to1, p0, bars + B_VM + to1); st_async1(a + to1 + 128, p1, bars + B_VM + to1);
        st_async1(a + to2, p0, bars + B_VM + to2); st_async1(a + to2 + 128, p1, bars + B_VM + to2);
      }
      if (WG == 0) {
        bar_arrive<NB_A, 256>();
        if (Q_FENCE && !isC) fence_async_smem();
#pragma unroll
        for (int i = 0; i < 4; i++) ldsm4(vt[i], xa + (i >> 1) * 1024 + (i & 1) * 256);
        bar_sync<NB_S, 256>();
      } else {
        bar_sync<NB_A, 256>();
        if (!isC) {
          if (w < 3) {
            uint32_t q[8], k[4][4];
            ldsm4t(q, qa + 4096); ldsm4t(k[0], xa); ldsm4t(k[1], xa + 256);
            ldsm4t(q + 4, qa + 4096 + 512); ldsm4t(k[2], xa + 512); ldsm4t(k[3], xa + 768);
            float x[4], y[4];
            hmma0(x, k[0][0], k[0][1], k[0][2], k[0][3], q[0], q[1]); hmma0(y, k[1][0], k[1][1], k[1][2], k[1][3], q[2], q[3]);
            hmma(x, k[2][0], k[2][1], k[2][2], k[2][3], q[4], q[5]); hmma(y, k[3][0], k[3][1], k[3][2], k[3][3], q[6], q[7]);
            const uint32_t s0 = pack2(x[0] + y[0], x[1] + y[1]), s1 = pack2(x[2] + y[2], x[3] + y[3]);
            st_async1(d + to1, s0, bars + B_XS + to1);
            st_async1(d + to2, s0, bars + B_XS + to2);
            if (w < 2) { st_async1(d + to1 + 128, s1, bars + B_XS + to1); st_async1(d + to2 + 128, s1, bars + B_XS + to2); sts32(d + 128, s1); }
            sts32(d, s0);
          }
        }
        bar_arrive<NB_S, 256>();
      }
    }
    if (WG == 1) {
      if (!last && elect_one()) load_chunk(sb + R_GA + w * 4096, s + 1, g1, bars + B_FA);
      {
        if (w > 0 && elect_one()) mbar_expect(bars + B_MB + 8 * w, w < 3 ? 3072 : SELF_STAS ? 28 * 256 : isC ? 18 * 256 : 19 * 256);
      }
      fence_async_smem();
      bar_sync<NB_B, 256>();
    }
    TRACE(7);
    WG_FENCE();
#pragma unroll
    for (int k = 0; k < 16; k++) wg_rs32<1>(acc, W[k][0], W[k][1], W[k][2], W[k][3], dsc.tok[16 + k]);
    WG_COMMIT();
    uint32_t wa[3][4];
    const uint32_t oxa = L16 + R_OX;
    if (WG == 0) {
      const uint32_t vma = oxa - (R_OX - R_VM) + w * 512, oa = opaque32(L4 + w * 512 + R_OX);
      TRACE(8);
      mbar_wait(bars + B_XS, par);
      TRACE(9);
      float sv[10];
      {
        uint32_t x[10];
        ldsm4t(x, oxa - (R_OX - R_XS)); ldsm4t(x + 4, oxa - (R_OX - R_XS) + 512); ldsm2t(x + 8, oxa - (R_OX - R_XS) + 1024);
        bar_arrive<NB_B, 256>();
#pragma unroll
        for (int j = 0; j < 5; j++) x[j] = hadd2(x[j], x[j + 5]);
        exp10(sv, x);
      }
      WG_WAIT(0);
      bar_arrive<NB_X, 256>();
      mbar_wait(bars + B_VM, par);
      uint32_t vm[4];
      ldsm4(vm, vma);
      uint32_t pb[5];
#pragma unroll
      for (int j = 0; j < 5; j++) pb[j] = pack2(sv[2 * j], sv[2 * j + 1]);
      TRACE(10);
      float o0[4], o1[4], sm[4];
      const uint32_t ONE = 0x3f803f80u;
      hmma0(o0, vt[0][0], vt[0][1], vt[0][2], vt[0][3], pb[0], pb[1]);
      hmma0(o1, vt[2][0], vt[2][1], vt[2][2], vt[2][3], pb[0], pb[1]);
      hmma0(sm, ONE, ONE, ONE, ONE, pb[0], pb[1]);
      hmma(sm, ONE, ONE, ONE, ONE, pb[2], pb[3]);
      hmma(o0, vt[1][0], vt[1][1], vt[1][2], vt[1][3], pb[2], pb[3]);
      hmma(o1, vt[3][0], vt[3][1], vt[3][2], vt[3][3], pb[2], pb[3]);
      hmma_k8(sm, ONE, ONE, pb[4]);
      hmma_k8(o0, vm[0], vm[1], pb[4]);
      hmma_k8(o1, vm[2], vm[3], pb[4]);
#pragma unroll
      for (int i = 0; i < 3; i++) ldsm4t(wa[i], woa + i * 4096);
      __syncwarp();
      const float i0 = rcp(sm[0]), i1 = rcp(sm[1]);
      sts32(oa, pack2(o0[0] * i0, o0[1] * i1)); sts32(oa + 128, pack2(o0[2] * i0, o0[3] * i1));
      sts32(oa + 256, pack2(o1[0] * i0, o1[1] * i1)); sts32(oa + 384, pack2(o1[2] * i0, o1[3] * i1));
      TRACE(11);
      bar_sync<NB_C, 128>();
    } else {
      if (!isC) {
        constexpr uint64_t dQ = mkdesc(0x400 + R_QK, 128, 1024, 0), dK = mkdesc(0x400 + R_QK + 5120, 128, 1024, 0);
        float sc[16];
        zero_regs<16>(sc);
        WG_FENCE();
#pragma unroll
        for (int k = 0; k < 4; k++) wg_ss32<1>(sc, dK + k * 16, dQ + k * 16);
        WG_COMMIT();
        const uint32_t top = rank == 0 ? to2 : to1, e = L4 + R_P + w * 256;
        WG_WAIT(0);
        bar_sync<NB_X, 256>();
        if (!last && elect_one()) load_chunk(sb + R_GB + w * 4096, s + 1, g2, bars + B_FB);
        reg_fence<16>(sc);
        if (w < 3) {
#pragma unroll
          for (int j = 0; j < 8; j++) {
            if ((j & 1) ? (j > 1 && (w == 0 || (w == 1 && j == 7))) : (j >= 4 || w != 1)) {
              const uint32_t t = pack2(sc[2 * j], sc[2 * j + 1]), o = (j >> 1) * 768 + (j & 1) * 128;
              st_async1(e + top + 3072 + o, t, bars + top + B_TS);
              sts32(e + o, t);
            }
          }
          __syncwarp();
          if (elect_one()) mbar_arrive(bars + B_TS);
        }
      } else {
        WG_WAIT(0);
        bar_sync<NB_X, 256>();
        if (!last && elect_one()) load_chunk(sb + R_GB + w * 4096, s + 1, g2, bars + B_FB);
      }
      TRACE(8);
      mbar_wait(bars + B_FA, 1);
      TRACE(11);
    }
    if (has_wo) {
      float* rslot = SLOT(s);
      uint32_t ob[4][4];
      float c[3][4];
      if (WG == 1) {
#pragma unroll
        for (int i = 0; i < 3; i++) ldsm4t(wa[i], woa + i * 4096);
        bar_sync<NB_D, 256>();
      }
      ldsm4t(ob[0], oxa);
      __syncwarp();
#pragma unroll
      for (int k = 0; k < 8; k++) {
        uint32_t nx[3][4];
        if ((k & 1) == 0 && k < 6) { ldsm4t(ob[(k >> 1) + 1], oxa + ((k >> 1) + 1) * 512); __syncwarp(); }
#pragma unroll
        for (int i = 0; i < 3; i++) {
          const uint32_t* o = ob[k >> 1] + (k & 1) * 2;
          if (k < 7) { ldsm4t(nx[i], woa + i * 4096 + (k + 1) * 512); if (i == 2) __syncwarp(); }
          if (k == 0) hmma0(c[i], wa[i][0], wa[i][1], wa[i][2], wa[i][3], o[0], o[1]);
          else hmma(c[i], wa[i][0], wa[i][1], wa[i][2], wa[i][3], o[0], o[1]);
#pragma unroll
          for (int q = 0; q < 4; q++) if (k < 7) wa[i][q] = nx[i][q];
        }
        if (k == ND_K && WG == 0) bar_arrive<NB_D, 256>();
      }
      const float* cv = &c[0][0];
      uint32_t r[6];
#pragma unroll
      for (int j = 0; j < 6; j++) r[j] = pack2(cv[2 * j], cv[2 * j + 1]);
      asm volatile("{\n.reg .pred p;\nsetp.lt.s32 p, %8, 0;\n@p bra.uni SKIP;\n"
                   "red.relaxed.gpu.global.add.noftz.v4.bf16x2 [%0], {%1, %2, %3, %7};\n"
                   "red.relaxed.gpu.global.add.noftz.v4.bf16x2 [%0+1024], {%4, %5, %6, %7};\nSKIP:\n}"
                   :: "l"(rslot), "r"(r[0]), "r"(r[1]), "r"(r[2]), "r"(r[3]), "r"(r[4]), "r"(r[5]), "r"(0x3f800000), "r"(s) : "memory");
    } else {
      bar_arrive<NB_D, 256>();
      if ((s & 3) == 0) {
        fence_gpu();
        if (s > 0 && elect_one()) red_add_u32(&g_flags[FL_ATT + 2 * (s - 4)], 1);
      }
      if (PFD && head < 8 && (PFD > 90 || s + PFD < NSEG) && elect_one())
        asm volatile("cp.async.bulk.prefetch.L2.global [%0], 4096;" :: "l"(g_h + (size_t)((PFD > 90 ? 0 : s + PFD) * 16 + head * 2 + rank) * 4096) : "memory");
      if (rank == 0 || head < 16)
        reinterpret_cast<uint4*>(g_slot)[((s + CLR_D) & 3) * 3072 + ((s + CLR_D) & 4) * 8 + rank * 2048 + head * 64 + opaque32(lane)] = make_uint4(0, 0, 0, 0);
    }
    const uint32_t t_red = clk32();
    uint32_t v[8];
    const float* slot = SLOT(s);
    TRACE(13);
    if (WG == 0) {
      if (!isC) {
        const int ln = opaque32(lane), kg = w - (ln >> 3);
        const uint32_t r16 = sb + R_P + w * 768 + (ln & 7) * 16;
        const uint32_t ta = r16 + (kg >= 0 ? kg * 128 : 640);
        const int dg = (ln >> 2) - 2 * (ln & 3);
        const uint32_t keep = dg > 0 ? 0xffffffffu : dg == 0 ? 0x0000ffffu : 0u;
        mbar_wait(bars + B_TS, par);
        uint32_t x[6], y[4];
        ldsm4t(x, ta); ldsm4t(y, ta + 3072); ldsm2t(x + 4, r16 + 512 + ((ln >> 3) & 1) * 3072);
#pragma unroll
        for (int j = 0; j < 5; j++) x[j] = hadd2(x[j], j < 4 ? y[j] : x[5]);
        x[0] = (x[0] & keep) | (0xff80ff80u & ~keep);
        float sv[10];
        exp10(sv, x);
        float sum = (((sv[0] + sv[1]) + (sv[2] + sv[3])) + ((sv[4] + sv[5]) + (sv[6] + sv[7]))) + (sv[8] + sv[9]);
        sum += __shfl_xor_sync(0xffffffffu, sum, 1);
        sum += __shfl_xor_sync(0xffffffffu, sum, 2);
        const float inv = rcp(sum);
#pragma unroll
        for (int j = 0; j < 5; j++) x[j] = pack2(sv[2 * j] * inv, sv[2 * j + 1] * inv);
        stsm4(r16 + (kg & 3) * 128, x);
        sts32(sb + ln * 4 + w * 768 + R_P + 512, x[4]);
        fence_async_smem();
        bar_arrive<NB_P, 256>();
      }
      while (clk32() - t_red < POLL_DELAY) {}
      load_red(v, slot);
      bar_sync<NB_E, 256>();
    } else {
      mbar_wait(bars + B_FB, 1);
    }
    TRACE(14);
    float ao[16];
    if (WG == 1) zero_regs<16>(ao);
    WG_FENCE();
#pragma unroll
    for (int k = 0; k < 32; k++) {
      if (WG == 0 && k == 16) WG_COMMIT();
      wg_rs32<1>(acc, W[16 + k][0], W[16 + k][1], W[16 + k][2], W[16 + k][3], dsc.tok[k]);
    }
    WG_COMMIT();
    TRACE(12);
    if (WG == 1) {
      if (!isC) {
        constexpr uint64_t dP = mkdesc(0x400 + R_P, 128, 768, 0);
        const uint64_t dV = mkdesc(0x400 + R_VT, 128, 512, 0) + rank * 256, dM = mkdesc(0x400 + R_VM, 0, 128, 0) + rank * 64;
        bar_sync<NB_P, 256>();
        WG_FENCE();
        wg_ss32<0>(ao, dV, dP); wg_ss32<0>(ao, dV + 16, dP + 16); wg_ss32<0>(ao, dM, dP + 32);
        WG_COMMIT();
      }
      bar_arrive<NB_E, 256>();
      if (elect_one()) mbar_expect(bars + B_XS + 8 * w, arm_bytes);
      while (clk32() - t_red < POLL_DELAY1) {}
      load_red(v, slot);
      bar_arrive<NB_W0, 128>();
    } else {
      WG_WAIT(1);
      bar_arrive<NB_F, 256>();
      sched_fence(head, 100);
      v[3] = opaque32(v[3]);
      const uint32_t tries = finish_red(v, slot);
      forward(std::integral_constant<int, 0>(), v, s, tries);
      TRACE(16);
    }
    WG_WAIT(0);
    reg_fence<16>(acc);
    if (WG == 0) bar_arrive<NB_G, 256>();
    TRACE(15);
    {
      uint32_t pq[8];
#pragma unroll
      for (int j = 0; j < 8; j++) pq[j] = pack2(acc[2 * j], acc[2 * j + 1]);
      if (WG == 1) {
        reg_fence<16>(ao);
#pragma unroll
        for (int j = 0; j < 8; j++) pk[j] = pack2(ao[2 * j], ao[2 * j + 1]);
      }
      if (!isC) {
        const uint32_t q = L4 + w * 256 + R_QK + WG * 5120;
#pragma unroll
        for (int j = 0; j < 8; j++) sts32(q + (j >> 1) * 1024 + (j & 1) * 128, pq[j]);
        if (WG == 1 && !ATT_LATE && s >= 0) store_att(s);
      } else {
        const uint32_t a = LV + warp * 1024;
        stsm4(a, pq); stsm4(a + 256, pq + 4);
      }
    }
    TRACE(17);
    if (WG == 1) {
      auto refill = [&]() {
        bar_sync<NB_F, 256>();
        if (s < NSEG - 2 && elect_one()) load_chunk(sb + R_GA + w * 4096, s + 2, 12 + w, bars + B_FA);
      };
      if (RF_FIRST) refill();
      if (has_wo) { v[3] = opaque32(v[3]); const uint32_t tries = finish_red(v, slot); forward(std::integral_constant<int, 1>(), v, s, tries); }
      if (!RF_FIRST) refill();
      TRACE(16);
    }
    if (isC && V_FENCE) { fence_async_smem(); __syncwarp(); }
    TRACE(18);
  }
  {
    constexpr uint32_t par = NSEG & 1;
    if (WG == 1 || isC) {
      float c[NCH][4], m[4];
      uint32_t b[3][6];
      const uint32_t ma = L16, m8 = L8;
#pragma unroll
      for (int i = 0; i < 18; i++) {
        if (i < 16) {
          if (i % 4 == 0) mbar_wait(bars + B_MB + (i / 4) * 8, par ^ 1);
          if (i < 12) { lds128(b[i % 3], ma + R_M1 + i * 768); lds64(b[i % 3] + 4, m8 + R_M1 + 512 + i * 768); }
          else { ldsm4(b[i % 3], ma + R_M2 + 4096 + (i - 12) * 768); ldsm2(b[i % 3] + 4, ma + R_M2 + 4096 + 512 + (i - 12) * 768); }
          if (i == CX_I && isC) send_vt();
          __syncwarp();
        }
        if (i >= 2) {
          const int j = i - 2;
#pragma unroll
          for (int q = 0; q < 3; q++) {
            const uint32_t* f = W[3 * j + q];
            if (3 * j + q < NCH) hmma0(c[3 * j + q], f[0], f[1], f[2], f[3], b[j % 3][2 * q], b[j % 3][2 * q + 1]);
            else hmma(c[(3 * j + q) % NCH], f[0], f[1], f[2], f[3], b[j % 3][2 * q], b[j % 3][2 * q + 1]);
          }
        }
      }
#pragma unroll
      for (int j = 0; j < 4; j++) m[j] = NCH == 3 ? (c[0][j] + c[1][j]) + c[2][j] : (c[0][j] + c[1][j]) + (c[2][j] + c[NCH - 1][j]);
      if (isC) bar_sync<NB_H, 256>();
      WG_FENCE();
#pragma unroll
      for (int k = 0; k < 16; k++) wg_ss8(m, dsc.tail_a[WG * 16 + k], dsc.tail_b[k] + 1024);
      WG_COMMIT();
      const uint32_t a = opaque32(L4 + w * 256 + (isC ? WG * 1024 + R_VM : R_QK + 4096 + WG * 5120));
      WG_WAIT(0);
      reg_fence<4>(m);
      const uint32_t p0 = pack2(m[0], m[1]), p1 = pack2(m[2], m[3]);
      if (isC) {
        st_async1(a + to1, p0, bars + B_VM + to1); st_async1(a + to1 + 128, p1, bars + B_VM + to1);
        st_async1(a + to2, p0, bars + B_VM + to2); st_async1(a + to2 + 128, p1, bars + B_VM + to2);
      } else {
        sts32(a, p0); sts32(a + 128, p1);
      }
    }
    if (WG == 1) bar_sync<NB_G, 256>();
    if (isC) {
      asm volatile("barrier.cluster.arrive.relaxed.aligned;" ::: "memory");
    } else if (WG == 1) {
      constexpr uint64_t dQ = mkdesc(0x400 + R_QK, 128, 1024, 0), dK = mkdesc(0x400 + R_QK + 5120, 128, 1024, 0);
      float sc[16];
      zero_regs<16>(sc);
      fence_async_smem();
      bar_sync<NB_B, 256>();
      WG_FENCE();
#pragma unroll
      for (int k = 0; k < 4; k++) wg_ss32<1>(sc, dK + k * 16, dQ + k * 16);
      WG_COMMIT();
      const uint32_t top = rank == 0 ? to2 : to1, e = L4 + R_P + w * 256;
      WG_WAIT(0);
      reg_fence<16>(sc);
      if (w < 3) {
#pragma unroll
        for (int j = 0; j < 8; j++) {
          if ((j & 1) ? (j > 1 && (w == 0 || (w == 1 && j == 7))) : (j >= 4 || w != 1)) {
            const uint32_t t = pack2(sc[2 * j], sc[2 * j + 1]), o = (j >> 1) * 768 + (j & 1) * 128;
            st_async1(e + top + 3072 + o, t, bars + top + B_TS);
            sts32(e + o, t);
          }
        }
        __syncwarp();
        if (elect_one()) mbar_arrive(bars + B_TS);
      }
      constexpr uint64_t dP = mkdesc(0x400 + R_P, 128, 768, 0);
      const uint64_t dV = mkdesc(0x400 + R_VT, 128, 512, 0) + rank * 256, dM = mkdesc(0x400 + R_VM, 0, 128, 0) + rank * 64;
      float ao[16];
      zero_regs<16>(ao);
      mbar_wait(bars + B_VT, par);
      mbar_wait(bars + B_VM, par);
      asm volatile("barrier.cluster.arrive.relaxed.aligned;" ::: "memory");
      bar_sync<NB_P, 256>();
      WG_FENCE();
      wg_ss32<0>(ao, dV, dP); wg_ss32<0>(ao, dV + 16, dP + 16); wg_ss32<0>(ao, dM, dP + 32);
      WG_COMMIT();
      WG_WAIT(0);
      reg_fence<16>(ao);
#pragma unroll
      for (int j = 0; j < 8; j++) pk[j] = pack2(ao[2 * j], ao[2 * j + 1]);
      store_att(NSEG - 1);
      bar_sync<NB_C, 128>();
      if (w == 0 && elect_one()) { fence_gpu(); red_add_u32(&g_flags[FL_ATT + 8 * 15], 1); }
    } else {
      fence_async_smem();
      bar_arrive<NB_B, 256>();
      const int ln = opaque32(lane), kg = w - (ln >> 3);
      const uint32_t r16 = sb + R_P + w * 768 + (ln & 7) * 16;
      const uint32_t ta = r16 + (kg >= 0 ? kg * 128 : 640);
      const int dg = (ln >> 2) - 2 * (ln & 3);
      const uint32_t keep = dg > 0 ? 0xffffffffu : dg == 0 ? 0x0000ffffu : 0u;
      mbar_wait(bars + B_TS, par);
      asm volatile("barrier.cluster.arrive.relaxed.aligned;" ::: "memory");
      uint32_t x[6], y[4];
      ldsm4t(x, ta); ldsm4t(y, ta + 3072); ldsm2t(x + 4, r16 + 512 + ((ln >> 3) & 1) * 3072);
#pragma unroll
      for (int j = 0; j < 5; j++) x[j] = hadd2(x[j], j < 4 ? y[j] : x[5]);
      x[0] = (x[0] & keep) | (0xff80ff80u & ~keep);
      float sv[10];
      exp10(sv, x);
      float sum = (((sv[0] + sv[1]) + (sv[2] + sv[3])) + ((sv[4] + sv[5]) + (sv[6] + sv[7]))) + (sv[8] + sv[9]);
      sum += __shfl_xor_sync(0xffffffffu, sum, 1);
      sum += __shfl_xor_sync(0xffffffffu, sum, 2);
      const float inv = rcp(sum);
#pragma unroll
      for (int j = 0; j < 5; j++) x[j] = pack2(sv[2 * j] * inv, sv[2 * j + 1] * inv);
      stsm4(r16 + (kg & 3) * 128, x);
      sts32(sb + ln * 4 + w * 768 + R_P + 512, x[4]);
      fence_async_smem();
      bar_arrive<NB_P, 256>();
    }
    asm volatile("barrier.cluster.wait.aligned;" ::: "memory");
  }
#undef L16
#undef L8
#undef L4
#undef SLOT
#undef LV
}

__global__ void __cluster_dims__(3, 1, 1) __launch_bounds__(256, 1)
kernel_R(const __grid_constant__ CUtensorMap tmq, const __grid_constant__ CUtensorMap tmk, const __grid_constant__ CUtensorMap tmv,
         const __grid_constant__ CUtensorMap tmo, const __grid_constant__ CUtensorMap tmm, const __nv_bfloat16* __restrict__ x,
         const __nv_bfloat16* __restrict__ mem0, const __nv_bfloat16* __restrict__ cvec, const __grid_constant__ RDesc dsc) {
  extern __shared__ __align__(1024) uint8_t smem[];
  const uint32_t sb = smem_u32(smem);
  uint32_t rank; asm("mov.u32 %0, %%cluster_ctarank;" : "=r"(rank));
  rank = __shfl_sync(0xffffffffu, rank, 0);
  const int cta = blockIdx.x, head = __shfl_sync(0xffffffffu, cta / 3, 0);
  const int tid = threadIdx.x, lane = tid & 31;
  const int warp = __shfl_sync(0xffffffffu, tid >> 5, 0);
  const int wg = warp >> 2, w = warp & 3;
  const uint32_t bars = sb + R_BAR;
  const CUtensorMap* tmw = rank == 2 ? &tmv : (wg == 0 ? &tmq : &tmk);
  const int fcol = head * 128 + (rank == 2 ? wg * 64 : (int)rank * 64);

  asm volatile("griddepcontrol.launch_dependents;");
  uint32_t W[48][4];
  {
    if (sb != (rank << 24) + 0x400) __trap();
    if (tid == 0) {
      sts64(bars + 248, rank, head);
      mbar_init(bars + B_MB, 4); mbar_init(bars + B_MB + 8, 1); mbar_init(bars + B_MB + 16, 1); mbar_init(bars + B_MB + 24, SELF_STAS ? 1 : rank == 2 ? 5 : 4);
      for (int i = B_XS; i <= B_X; i += 8) mbar_init(bars + i, i == B_FA || i == B_FB || (i == B_TS && rank < 2) ? 4 : 1);
      asm volatile("fence.mbarrier_init.release.cluster;" ::: "memory");
      fence_async_smem();
    }
    __syncthreads();
    asm volatile("barrier.cluster.arrive.relaxed.aligned;" ::: "memory");
    TS(0);
    const int nwm = rank == 0 ? 6 : 5, wm0 = rank == 0 ? 0 : 5 * rank + 1, nrg = cta < 64 ? 3 : 2;
    if (elect_one()) {
      if (warp == 0) { mbar_expect(bars + B_WM, nwm * 8192); mbar_expect(bars + B_X, nrg * 16384); }
      if (warp < nwm) tma2d_once(sb + R_GA + warp * 8192, &tmm, head * 64, (wm0 + warp) * 64, bars + B_WM);
#pragma unroll 1
      for (int r = 0; r < nrg; r++) bulk_g2s(sb + R_TAIL + (r * 8 + warp) * 2064, x + (size_t)((cta + 96 * r) * 8 + warp) * D_, 2048, bars + B_X);
      if (w == 0) mbar_expect(bars + B_STG + wg * 16, 49152);
      if (w < 2) tma2d_once(sb + R_WO + wg * 49152 + w * 8192, tmw, fcol, rot_chunk(w, rank) * 64, bars + B_STG + wg * 16);
    }
    float* scr = reinterpret_cast<float*>(smem + R_VT);
#pragma unroll 1
    for (int i = tid; i < nwm * 64; i += 256) {
      const float c = __bfloat162float(cvec[wm0 * 64 + i]);
      scr[i] = __bfloat162float(__float2bfloat16(c / (1.f + __expf(-c))));
    }
    if (tid < 128) {
      uint32_t e[4] = {0u, 0u, 0u, 0u};
      if (cta >= 72 && (tid & 32)) {
        const uint16_t* mp = reinterpret_cast<const uint16_t*>(mem0) + 2 * (lane & 3) * D_ + (lane >> 2);
#pragma unroll
        for (int q = 0; q < 3; q++) {
          const int n = 3 * (tid >> 6) + q, col = wo_tile(3 * (cta & 7) + (n >> 1), (cta - 72) >> 3) * 16 + 8 * (n & 1);
          e[q] = mp[col] | (uint32_t)mp[col + D_] << 16;
        }
        e[3] = 0x42000000u;
      }
      reinterpret_cast<uint4*>(g_slot)[cta * 128 + tid] = make_uint4(e[0], e[1], e[2], e[3]);
    }
    __syncthreads();
    TS(1);
    mbar_wait_safe(bars + B_WM, 0);
    if (elect_one()) tma2d_once(sb + R_WO + wg * 49152 + (2 + w) * 8192, tmw, fcol, rot_chunk(2 + w, rank) * 64, bars + B_STG + wg * 16);
    {
      float a[8];
#pragma unroll
      for (int j = 0; j < 8; j++) a[j] = 0.f;
#pragma unroll 2
      for (int i = 0; i < 2 * nwm; i++) {
        uint32_t u[4];
        lds128(u, sb + R_GA + i * 4096 + tid * 16);
        const float sc = scr[i * 32 + (tid >> 3)];
#pragma unroll
        for (int j = 0; j < 4; j++) { a[2 * j] += sc * bf_lo(u[j]); a[2 * j + 1] += sc * bf_hi(u[j]); }
      }
#pragma unroll
      for (int j = 0; j < 8; j++) { a[j] += __shfl_xor_sync(0xffffffffu, a[j], 8); a[j] += __shfl_xor_sync(0xffffffffu, a[j], 16); }
      if (lane < 8) {
        sts128(sb + R_VT + 1536 + warp * 256 + lane * 32, __float_as_uint(a[0]), __float_as_uint(a[1]), __float_as_uint(a[2]), __float_as_uint(a[3]));
        sts128(sb + R_VT + 1552 + warp * 256 + lane * 32, __float_as_uint(a[4]), __float_as_uint(a[5]), __float_as_uint(a[6]), __float_as_uint(a[7]));
      }
    }
    __syncthreads();
    TS(2);
    if (warp == 7) {
      float t0 = 0.f, t1 = 0.f;
#pragma unroll
      for (int i = 0; i < 8; i++) { float t[2]; lds64f(t, sb + R_VT + 1536 + i * 256 + lane * 8); t0 += t[0]; t1 += t[1]; }
      reinterpret_cast<float2*>(g_modp + rank * 2048 + head * 64)[lane] = make_float2(t0, t1);
      fence_gpu();
      __syncwarp();
      if (lane == 0) red_add_u32(&g_flags[FL_S1], 1);
      __syncwarp();
    }
    mbar_wait_safe(bars + B_X, 0);
#pragma unroll 1
    for (int r = 0; r < nrg; r++) {
      float f[32];
#pragma unroll
      for (int i = 0; i < 4; i++) {
        uint32_t u[4];
        lds128(u, sb + R_TAIL + (r * 8 + warp) * 2064 + i * 512 + lane * 16);
#pragma unroll
        for (int j = 0; j < 4; j++) { f[8 * i + 2 * j] = bf_lo(u[j]); f[8 * i + 2 * j + 1] = bf_hi(u[j]); }
      }
      float t = 0.f;
#pragma unroll
      for (int i = 0; i < 32; i++) t += f[i];
#pragma unroll
      for (int o = 1; o < 32; o <<= 1) t += __shfl_xor_sync(0xffffffffu, t, o);
      const float mean = t * (1.f / D_);
      t = 0.f;
#pragma unroll
      for (int i = 0; i < 32; i++) t = fmaf(f[i] - mean, f[i] - mean, t);
#pragma unroll
      for (int o = 1; o < 32; o <<= 1) t += __shfl_xor_sync(0xffffffffu, t, o);
      const float rstd = rsqrtf(t * (1.f / D_) + 1e-5f);
      if (lane == 0) sts64(sb + R_VT + 3584 + (r * 8 + warp) * 8, __float_as_uint(rstd), __float_as_uint(-mean * rstd));
    }
    TS(3);
    if (w < PF1 && elect_one()) tma2d_prefetch(tmw, fcol, rot_chunk(6 + w, rank) * 64);
    if (tid == 0) wait_flag(&g_flags[FL_S1], 96);
    __syncthreads();
    TS(4);
    {
      float4 p[6];
#pragma unroll
      for (int i = 0; i < 6; i++) p[i] = __ldcg(reinterpret_cast<const float4*>(g_modp + (i >> 1) * 2048) + 2 * tid + (i & 1));
      if (w < PF2 && elect_one()) tma2d_prefetch(tmw, fcol, (9 + w) * 64);
      sts128(sb + R_VT + 5120 + tid * 16, pack2(p[0].x + p[2].x + p[4].x, p[0].y + p[2].y + p[4].y), pack2(p[0].z + p[2].z + p[4].z, p[0].w + p[2].w + p[4].w),
             pack2(p[1].x + p[3].x + p[5].x, p[1].y + p[3].y + p[5].y), pack2(p[1].z + p[3].z + p[5].z, p[1].w + p[3].w + p[5].w));
    }
    __syncthreads();
#pragma unroll 2
    for (int it = 0; it < 4 * nrg; it++) {
      const int r = it >> 2, rg = cta + 96 * r, c = 16 * warp + (lane >> 3) + 4 * (it & 3);
      uint32_t a[4], b[4], u[4], o[4];
      float t[2];
      lds128(u, sb + R_TAIL + (r * 8 + (lane & 7)) * 2064 + c * 16);
      lds128(a, sb + R_VT + 5120 + c * 16); lds128(b, sb + R_VT + 7168 + c * 16);
      lds64f(t, sb + R_VT + 3584 + (r * 8 + (lane & 7)) * 8);
#pragma unroll
      for (int j = 0; j < 4; j++)
        o[j] = pack2(fmaf(fmaf(bf_lo(u[j]), t[0], t[1]), 1.f + bf_lo(b[j]), bf_lo(a[j])), fmaf(fmaf(bf_hi(u[j]), t[0], t[1]), 1.f + bf_hi(b[j]), bf_hi(a[j])));
      *reinterpret_cast<uint4*>(g_h + (size_t)(rg >> 2) * 65536 + (lane & 7) * 16 + (c & 7) * 128 +
                                (c < 96 ? (c >> 3) * 4096 + (rg & 3) * 1024 : 49152 + (rg & 3) * 4096 + ((c >> 3) - 12) * 1024)) =
          make_uint4(o[0], o[1], o[2], o[3]);
    }
    TS(5);
    __syncthreads();
    TS(6);
    if (w < PF3 && elect_one()) tma2d_once(sb + R_TAIL + warp * 8192, tmw, fcol, 768 + w * 64, bars + B_TAIL);
    if (warp == 3 && lane == 0) { fence_gpu(); red_add_u32(&g_flags[FL_S2], 1); }
    __syncwarp();

    const uint32_t a0 = opaque32(sb + R_WO + wg * 49152 + ((lane >> 4) * 8 + (lane & 7)) * 128 + (((2 * w + ((lane >> 3) & 1)) ^ (lane & 7)) << 4));
    mbar_wait_safe(bars + B_STG + wg * 16, 0);
    TS(7);
#pragma unroll
    for (int i = 0; i < 24; i++) ldsm4t(W[i], a0 + i * 2048);
    if (tid == 0) wait_flag(&g_flags[FL_S2], 96);
    __syncthreads();
    asm volatile("fence.proxy.async.global;" ::: "memory");
    if (elect_one()) {
      if (wg == 0) load_chunk(sb + R_GA + w * 4096, 0, 12 + w, bars + B_FA);
      if (w == 0) mbar_expect(bars + B_STG + wg * 16 + 8, 49152);
#pragma unroll 1
      for (int c = w; c < 6; c += 4) tma2d_once(sb + R_WO + wg * 49152 + c * 8192, tmw, fcol, rot_chunk(6 + c, rank) * 64, bars + B_STG + wg * 16 + 8);
      if (warp == 0) mbar_expect(bars + B_TAIL, 65536);
      if (w >= PF3) tma2d_once(sb + R_TAIL + warp * 8192, tmw, fcol, 768 + w * 64, bars + B_TAIL);
      if (wg == 1) mbar_expect(bars + B_XS + 8 * w, w == 2 ? 0 : arm_size(w, rank == 2));
#pragma unroll 1
      for (int i = warp; i < PF4; i += 8) tma2d_prefetch(&tmo, 16 * wo_tile(i, rank), head * 128);
    }
    TS(8);
    mbar_wait_safe(bars + B_STG + wg * 16 + 8, 0);
    TS(9);
#pragma unroll
    for (int i = 0; i < 24; i++) ldsm4t(W[24 + i], a0 + i * 2048);
    __syncthreads();
    if (elect_one()) {
      const int n = rank == 2 ? 22 : 21;
      if (warp == 0) mbar_expect(bars + B_WO, n * 4096);
#pragma unroll 1
      for (int i = warp; i < n; i += 8) tma2d(sb + R_WO + i * 4096, &tmo, 16 * wo_tile(i, rank), head * 128, bars + B_WO);
    }
    sts32(sb + R_P + warp * 768 + 640 + lane * 4, wg == 0 ? 0u : 0xff80ff80u);
    mbar_wait_safe(bars + B_TAIL, 0);
    if (GO_EARLY && cta == GO_EARLY - 1 && tid == 0) red_add_u32(&g_flags[FL_GO], 1);
    asm volatile("barrier.cluster.wait.aligned;\nbarrier.cluster.arrive.relaxed.aligned;\nbarrier.cluster.wait.aligned;" ::: "memory");
  }
  uint32_t rh[2];
  lds64(rh, bars + 248);
  rh[0] = __shfl_sync(0xffffffffu, rh[0], 0); rh[1] = __shfl_sync(0xffffffffu, rh[1], 0);
  if (wg == 0) r_main<0>(W, dsc, rh[1], rh[0], lane, w);
  else r_main<1>(W, dsc, rh[1], rh[0], lane, w);
}

template <int TA, bool FIRST> __device__ __forceinline__ void wg_ss256(float* d, uint64_t a, uint64_t b) {
  if (FIRST)
    asm volatile("wgmma.mma_async.sync.aligned.m64n256k16.f32.bf16.bf16 {%0,%1,%2,%3,%4,%5,%6,%7,%8,%9,%10,%11,%12,%13,%14,%15,%16,%17,%18,%19,%20,%21,%22,%23,%24,%25,%26,%27,%28,%29,%30,%31,%32,%33,%34,%35,%36,%37,%38,%39,%40,%41,%42,%43,%44,%45,%46,%47,%48,%49,%50,%51,%52,%53,%54,%55,%56,%57,%58,%59,%60,%61,%62,%63,%64,%65,%66,%67,%68,%69,%70,%71,%72,%73,%74,%75,%76,%77,%78,%79,%80,%81,%82,%83,%84,%85,%86,%87,%88,%89,%90,%91,%92,%93,%94,%95,%96,%97,%98,%99,%100,%101,%102,%103,%104,%105,%106,%107,%108,%109,%110,%111,%112,%113,%114,%115,%116,%117,%118,%119,%120,%121,%122,%123,%124,%125,%126,%127}, %128, %129, 0, 1, 1, %130, 1;"
               : "=f"(d[0]), "=f"(d[1]), "=f"(d[2]), "=f"(d[3]), "=f"(d[4]), "=f"(d[5]), "=f"(d[6]), "=f"(d[7]),
                 "=f"(d[8]), "=f"(d[9]), "=f"(d[10]), "=f"(d[11]), "=f"(d[12]), "=f"(d[13]), "=f"(d[14]), "=f"(d[15]),
                 "=f"(d[16]), "=f"(d[17]), "=f"(d[18]), "=f"(d[19]), "=f"(d[20]), "=f"(d[21]), "=f"(d[22]), "=f"(d[23]),
                 "=f"(d[24]), "=f"(d[25]), "=f"(d[26]), "=f"(d[27]), "=f"(d[28]), "=f"(d[29]), "=f"(d[30]), "=f"(d[31]),
                 "=f"(d[32]), "=f"(d[33]), "=f"(d[34]), "=f"(d[35]), "=f"(d[36]), "=f"(d[37]), "=f"(d[38]), "=f"(d[39]),
                 "=f"(d[40]), "=f"(d[41]), "=f"(d[42]), "=f"(d[43]), "=f"(d[44]), "=f"(d[45]), "=f"(d[46]), "=f"(d[47]),
                 "=f"(d[48]), "=f"(d[49]), "=f"(d[50]), "=f"(d[51]), "=f"(d[52]), "=f"(d[53]), "=f"(d[54]), "=f"(d[55]),
                 "=f"(d[56]), "=f"(d[57]), "=f"(d[58]), "=f"(d[59]), "=f"(d[60]), "=f"(d[61]), "=f"(d[62]), "=f"(d[63]),
                 "=f"(d[64]), "=f"(d[65]), "=f"(d[66]), "=f"(d[67]), "=f"(d[68]), "=f"(d[69]), "=f"(d[70]), "=f"(d[71]),
                 "=f"(d[72]), "=f"(d[73]), "=f"(d[74]), "=f"(d[75]), "=f"(d[76]), "=f"(d[77]), "=f"(d[78]), "=f"(d[79]),
                 "=f"(d[80]), "=f"(d[81]), "=f"(d[82]), "=f"(d[83]), "=f"(d[84]), "=f"(d[85]), "=f"(d[86]), "=f"(d[87]),
                 "=f"(d[88]), "=f"(d[89]), "=f"(d[90]), "=f"(d[91]), "=f"(d[92]), "=f"(d[93]), "=f"(d[94]), "=f"(d[95]),
                 "=f"(d[96]), "=f"(d[97]), "=f"(d[98]), "=f"(d[99]), "=f"(d[100]), "=f"(d[101]), "=f"(d[102]), "=f"(d[103]),
                 "=f"(d[104]), "=f"(d[105]), "=f"(d[106]), "=f"(d[107]), "=f"(d[108]), "=f"(d[109]), "=f"(d[110]), "=f"(d[111]),
                 "=f"(d[112]), "=f"(d[113]), "=f"(d[114]), "=f"(d[115]), "=f"(d[116]), "=f"(d[117]), "=f"(d[118]), "=f"(d[119]),
                 "=f"(d[120]), "=f"(d[121]), "=f"(d[122]), "=f"(d[123]), "=f"(d[124]), "=f"(d[125]), "=f"(d[126]), "=f"(d[127])
               : "l"(a), "l"(b), "n"(TA));
  else
    asm volatile("wgmma.mma_async.sync.aligned.m64n256k16.f32.bf16.bf16 {%0,%1,%2,%3,%4,%5,%6,%7,%8,%9,%10,%11,%12,%13,%14,%15,%16,%17,%18,%19,%20,%21,%22,%23,%24,%25,%26,%27,%28,%29,%30,%31,%32,%33,%34,%35,%36,%37,%38,%39,%40,%41,%42,%43,%44,%45,%46,%47,%48,%49,%50,%51,%52,%53,%54,%55,%56,%57,%58,%59,%60,%61,%62,%63,%64,%65,%66,%67,%68,%69,%70,%71,%72,%73,%74,%75,%76,%77,%78,%79,%80,%81,%82,%83,%84,%85,%86,%87,%88,%89,%90,%91,%92,%93,%94,%95,%96,%97,%98,%99,%100,%101,%102,%103,%104,%105,%106,%107,%108,%109,%110,%111,%112,%113,%114,%115,%116,%117,%118,%119,%120,%121,%122,%123,%124,%125,%126,%127}, %128, %129, 1, 1, 1, %130, 1;"
               : "+f"(d[0]), "+f"(d[1]), "+f"(d[2]), "+f"(d[3]), "+f"(d[4]), "+f"(d[5]), "+f"(d[6]), "+f"(d[7]),
                 "+f"(d[8]), "+f"(d[9]), "+f"(d[10]), "+f"(d[11]), "+f"(d[12]), "+f"(d[13]), "+f"(d[14]), "+f"(d[15]),
                 "+f"(d[16]), "+f"(d[17]), "+f"(d[18]), "+f"(d[19]), "+f"(d[20]), "+f"(d[21]), "+f"(d[22]), "+f"(d[23]),
                 "+f"(d[24]), "+f"(d[25]), "+f"(d[26]), "+f"(d[27]), "+f"(d[28]), "+f"(d[29]), "+f"(d[30]), "+f"(d[31]),
                 "+f"(d[32]), "+f"(d[33]), "+f"(d[34]), "+f"(d[35]), "+f"(d[36]), "+f"(d[37]), "+f"(d[38]), "+f"(d[39]),
                 "+f"(d[40]), "+f"(d[41]), "+f"(d[42]), "+f"(d[43]), "+f"(d[44]), "+f"(d[45]), "+f"(d[46]), "+f"(d[47]),
                 "+f"(d[48]), "+f"(d[49]), "+f"(d[50]), "+f"(d[51]), "+f"(d[52]), "+f"(d[53]), "+f"(d[54]), "+f"(d[55]),
                 "+f"(d[56]), "+f"(d[57]), "+f"(d[58]), "+f"(d[59]), "+f"(d[60]), "+f"(d[61]), "+f"(d[62]), "+f"(d[63]),
                 "+f"(d[64]), "+f"(d[65]), "+f"(d[66]), "+f"(d[67]), "+f"(d[68]), "+f"(d[69]), "+f"(d[70]), "+f"(d[71]),
                 "+f"(d[72]), "+f"(d[73]), "+f"(d[74]), "+f"(d[75]), "+f"(d[76]), "+f"(d[77]), "+f"(d[78]), "+f"(d[79]),
                 "+f"(d[80]), "+f"(d[81]), "+f"(d[82]), "+f"(d[83]), "+f"(d[84]), "+f"(d[85]), "+f"(d[86]), "+f"(d[87]),
                 "+f"(d[88]), "+f"(d[89]), "+f"(d[90]), "+f"(d[91]), "+f"(d[92]), "+f"(d[93]), "+f"(d[94]), "+f"(d[95]),
                 "+f"(d[96]), "+f"(d[97]), "+f"(d[98]), "+f"(d[99]), "+f"(d[100]), "+f"(d[101]), "+f"(d[102]), "+f"(d[103]),
                 "+f"(d[104]), "+f"(d[105]), "+f"(d[106]), "+f"(d[107]), "+f"(d[108]), "+f"(d[109]), "+f"(d[110]), "+f"(d[111]),
                 "+f"(d[112]), "+f"(d[113]), "+f"(d[114]), "+f"(d[115]), "+f"(d[116]), "+f"(d[117]), "+f"(d[118]), "+f"(d[119]),
                 "+f"(d[120]), "+f"(d[121]), "+f"(d[122]), "+f"(d[123]), "+f"(d[124]), "+f"(d[125]), "+f"(d[126]), "+f"(d[127])
               : "l"(a), "l"(b), "n"(TA));
}
template <int TA, bool FIRST> __device__ __forceinline__ void wg_ss128(float* d, uint64_t a, uint64_t b) {
  if (FIRST)
    asm volatile("wgmma.mma_async.sync.aligned.m64n128k16.f32.bf16.bf16 {%0,%1,%2,%3,%4,%5,%6,%7,%8,%9,%10,%11,%12,%13,%14,%15,%16,%17,%18,%19,%20,%21,%22,%23,%24,%25,%26,%27,%28,%29,%30,%31,%32,%33,%34,%35,%36,%37,%38,%39,%40,%41,%42,%43,%44,%45,%46,%47,%48,%49,%50,%51,%52,%53,%54,%55,%56,%57,%58,%59,%60,%61,%62,%63}, %64, %65, 0, 1, 1, %66, 1;"
               : "=f"(d[0]), "=f"(d[1]), "=f"(d[2]), "=f"(d[3]), "=f"(d[4]), "=f"(d[5]), "=f"(d[6]), "=f"(d[7]),
                 "=f"(d[8]), "=f"(d[9]), "=f"(d[10]), "=f"(d[11]), "=f"(d[12]), "=f"(d[13]), "=f"(d[14]), "=f"(d[15]),
                 "=f"(d[16]), "=f"(d[17]), "=f"(d[18]), "=f"(d[19]), "=f"(d[20]), "=f"(d[21]), "=f"(d[22]), "=f"(d[23]),
                 "=f"(d[24]), "=f"(d[25]), "=f"(d[26]), "=f"(d[27]), "=f"(d[28]), "=f"(d[29]), "=f"(d[30]), "=f"(d[31]),
                 "=f"(d[32]), "=f"(d[33]), "=f"(d[34]), "=f"(d[35]), "=f"(d[36]), "=f"(d[37]), "=f"(d[38]), "=f"(d[39]),
                 "=f"(d[40]), "=f"(d[41]), "=f"(d[42]), "=f"(d[43]), "=f"(d[44]), "=f"(d[45]), "=f"(d[46]), "=f"(d[47]),
                 "=f"(d[48]), "=f"(d[49]), "=f"(d[50]), "=f"(d[51]), "=f"(d[52]), "=f"(d[53]), "=f"(d[54]), "=f"(d[55]),
                 "=f"(d[56]), "=f"(d[57]), "=f"(d[58]), "=f"(d[59]), "=f"(d[60]), "=f"(d[61]), "=f"(d[62]), "=f"(d[63])
               : "l"(a), "l"(b), "n"(TA));
  else
    asm volatile("wgmma.mma_async.sync.aligned.m64n128k16.f32.bf16.bf16 {%0,%1,%2,%3,%4,%5,%6,%7,%8,%9,%10,%11,%12,%13,%14,%15,%16,%17,%18,%19,%20,%21,%22,%23,%24,%25,%26,%27,%28,%29,%30,%31,%32,%33,%34,%35,%36,%37,%38,%39,%40,%41,%42,%43,%44,%45,%46,%47,%48,%49,%50,%51,%52,%53,%54,%55,%56,%57,%58,%59,%60,%61,%62,%63}, %64, %65, 1, 1, 1, %66, 1;"
               : "+f"(d[0]), "+f"(d[1]), "+f"(d[2]), "+f"(d[3]), "+f"(d[4]), "+f"(d[5]), "+f"(d[6]), "+f"(d[7]),
                 "+f"(d[8]), "+f"(d[9]), "+f"(d[10]), "+f"(d[11]), "+f"(d[12]), "+f"(d[13]), "+f"(d[14]), "+f"(d[15]),
                 "+f"(d[16]), "+f"(d[17]), "+f"(d[18]), "+f"(d[19]), "+f"(d[20]), "+f"(d[21]), "+f"(d[22]), "+f"(d[23]),
                 "+f"(d[24]), "+f"(d[25]), "+f"(d[26]), "+f"(d[27]), "+f"(d[28]), "+f"(d[29]), "+f"(d[30]), "+f"(d[31]),
                 "+f"(d[32]), "+f"(d[33]), "+f"(d[34]), "+f"(d[35]), "+f"(d[36]), "+f"(d[37]), "+f"(d[38]), "+f"(d[39]),
                 "+f"(d[40]), "+f"(d[41]), "+f"(d[42]), "+f"(d[43]), "+f"(d[44]), "+f"(d[45]), "+f"(d[46]), "+f"(d[47]),
                 "+f"(d[48]), "+f"(d[49]), "+f"(d[50]), "+f"(d[51]), "+f"(d[52]), "+f"(d[53]), "+f"(d[54]), "+f"(d[55]),
                 "+f"(d[56]), "+f"(d[57]), "+f"(d[58]), "+f"(d[59]), "+f"(d[60]), "+f"(d[61]), "+f"(d[62]), "+f"(d[63])
               : "l"(a), "l"(b), "n"(TA));
}
template <int TA, bool FIRST> __device__ __forceinline__ void wg_ss64(float* d, uint64_t a, uint64_t b) {
  if (FIRST)
    asm volatile("wgmma.mma_async.sync.aligned.m64n64k16.f32.bf16.bf16 {%0,%1,%2,%3,%4,%5,%6,%7,%8,%9,%10,%11,%12,%13,%14,%15,%16,%17,%18,%19,%20,%21,%22,%23,%24,%25,%26,%27,%28,%29,%30,%31}, %32, %33, 0, 1, 1, %34, 1;"
               : "=f"(d[0]), "=f"(d[1]), "=f"(d[2]), "=f"(d[3]), "=f"(d[4]), "=f"(d[5]), "=f"(d[6]), "=f"(d[7]),
                 "=f"(d[8]), "=f"(d[9]), "=f"(d[10]), "=f"(d[11]), "=f"(d[12]), "=f"(d[13]), "=f"(d[14]), "=f"(d[15]),
                 "=f"(d[16]), "=f"(d[17]), "=f"(d[18]), "=f"(d[19]), "=f"(d[20]), "=f"(d[21]), "=f"(d[22]), "=f"(d[23]),
                 "=f"(d[24]), "=f"(d[25]), "=f"(d[26]), "=f"(d[27]), "=f"(d[28]), "=f"(d[29]), "=f"(d[30]), "=f"(d[31])
               : "l"(a), "l"(b), "n"(TA));
  else
    asm volatile("wgmma.mma_async.sync.aligned.m64n64k16.f32.bf16.bf16 {%0,%1,%2,%3,%4,%5,%6,%7,%8,%9,%10,%11,%12,%13,%14,%15,%16,%17,%18,%19,%20,%21,%22,%23,%24,%25,%26,%27,%28,%29,%30,%31}, %32, %33, 1, 1, 1, %34, 1;"
               : "+f"(d[0]), "+f"(d[1]), "+f"(d[2]), "+f"(d[3]), "+f"(d[4]), "+f"(d[5]), "+f"(d[6]), "+f"(d[7]),
                 "+f"(d[8]), "+f"(d[9]), "+f"(d[10]), "+f"(d[11]), "+f"(d[12]), "+f"(d[13]), "+f"(d[14]), "+f"(d[15]),
                 "+f"(d[16]), "+f"(d[17]), "+f"(d[18]), "+f"(d[19]), "+f"(d[20]), "+f"(d[21]), "+f"(d[22]), "+f"(d[23]),
                 "+f"(d[24]), "+f"(d[25]), "+f"(d[26]), "+f"(d[27]), "+f"(d[28]), "+f"(d[29]), "+f"(d[30]), "+f"(d[31])
               : "l"(a), "l"(b), "n"(TA));
}

constexpr int H_STAGE = 49152, H_NST = 4;
constexpr int H_STG = H_NST * H_STAGE;
constexpr int H_VEC = H_STG + 16384;
constexpr int H_BAR = H_VEC + 6144;
constexpr int H_SMEM = H_BAR + 256;
constexpr int HB_FULL = 0, HB_EMPTY = 32, HB_IFULL = 64, HB_IEMPTY = 80, HB_ITEM = 96, HB_INC = 104;
enum { IT_END = 0, IT_MOD = 1, IT_XT = 2, IT_OUT = 3, IT_UV = 4, IT_F1 = 5, IT_F2 = 6 };
constexpr int MAX_ITEMS = 1400;
#define D_MOD 4
#define D_UV 2
#define R_LATE 1
#define CH_FENCE 1
#define CH_FENCE1 1
#define N_UV1 20
#define B_EARLY 1
#define XT_GO 0
struct HList { uint32_t n; uint32_t it[MAX_ITEMS]; };
#define HT(i)

__device__ __forceinline__ uint32_t tile_lane(int warp, int lane) { return warp * 1024 + (lane >> 2) * 64 + (((lane & 3) ^ (lane >> 3)) << 4); }
__device__ __forceinline__ constexpr uint32_t tile_off(int c, int h) { return (c >> 1) * 16384 + (c & 1) * 8192 + h * 512; }

__device__ __forceinline__ void h_pass(uint32_t sb, int nst, uint32_t& st, uint32_t& ph, bool leader) {
#pragma unroll 1
  for (int i = 0; i < nst; i++) {
    mbar_wait(sb + H_BAR + HB_FULL + st * 8, ph);
    if (leader) mbar_arrive(sb + H_BAR + HB_EMPTY + st * 8);
    if (++st == H_NST) { st = 0; ph ^= 1; }
  }
}
template <int BN, int TA, class PRE>
__device__ __forceinline__ void h_mainloop(float* acc, uint32_t sb, int nst, uint32_t& st, uint32_t& ph, int wg, bool leader, bool fixed_a, PRE pre) {
  constexpr int KS = BN == 64 ? 8 : 4;
  constexpr uint32_t BOFF = BN == 64 ? 32768 : 16384;
  const uint64_t da0 = fixed_a ? mkdesc(sb + H_STG, 16, 0, 2) : TA ? mkdesc(sb + wg * 1024, 2048, 128, 0) : mkdesc(sb + wg * 4096, 16, 512, 2);
  const uint64_t db0 = mkdesc(sb + BOFF, 8192, 1024, 1);
  const uint32_t kh = fixed_a ? 32 : 512;
  uint32_t prev = 0;
  auto stage = [&](auto first, int i) {
    constexpr bool FIRST = decltype(first)::value;
    mbar_wait(sb + H_BAR + HB_FULL + st * 8, ph);
    if (FIRST) HT(1);
    const uint64_t da = da0 + (fixed_a ? i * 64 : st * (H_STAGE >> 4)), db = db0 + st * (H_STAGE >> 4);
    WG_FENCE();
#pragma unroll
    for (int k = 0; k < KS; k++) {
      const uint64_t a = da + (k >> 2) * 1024 + (TA ? (k & 3) * 256 : ((k >> 1) & 1) * kh + (k & 1) * 2), b = db + k * 128;
      if (FIRST && k == 0) { if (BN == 256) wg_ss256<TA, true>(acc, a, b); else if (BN == 128) wg_ss128<TA, true>(acc, a, b); else wg_ss64<TA, true>(acc, a, b); }
      else { if (BN == 256) wg_ss256<TA, false>(acc, a, b); else if (BN == 128) wg_ss128<TA, false>(acc, a, b); else wg_ss64<TA, false>(acc, a, b); }
    }
    WG_COMMIT();
  };
  stage(std::true_type(), 0);
  pre();
  prev = st;
  if (++st == H_NST) { st = 0; ph ^= 1; }
#pragma unroll 1
  for (int i = 1; i < nst; i++) {
    stage(std::false_type(), i);
    WG_WAIT(1);
    if (leader) mbar_arrive(sb + H_BAR + HB_EMPTY + prev * 8);
    prev = st;
    if (++st == H_NST) { st = 0; ph ^= 1; }
  }
  WG_WAIT(0);
  HT(2);
  reg_fence<BN / 2>(acc);
  if (leader) mbar_arrive(sb + H_BAR + HB_EMPTY + prev * 8);
}

template <int BN, bool FINAL>
__device__ __forceinline__ bool h_residual(uint32_t sb, uint32_t va, int mt, int n0, uint32_t& st, uint32_t& ph, int warp, int lane, __nv_bfloat16* out,
                                           int part = 0, int lgp = 0) {
  const size_t toff = (size_t)(mt * 16 + (n0 >> 6)) * 16384 + tile_lane(warp, lane);
  uint4 r[BN / 16];
  auto load_r = [&]() {
#pragma unroll
    for (int i = 0; i < BN / 16; i++) r[i] = __ldcg(reinterpret_cast<const uint4*>(g_x1 + toff + tile_off(i >> 1, i & 1)));
  };
  if (!R_LATE) load_r();
  float acc[BN / 2];
  h_mainloop<BN, FINAL ? 0 : 1>(acc, sb, ((FINAL ? 56 : 64) / (BN == 64 ? 2 : 1)) >> lgp, st, ph, warp >> 2, (warp & 3) == 0 && lane == 0, false,
                                [&]() { if (R_LATE) load_r(); });
  if (BN == 64 && lgp > 0) {
    const int tile = (FINAL * 4 + (mt & 3)) * 16 + (n0 >> 6);
    float4* ws = reinterpret_cast<float4*>(g_ws) + (size_t)tile * 8192 + warp * 32 + lane;
#pragma unroll
    for (int i = 0; i < 8; i++) ws[part * 2048 + i * 256] = make_float4(acc[4 * i], acc[4 * i + 1], acc[4 * i + 2], acc[4 * i + 3]);
    bar_sync<1, 256>();
    if (warp == 0 && lane == 0) { fence_gpu(); const uint32_t t = atomicAdd(&g_flags[FL_SPL + tile], 1); fence_gpu(); sts32(sb + H_BAR + HB_INC + 8, t); }
    bar_sync<1, 256>();
    if (lds32(sb + H_BAR + HB_INC + 8) != (1u << lgp) - 1) return false;
#pragma unroll 1
    for (int p = 1; p < (1 << lgp); p++) {
      float4 o[8];
#pragma unroll
      for (int i = 0; i < 8; i++) o[i] = __ldcg(ws + (part ^ p) * 2048 + i * 256);
#pragma unroll
      for (int i = 0; i < 8; i++) { acc[4 * i] += o[i].x; acc[4 * i + 1] += o[i].y; acc[4 * i + 2] += o[i].z; acc[4 * i + 3] += o[i].w; }
    }
  }
  float sm[4] = {0.f, 0.f, 0.f, 0.f};
  const uint32_t stg = sb + H_STG + warp * 2048;
#pragma unroll
  for (int c = 0; c < BN / 32; c++) {
    uint32_t y[2][4] = {{r[2 * c].x, r[2 * c].y, r[2 * c].z, r[2 * c].w}, {r[2 * c + 1].x, r[2 * c + 1].y, r[2 * c + 1].z, r[2 * c + 1].w}}, z[2][4];
#pragma unroll
    for (int j = 0; j < 4; j++) {
      const uint32_t gt = lds32(va + c * 64 + j * 16 + (lane & 3) * 4);
      const uint32_t cb = FINAL ? 0 : lds32(va + 512 + c * 64 + j * 16 + (lane & 3) * 4);
#pragma unroll
      for (int h = 0; h < 2; h++) {
        const float* a = acc + c * 16 + j * 4 + h * 2;
        y[h][j] = pack2(fmaf(bf_lo(gt), a[0], bf_lo(y[h][j])), fmaf(bf_hi(gt), a[1], bf_hi(y[h][j])));
        if (!FINAL) {
          const float p = bf_lo(y[h][j]), q = bf_hi(y[h][j]);
          sm[2 * h] += p + q;
          sm[2 * h + 1] = fmaf(p, p, fmaf(q, q, sm[2 * h + 1]));
          z[h][j] = pack2(fmaf(p, bf_lo(cb), p), fmaf(q, bf_hi(cb), q));
        }
      }
    }
    if (!FINAL) {
#pragma unroll
      for (int h = 0; h < 2; h++) {
        const size_t o = toff + tile_off(c, h);
        *reinterpret_cast<uint4*>(g_x1 + o) = make_uint4(y[h][0], y[h][1], y[h][2], y[h][3]);
        *reinterpret_cast<uint4*>(g_h2 + o) = make_uint4(z[h][0], z[h][1], z[h][2], z[h][3]);
      }
    } else {
#pragma unroll
      for (int h = 0; h < 2; h++) stsm4(stg + (h * 8 + (lane & 7)) * 128 + ((((c & 1) * 4 + (lane >> 3)) ^ (lane & 7)) << 4), y[h]);
      if (c & 1) {
        __syncwarp();
#pragma unroll
        for (int j = 0; j < 4; j++) {
          const int rr = 4 * j + (lane >> 3);
          uint32_t v[4];
          lds128(v, stg + rr * 128 + (((lane & 7) ^ (rr & 7)) << 4));
          *reinterpret_cast<uint4*>(out + (size_t)(mt * 128 + warp * 16 + rr) * D_ + n0 + (c >> 1) * 64 + (lane & 7) * 8) = make_uint4(v[0], v[1], v[2], v[3]);
        }
        __syncwarp();
      }
    }
    if (CH_FENCE && c + 1 < BN / 32) sched_fence(lane, 100);
  }
  if (!FINAL) {
#pragma unroll
    for (int j = 0; j < 4; j++) { sm[j] += __shfl_xor_sync(0xffffffffu, sm[j], 1); sm[j] += __shfl_xor_sync(0xffffffffu, sm[j], 2); }
    const int t = lane & 3;
    const float sv = t == 0 ? sm[0] : t == 1 ? sm[1] : t == 2 ? sm[2] : sm[3];
    asm volatile("red.relaxed.gpu.global.add.f32 [%0], %1;" :: "l"(g_stat + (mt * 128 + warp * 16 + (t >> 1) * 8 + (lane >> 2)) * 2 + (t & 1)), "f"(sv) : "memory");
  }
  return true;
}

__device__ __forceinline__ float silu_mul(float hg, float u) {
  float t; asm("tanh.approx.f32 %0, %1;" : "=f"(t) : "f"(hg));
  const float h = hg * u;
  return fmaf(h, t, h);
}

template <int BN>
__device__ __forceinline__ void h_swiglu(const float* acc, uint32_t va, int mt, int kb0, int warp, int lane) {
  uint8_t* ap = g_act + (size_t)(mt * 56 + kb0) * 16384 + tile_lane(warp, lane);
  float rs[2], nm[2], rh[2];
#pragma unroll
  for (int h = 0; h < 2; h++) {
    float t[2];
    lds64f(t, va + 2048 + (warp * 16 + h * 8 + (lane >> 2)) * 8);
    const float mean = t[0] * (1.f / D_);
    rs[h] = rsqrtf(fmaxf(t[1] * (1.f / D_) - mean * mean, 0.f) + 1e-5f);
    nm[h] = -mean * rs[h];
    rh[h] = 0.5f * rs[h];
  }
#pragma unroll
  for (int c = 0; c < BN / 64; c++) {
    uint32_t y[2][4];
#pragma unroll
    for (int j = 0; j < 4; j++) {
      const float* g = acc + 16 * c + 4 * j; const float* u = g + BN / 4;
      float p[4], q[4], o[4];
      lds128f(p, va + (4 * c + j) * 128 + (lane & 3) * 32); lds128f(q, va + (4 * c + j) * 128 + (lane & 3) * 32 + 16);
#pragma unroll
      for (int e = 0; e < 4; e++)
        o[e] = silu_mul(fmaf(rh[e >> 1], g[e], fmaf(nm[e >> 1], p[e & 1], p[2 + (e & 1)])), fmaf(rs[e >> 1], u[e], fmaf(nm[e >> 1], q[e & 1], q[2 + (e & 1)])));
      y[0][j] = pack2(o[0], o[1]); y[1][j] = pack2(o[2], o[3]);
    }
#pragma unroll
    for (int h = 0; h < 2; h++)
      *reinterpret_cast<uint4*>(ap + tile_off(c, h)) = make_uint4(y[h][0], y[h][1], y[h][2], y[h][3]);
    if (CH_FENCE1 && c + 1 < BN / 64) sched_fence(lane, 100);
  }
}

__global__ void __launch_bounds__(384, 1)
kernel_H(const __grid_constant__ CUtensorMap tmo, const __grid_constant__ CUtensorMap tm1, const __grid_constant__ CUtensorMap tm3,
         const __grid_constant__ CUtensorMap tm2, const __grid_constant__ CUtensorMap tmm, const __nv_bfloat16* __restrict__ x,
         const __nv_bfloat16* __restrict__ cvec, __nv_bfloat16* __restrict__ out, const __grid_constant__ HList list) {
  extern __shared__ __align__(1024) uint8_t smem[];
  constexpr uint32_t sb = 0x400, bars = sb + H_BAR;
  const int tid = threadIdx.x, lane = tid & 31;
  const int warp = __shfl_sync(0xffffffffu, tid >> 5, 0);
  if (tid == 0) {
    if (smem_u32(smem) != sb) __trap();
    for (int i = 0; i < H_NST; i++) { mbar_init(bars + HB_FULL + i * 8, 1); mbar_init(bars + HB_EMPTY + i * 8, 2); }
    for (int i = 0; i < 2; i++) { mbar_init(bars + HB_IFULL + i * 8, 1); mbar_init(bars + HB_IEMPTY + i * 8, 3); }
    fence_async_smem();
  }
  __syncthreads();
  if (warp >= 8) {
    asm volatile("setmaxnreg.dec.sync.aligned.u32 40;");
    if (warp == 8) {
      uint32_t st = 0, ph = 1;
#pragma unroll 1
      for (uint32_t n = 0;; n++) {
        uint32_t q = 0;
        if (lane == 0) q = atomicAdd(&g_flags[FL_HEAD], 1);
        q = __shfl_sync(0xffffffffu, q, 0);
        const uint32_t it = q < list.n ? list.it[q] : 0;
        const int type = it & 7, mt = (it >> 3) & 15, idx = (it >> 7) & 63, sz = (it >> 13) & 3, part = (it >> 15) & 3, lgp = (it >> 17) & 3;
        int f = FL_GO; uint32_t target = 0;
        if (type == IT_OUT) { f = lane == 0 ? FL_ATT + 8 * mt : lane == 1 ? FL_XT + 8 * mt : FL_MOD; target = lane == 0 ? 64 : lane == 1 ? 2 : 12; }
        else if (type == IT_F1) { f = lane == 0 ? FL_OUT + 8 * mt : FL_UV; target = lane == 0 ? 16 : 28; }
        else if (type == IT_F2) { f = lane == 0 ? FL_F1 + 8 * mt : FL_MODB; target = lane == 0 ? 56 : 4; }
        else if (type == IT_UV) { f = FL_MOD; target = 12; }
        else if (type == IT_MOD || (XT_GO && type == IT_XT)) target = 1;
        const bool has_a = type == IT_OUT || type >= IT_F1;
        auto publish = [&]() {
          mbar_wait(bars + HB_IEMPTY + (n & 1) * 8, ((n >> 1) & 1) ^ 1);
          if (elect_one()) {
            sts32(bars + HB_ITEM + (n & 1) * 4, it | (q << 19));
            mbar_arrive(bars + HB_IFULL + (n & 1) * 8);
          }
        };
        if (B_EARLY && has_a) publish();
        bool late = false;
        if (lane < 2 && (lane == 0 || type == IT_OUT)) wait_flag(&g_flags[f], target);
        else if (lane == 2) late = ld_acquire(&g_flags[f]) < target;
        late = __shfl_sync(0xffffffffu, late, 2);
        asm volatile("fence.proxy.async.global;" ::: "memory");
        if (!(B_EARLY && has_a)) publish();
        if (type == IT_END) break;
        if (type != IT_XT) {
          const uint8_t* ap = type == IT_OUT ? g_att + (size_t)mt * 64 * 16384 : type == IT_F1 ? g_h2 + (size_t)mt * 16 * 16384 : g_act + (size_t)mt * 56 * 16384;
          const int nkb = (type == IT_OUT ? 64 : type == IT_F2 ? 56 : 16) >> lgp;
          const uint32_t abytes = has_a ? (sz == 2 ? 32768 : 16384) : 0, bytes = (sz == 0 ? 32768 : 16384) + abytes;
          const int dk = sz == 2 ? 1 : 0;
#pragma unroll 1
          for (int kb = part * nkb; kb < (part + 1) * nkb; kb += 1 + dk) {
            const uint32_t d = sb + st * H_STAGE, fb = bars + HB_FULL + st * 8;
            mbar_wait(bars + HB_EMPTY + st * 8, ph);
            if (has_a && kb + 1 + dk >= (part + 1) * nkb) {
              if (late) {
                if (lane == 2) wait_flag(&g_flags[f], target);
                __syncwarp();
                asm volatile("fence.proxy.async.global;" ::: "memory");
              }
              if (elect_one()) {
                const bool f1 = type == IT_F1;
                const int c0 = f1 ? idx * (128 >> sz) : idx * (256 >> sz);
                const uint32_t v = sb + H_VEC + (n & 1) * 3072;
                const uint32_t n0 = (f1 ? 2048 : 512) >> sz, n1 = f1 ? 1024 : n0;
                asm volatile("mbarrier.expect_tx.relaxed.cta.shared::cta.b64 [%0], %1;" :: "r"(fb), "r"(n0 + n1) : "memory");
                bulk_g2s(v, f1 ? (const void*)(g_uv + c0 * 4) : (const void*)(g_mod + (type == IT_OUT ? 2 : 5) * D_ + c0), n0, fb);
                bulk_g2s(v + (f1 ? 2048 : 512), f1 ? (const void*)(g_stat + mt * 256) : (const void*)(g_mod + 4 * D_ + c0), n1, fb);
              }
            }
            if (elect_one()) {
              mbar_expect(fb, bytes);
              if (has_a) bulk_g2s(d, ap + (size_t)kb * 16384, abytes, fb);
            }
            if (++st == H_NST) { st = 0; ph ^= 1; }
          }
        }
      }
    } else if (warp >= 10) {
      const int hb = warp - 10;
      uint32_t st = 0, ph = 1;
#pragma unroll 1
      for (uint32_t n = 0;; n++) {
        mbar_wait(bars + HB_IFULL + (n & 1) * 8, (n >> 1) & 1);
        const uint32_t it = __shfl_sync(0xffffffffu, lds32(bars + HB_ITEM + (n & 1) * 4), 0);
        const int type = it & 7, idx = (it >> 7) & 63, sz = (it >> 13) & 3, part = (it >> 15) & 3, lgp = (it >> 17) & 3;
        if (type == IT_END) break;
        if (elect_one()) mbar_arrive(bars + HB_IEMPTY + (n & 1) * 8);
        if (type == IT_XT) continue;
        const bool ffn1 = type == IT_F1 || type == IT_UV;
        const int nkb = (type == IT_OUT ? 64 : type == IT_F2 ? 56 : 16) >> lgp;
        const CUtensorMap* tb = type == IT_OUT ? &tmo : ffn1 ? &tm1 : type == IT_F2 ? &tm2 : &tmm;
        const CUtensorMap* tc = ffn1 ? &tm3 : tb;
        const int c0 = ffn1 ? idx * (128 >> sz) : idx * (256 >> sz) + (type == IT_MOD ? 2048 : 0), c2 = ffn1 ? c0 : c0 + 128;
        const int dk = sz == 2 ? 1 : 0;
        const CUtensorMap* t0 = hb == 1 && sz == 1 ? tc : tb;
        const int ca = hb == 0 || sz == 2 || (sz == 1 && ffn1) ? c0 : c0 + 64;
        const uint32_t off = (sz == 2 ? 32768 : 16384) + hb * 8192;
        const uint32_t cold = type == IT_MOD ? D_MOD : type == IT_UV ? D_UV : H_NST;
#pragma unroll 1
        for (int kb = part * nkb; kb < (part + 1) * nkb; kb += 1 + dk) {
          const uint32_t d = sb + st * H_STAGE + off, fb = bars + HB_FULL + st * 8;
          mbar_wait(bars + HB_EMPTY + st * 8, ph);
          if (cold < H_NST) mbar_wait(bars + HB_FULL + ((st - cold) & 3) * 8, st >= cold ? ph ^ 1 : ph);
          if (elect_one()) {
            tma5d(d, t0, ca, kb + hb * dk, fb);
            if (sz == 0) tma5d(d + 16384, tc, c2 + hb * 64, kb, fb);
          }
          if (++st == H_NST) { st = 0; ph ^= 1; }
        }
      }
    } else if (warp == 9) {
#pragma unroll 1
      for (uint32_t n = 0;; n++) {
        mbar_wait(bars + HB_IFULL + (n & 1) * 8, (n >> 1) & 1);
        const uint32_t itq = lds32(bars + HB_ITEM + (n & 1) * 4);
        const int type = itq & 7, mt = (itq >> 3) & 15;
        if (type == IT_END) break;
        if (n & 1) bar_sync<3, 288>(); else bar_sync<2, 288>();
        if (lane == 0) {
          const uint32_t inc = lds32(bars + HB_INC + (n & 1) * 4);
          mbar_arrive(bars + HB_IEMPTY + (n & 1) * 8);
          if (inc) {
            fence_gpu();
            red_add_u32(&g_flags[type == IT_MOD ? (((itq >> 7) & 63) < 12 ? FL_MOD : FL_MODB) : type == IT_UV ? FL_UV : (type == IT_XT ? FL_XT : type == IT_OUT ? FL_OUT : FL_F1) + 8 * mt], inc);
          }
        }
        __syncwarp();
      }
      asm volatile("griddepcontrol.wait;" ::: "memory");
      uint32_t k = 0;
      if (lane == 0) { fence_gpu(); k = atomicAdd(&g_flags[FL_EXIT], 1); }
      k = __shfl_sync(0xffffffffu, k, 0);
      if (k == gridDim.x - 1) {
        fence_gpu();
        for (int i = lane; i < 1024; i += 32) g_flags[i] = 0;
      }
    }
  } else {
    asm volatile("setmaxnreg.inc.sync.aligned.u32 232;");
    const int wg = warp >> 2;
    const bool leader = (tid & 127) == 0;
    uint32_t st = 0, ph = 0;
#pragma unroll 1
    for (uint32_t n = 0;; n++) {
      mbar_wait(bars + HB_IFULL + (n & 1) * 8, (n >> 1) & 1);
      const uint32_t itq = __shfl_sync(0xffffffffu, lds32(bars + HB_ITEM + (n & 1) * 4), 0);
      const int type = itq & 7, mt = (itq >> 3) & 15, idx = (itq >> 7) & 63, sz = (itq >> 13) & 3, part = (itq >> 15) & 3, lgp = (itq >> 17) & 3;
      uint32_t inc = type == IT_OUT ? 4 >> sz : type == IT_F1 ? 2 >> sz : type != IT_F2;
      if (type == IT_END) break;
      HT(0);
      const uint32_t va = sb + H_VEC + (n & 1) * 3072;
      if (type == IT_OUT) {
        if (sz == 0) h_residual<256, false>(sb, va, mt, idx * 256, st, ph, warp, lane, out);
        else if (sz == 1) h_residual<128, false>(sb, va, mt, idx * 128, st, ph, warp, lane, out);
        else inc = h_residual<64, false>(sb, va, mt, idx * 64, st, ph, warp, lane, out, part, lgp);
      } else if (type == IT_F2) {
        if (sz == 0) h_residual<256, true>(sb, va, mt, idx * 256, st, ph, warp, lane, out);
        else if (sz == 1) h_residual<128, true>(sb, va, mt, idx * 128, st, ph, warp, lane, out);
        else h_residual<64, true>(sb, va, mt, idx * 64, st, ph, warp, lane, out, part, lgp);
      } else if (type == IT_XT) {
        const int rg = idx * 8 + warp;
        const uint32_t* xp = reinterpret_cast<const uint32_t*>(x + (size_t)(mt * 128 + rg * 8 + (lane >> 2)) * D_) + (lane & 3);
        uint8_t* tp = g_x1 + (size_t)mt * 262144 + rg * 512 + tile_lane(0, lane);
        if (lane < 16) g_stat[(mt * 128 + rg * 8) * 2 + lane] = 0.f;
#pragma unroll 1
        for (int b = 0; b < 2; b++) {
          uint32_t v[64];
#pragma unroll
          for (int i = 0; i < 64; i++) v[i] = __ldg(xp + 256 * b + 4 * i);
#pragma unroll
          for (int i = 0; i < 16; i++)
            *reinterpret_cast<uint4*>(tp + tile_off(16 * b + i, 0)) = make_uint4(v[4 * i], v[4 * i + 1], v[4 * i + 2], v[4 * i + 3]);
        }
      } else if (sz == 1) {
        float acc[64];
        h_mainloop<128, 0>(acc, sb, 16, st, ph, wg, leader, false, []() {});
        h_swiglu<128>(acc, va, mt, idx, warp, lane);
      } else {
        if (type != IT_F1) {
          bar_sync<1, 256>();
          for (int i = tid; i < D_; i += 256) {
            __nv_bfloat16* p = reinterpret_cast<__nv_bfloat16*>(smem + H_STG + (i >> 5) * 512 + ((i >> 1) & 3) * 16) + ((i >> 3) & 3) * 2 + (i & 1);
            if (type == IT_UV) {
              p[0] = __float2bfloat16(1.f); p[32] = __ldcg(g_mod + 4 * D_ + i); p[64 + ((i & 2) ? -8 : 8)] = __ldcg(g_mod + 3 * D_ + i);
            }
            else { const float c = __bfloat162float(cvec[i]); p[0] = __float2bfloat16(c / (1.f + __expf(-c))); }
          }
          fence_async_smem();
          bar_sync<1, 256>();
        }
        if (type != IT_F1 && wg == 1) {
          h_pass(sb, 16, st, ph, leader);
        } else {
          float acc[128];
          h_mainloop<256, 0>(acc, sb, 16, st, ph, wg, leader, type != IT_F1, []() {});
          if (type == IT_F1) {
            h_swiglu<256>(acc, va, mt, idx * 2, warp, lane);
          } else if (warp == 0) {
#pragma unroll
            for (int j = 0; j < 32; j++) {
              if (type == IT_MOD) {
                if (lane < 4) reinterpret_cast<uint32_t*>(g_mod + 2048 + idx * 256)[j * 4 + lane] = pack2(acc[4 * j], acc[4 * j + 1]);
              } else {
                const float a = acc[4 * j] + __shfl_down_sync(0xffffffffu, acc[4 * j], 4), b = acc[4 * j + 1] + __shfl_down_sync(0xffffffffu, acc[4 * j + 1], 4);
                float2* up = reinterpret_cast<float2*>(g_uv + idx * 512 + ((j & 15) * 4 + (lane & 3)) * 8 + (j >> 4) * 4);
                const float sc = j < 16 ? 0.5f : 1.f;
                if (lane < 4) up[0] = make_float2(sc * a, sc * b);
                else if ((lane >> 2) == 2) up[1] = make_float2(sc * acc[4 * j], sc * acc[4 * j + 1]);
              }
            }
          }
        }
      }
      if (tid == 0) sts32(bars + HB_INC + (n & 1) * 4, inc);
      if (n & 1) bar_arrive<3, 288>(); else bar_arrive<2, 288>();
    }
  }
}

const uint32_t h_items[] = {
  2, 130, 10, 138, 18, 146, 26, 154, 34, 162, 42, 170, 50, 178, 58, 186, 66, 194, 74, 202, 82, 210, 90, 218,
  98, 226, 106, 234, 114, 242, 122, 250, 1, 129, 257, 385, 513, 641, 769, 897, 1025, 1153, 1281, 1409, 4, 132, 260, 388,
  516, 644, 772, 900, 1028, 1156, 1284, 1412, 1540, 1668, 1796, 1924, 2052, 2180, 2308, 16387, 2436, 16515, 16643, 16771, 16899, 17027, 17155, 17283,
  17411, 17539, 17667, 17795, 17923, 18051, 18179, 18307, 2564, 2692, 2820, 2948, 3076, 3204, 3332, 1537, 3460, 1665, 1793, 1921, 16395, 16523, 16651, 16779,
  16907, 17035, 17163, 17291, 17419, 17547, 17675, 17803, 17931, 18059, 18187, 18315, 8211, 8339, 8467, 8595, 8723, 5, 133, 261, 389, 517, 645, 773,
  901, 1029, 1157, 1285, 1413, 1541, 1669, 1797, 1925, 2053, 2181, 2309, 2437, 8851, 8979, 9107, 2565, 2693, 2821, 2949, 3077, 3205, 3333, 3461,
  13, 141, 269, 781, 909, 1037, 1165, 1293, 1421, 1549, 1677, 1805, 1933, 2061, 2189, 2317, 2445, 397, 8219, 525, 8347, 653, 8475, 2573,
  2701, 2829, 8603, 2957, 3085, 8731, 3213, 3341, 17691, 3469, 8198, 8326, 8454, 8582, 17819, 2837, 8710, 8838, 17947, 8966, 18075, 9094, 3093, 18203,
  21, 3221, 18331, 16419, 3349, 16547, 16675, 3477, 16803, 1173, 16931, 1301, 17059, 1429, 2965, 1557, 17187, 1685, 17315, 2197, 17443, 1813, 17571, 2325,
  17699, 1941, 149, 2453, 277, 2069, 405, 2581, 533, 2709, 661, 29, 789, 157, 917, 285, 1045, 413, 17827, 541, 17955, 669, 18083, 797,
  18211, 925, 18339, 1053, 14, 1181, 142, 1309, 270, 1437, 398, 1565, 1693, 1821, 8235, 8363, 8491, 8619, 8747, 8875, 1949, 9003, 9131, 2077,
  2205, 2333, 3229, 2461, 3357, 2589, 3485, 2717, 8243, 2845, 8371, 2973, 8499, 3101, 8627, 8755, 8883, 9011, 9139, 37, 165, 293, 421, 549,
  677, 805, 933, 1061, 1189, 1317, 1445, 1573, 1701, 1829, 1957, 8251, 8379, 8507, 8635, 8763, 8891, 9019, 9147, 2085, 2213, 2341, 2469, 2597,
  2725, 2853, 2981, 3109, 3237, 3365, 3493, 45, 173, 301, 429, 557, 685, 813, 941, 1069, 1453, 1197, 1581, 1325, 9027, 1709, 1837, 1965,
  8259, 8387, 8515, 8643, 8771, 8899, 693, 9155, 2093, 2221, 2349, 2477, 2605, 2733, 2861, 2989, 3117, 3245, 9163, 2101, 2229, 3373, 3501, 53,
  181, 309, 437, 565, 821, 949, 1077, 1205, 1333, 1461, 1589, 1717, 1845, 1973, 8267, 8395, 8523, 8651, 8779, 8907, 9035, 2357, 2485, 2613,
  2741, 2869, 2997, 3125, 3253, 3381, 3509, 61, 189, 317, 445, 573, 701, 829, 957, 1085, 1213, 1341, 1469, 1597, 1725, 2493, 8275, 1853,
  8403, 1981, 8531, 2109, 8659, 2237, 8787, 2365, 8915, 9043, 9171, 2621, 2749, 2877, 3005, 3133, 3261, 3389, 3517, 1733, 69, 453, 197, 1861,
  325, 581, 709, 837, 1477, 965, 1605, 1093, 1989, 10565, 10693, 12357, 12485, 10821, 10949, 12869, 12997, 2245, 2501, 8283, 8411, 8539, 2629, 8667,
  2757, 8795, 2885, 8923, 9179, 3269, 3397, 1229, 3525, 10061, 77, 10189, 205, 333, 461, 589, 10829, 717, 10957, 845, 1101, 3013, 9051, 3141,
  11085, 11213, 11341, 11469, 11597, 11725, 11853, 11981, 12109, 12237, 8675, 8291, 8803, 8419, 8931, 8547, 9059, 341, 3277, 85, 22, 469, 3405, 597,
  3533, 725, 853, 981, 1109, 1237, 1365, 1493, 9187, 12365, 12493, 12621, 12749, 13901, 14029, 2381, 2509, 3021, 213, 2637, 3149, 2765, 1621, 1749,
  1877, 2005, 2133, 2261, 8427, 8299, 2389, 8555, 2517, 8683, 2645, 8811, 2773, 8939, 2901, 9067, 3029, 9195, 150, 278, 406, 30, 158, 430,
  286, 414, 38, 46, 166, 174, 294, 302, 422, 54, 182, 310, 438, 8307, 8435, 8563, 8691, 8819, 8947, 9075, 9203, 278651, 311419, 344187,
  376955, 278779, 311547, 344315, 377083, 180987, 312315, 148347, 345083, 181115, 148731, 181499, 148859, 3157, 62, 148987, 149243, 278907, 3285, 190, 318, 149115, 311675, 148219,
  344443, 279547, 181627, 1757, 377211, 181755, 181883, 1885, 147963, 2013, 180731, 2141, 2269, 2397, 101, 2525, 182011, 148091, 180859, 3165, 149371, 182139, 280571, 313339,
  346107, 279675, 377851, 378875, 312443, 345211, 377979, 446, 2653, 2781, 2909, 3037, 3293, 3421, 3549, 3413, 733, 229, 989, 741, 1117, 1245, 869, 997,
  1373, 1125, 1501, 1253, 1509, 3541, 93, 1629, 221, 349, 477, 1381, 605, 357, 485, 861, 613, 1637, 1893, 2021, 2149, 2277, 2405, 2533,
  2661, 2789, 12269, 2917, 3045, 12397, 3173, 12525, 3301, 12653, 3429, 12781, 12909, 3557, 13037, 8301, 8429, 13165, 13293, 1765, 8557, 8685, 13421, 13549,
  8813, 13677, 9069, 13805, 9197, 13933, 8941, 14061, 9325, 9453, 14189, 14317, 9581, 9709, 14445, 14573, 9837, 10861, 10989, 11117, 11245, 11373, 11501, 11629,
  9965, 14701, 14829, 10093, 10221, 14957, 15213, 15341, 10605, 10733, 15085, 11757, 10349, 8573, 11885, 10477, 8701, 12013, 2549, 12141, 2677, 8317, 2805, 2933,
  8262, 8390, 8518, 8646, 8774, 9030, 9158, 8902, 9038, 9166, 8270, 8398, 8526, 8654, 8782, 3061, 8910, 3189, 3317, 117, 245, 373, 501, 629,
  757, 3445, 3573, 1269, 1397, 1525, 8445, 8829, 8957, 9085, 9213, 9341, 9469, 9597, 9725, 9853, 10621, 9981, 10109, 10749, 11645, 10237, 11773, 12029,
  10365, 11901, 12157, 12285, 10493, 885, 12413, 1653, 1781, 1013, 1909, 1141, 12541, 2037, 12669, 2165, 12797, 2293, 12925, 2421, 13053, 13181, 13309, 13565,
  13437, 13693, 13821, 10877, 11005, 11133, 11517, 13949, 14077, 14205, 14333, 14461, 14589, 14717, 14845, 14973, 8278, 8406, 8534, 15101, 8662, 15229, 8790, 15357,
  9174, 8918, 11261, 8286, 9046, 8542, 11389, 8414, 8670, 8798, 8926, 9054, 9182, 147558, 180326, 147686, 180454, 147814, 180582, 16870, 16998, 17126, 17254, 17382,
  17510, 17638, 17766, 17894, 18022, 18150, 18278, 18406, 16494, 16622, 16750, 16878, 17006, 17134, 17390, 17518, 17646, 17774, 17902, 18030, 18158, 278774, 17262, 18414,
  311542, 18286, 344310, 147574, 377078, 180342, 147830, 180598, 148470, 181238, 16894, 17022, 182006, 149366, 17150, 182134, 148598, 17278, 181366, 148726, 148854, 17534, 181494, 17662,
  181622, 17790, 147958, 180726, 18046, 148086, 180854, 18174, 148214, 180982, 148342, 181110, 148982, 181750, 149110, 181878, 149238, 149494, 182262, 16510, 16638, 16766, 18302, 18430,
  17918, 17406,
};
void build_list(HList& l) {
  l.n = sizeof(h_items) / sizeof(h_items[0]);
  for (uint32_t i = 0; i < l.n; i++) l.it[i] = h_items[i];
}

typedef CUresult (*EncodeFn)(CUtensorMap*, CUtensorMapDataType, cuuint32_t, void*, const cuuint64_t*, const cuuint64_t*,
                             const cuuint32_t*, const cuuint32_t*, CUtensorMapInterleave, CUtensorMapSwizzle,
                             CUtensorMapL2promotion, CUtensorMapFloatOOBfill);

#define PROMO_W CU_TENSOR_MAP_L2_PROMOTION_L2_128B
#define PROMO_O CU_TENSOR_MAP_L2_PROMOTION_L2_128B
#define PROMO_M CU_TENSOR_MAP_L2_PROMOTION_L2_128B
#define PROMO_H CU_TENSOR_MAP_L2_PROMOTION_L2_128B
void make_map(EncodeFn fn, CUtensorMap* m, const void* p, uint64_t cols, uint64_t rows, uint32_t bc, uint32_t br, CUtensorMapSwizzle sw,
              CUtensorMapL2promotion promo) {
  cuuint64_t dims[2] = {cols, rows};
  cuuint64_t strides[1] = {cols * 2};
  cuuint32_t box[2] = {bc, br};
  cuuint32_t es[2] = {1, 1};
  fn(m, CU_TENSOR_MAP_DATA_TYPE_BFLOAT16, 2, const_cast<void*>(p), dims, strides, box, es, CU_TENSOR_MAP_INTERLEAVE_NONE, sw,
     promo, CU_TENSOR_MAP_FLOAT_OOB_FILL_NONE);
}

void make_map_perm(EncodeFn fn, CUtensorMap* m, const void* p, uint64_t cols, uint64_t rows, bool perm) {
  cuuint64_t dims[5] = {cols, 2, 4, 4, rows / 32};
  cuuint64_t strides[4] = {cols * 2, cols * 2 * (perm ? 8 : 2), cols * 2 * (perm ? 2 : 8), cols * 2 * 32};
  cuuint32_t box[5] = {64, 2, 4, 4, 2};
  cuuint32_t es[5] = {1, 1, 1, 1, 1};
  fn(m, CU_TENSOR_MAP_DATA_TYPE_BFLOAT16, 5, const_cast<void*>(p), dims, strides, box, es, CU_TENSOR_MAP_INTERLEAVE_NONE,
     CU_TENSOR_MAP_SWIZZLE_128B, PROMO_H, CU_TENSOR_MAP_FLOAT_OOB_FILL_NONE);
}

}

extern "C" void kernel_launch(void* const* d_in, const int* in_sizes, int n_in, void* d_out, int out_size) {
  const __nv_bfloat16* x = (const __nv_bfloat16*)d_in[0];
  const __nv_bfloat16* mem0 = (const __nv_bfloat16*)d_in[1];
  const __nv_bfloat16* cvec = (const __nv_bfloat16*)d_in[11];
  static EncodeFn enc = nullptr;
  if (!enc) {
    cudaDriverEntryPointQueryResult qr;
    void* fp = nullptr;
    cudaGetDriverEntryPoint("cuTensorMapEncodeTiled", &fp, cudaEnableDefault, &qr);
    enc = (EncodeFn)fp;
    cudaFuncSetAttribute(kernel_R, cudaFuncAttributeMaxDynamicSharedMemorySize, R_SMEM);
    cudaFuncSetAttribute(kernel_H, cudaFuncAttributeMaxDynamicSharedMemorySize, H_SMEM);
  }
  CUtensorMap tmq, tmk, tmv, tmo, tmm;
  make_map(enc, &tmm, d_in[12], 6144, 1024, 64, 64, CU_TENSOR_MAP_SWIZZLE_NONE, PROMO_M);
  make_map(enc, &tmq, d_in[2], 4096, 1024, 64, 64, CU_TENSOR_MAP_SWIZZLE_128B, PROMO_W);
  make_map(enc, &tmk, d_in[3], 4096, 1024, 64, 64, CU_TENSOR_MAP_SWIZZLE_128B, PROMO_W);
  make_map(enc, &tmv, d_in[4], 4096, 1024, 64, 64, CU_TENSOR_MAP_SWIZZLE_128B, PROMO_W);
  make_map(enc, &tmo, d_in[5], 1024, 4096, 16, 128, CU_TENSOR_MAP_SWIZZLE_32B, PROMO_O);
  RDesc dsc;
  for (int k = 0; k < 32; k++) {
    dsc.tok[k] = mkdesc(0x400 + (k < 16 ? R_GA : R_GB) + ((k & 15) >> 2) * 4096 + (k & 3) * 256, 128, 1024, 0);
    dsc.tail_a[k] = mkdesc(0x400 + R_TAIL + k * 2048, 1024, 1024, 1);
    if (k < 16) dsc.tail_b[k] = mkdesc(0x400 + R_GA + k * 256, 128, 4096, 0);
  }
  kernel_R<<<96, 256, R_SMEM, cudaStreamPerThread>>>(tmq, tmk, tmv, tmo, tmm, x, mem0, cvec, dsc);

  CUtensorMap ho, h1, h3, h2, hm;
  make_map_perm(enc, &ho, d_in[5], 1024, 4096, false);
  make_map_perm(enc, &h1, d_in[8], F_, 1024, true);
  make_map_perm(enc, &h3, d_in[9], F_, 1024, true);
  make_map_perm(enc, &h2, d_in[10], 1024, F_, true);
  make_map_perm(enc, &hm, d_in[12], 6144, 1024, true);
  HList list;
  build_list(list);
  cudaLaunchConfig_t cfg = {};
#define H_GRID 132
  cfg.gridDim = dim3(H_GRID); cfg.blockDim = dim3(384); cfg.dynamicSmemBytes = H_SMEM; cfg.stream = cudaStreamPerThread;
  cudaLaunchAttribute at[1];
  at[0].id = cudaLaunchAttributeProgrammaticStreamSerialization;
  at[0].val.programmaticStreamSerializationAllowed = 1;
  cfg.attrs = at;
  cfg.numAttrs = 1;
  cudaLaunchKernelEx(&cfg, kernel_H, ho, h1, h3, h2, hm, x, cvec, (__nv_bfloat16*)d_out, list);
}
```

```cpp
#include <cuda_runtime.h>
#include <cuda_bf16.h>
#include <cuda.h>
#include <stdint.h>
#include <type_traits>

namespace {

constexpr int S_ = 2048, D_ = 1024, NSEG = 64, F_ = 3584;

__device__ __align__(1024) uint8_t g_h[S_ * D_ * 2];
__device__ __align__(1024) uint8_t g_att[S_ * 4096 * 2];
__device__ __align__(1024) uint8_t g_x1[S_ * D_ * 2];
__device__ __align__(1024) uint8_t g_h2[S_ * D_ * 2];
__device__ __align__(1024) uint8_t g_act[S_ * F_ * 2];
__device__ __align__(1024) float g_ws[2 * 4 * 16 * 4 * 8192];
__device__ __align__(1024) float g_stat[S_ * 2];
__device__ __align__(1024) float g_uv[F_ * 4];
__device__ __align__(1024) float g_slot[4 * 3 * 8 * 4 * 32 * 4];
__device__ __align__(128) __nv_bfloat16 g_mod[6 * D_];
__device__ __align__(128) float g_modp[3 * 2 * D_];
__device__ __align__(128) uint32_t g_flags[1024];
constexpr int FL_S1 = 0, FL_S2 = 32, FL_MOD = 64, FL_HEAD = 96, FL_EXIT = 128, FL_UV = 160, FL_GO = 192, FL_MODB = 224, FL_ATT = 256, FL_XT = 384, FL_OUT = 512, FL_F1 = 640, FL_SPL = 768;

#define EVF 1
__device__ __forceinline__ uint32_t smem_u32(const void* p) { return (uint32_t)__cvta_generic_to_shared(p); }
__device__ __forceinline__ uint32_t mapa(uint32_t a, uint32_t r) { uint32_t o; asm("mapa.shared::cluster.u32 %0, %1, %2;" : "=r"(o) : "r"(a), "r"(r)); return o; }
__device__ __forceinline__ uint32_t pack2(float a, float b) { uint32_t r; asm("cvt.rn.bf16x2.f32 %0, %1, %2;" : "=r"(r) : "f"(b), "f"(a)); return r; }
__device__ __forceinline__ float bf_lo(uint32_t w) { return __uint_as_float(w << 16); }
__device__ __forceinline__ float bf_hi(uint32_t w) { return __uint_as_float(w & 0xffff0000u); }
__device__ __forceinline__ float ex2(float x) { float y; asm("ex2.approx.ftz.f32 %0, %1;" : "=f"(y) : "f"(x)); return y; }
__device__ __forceinline__ float rcp(float x) { float y; asm("rcp.approx.ftz.f32 %0, %1;" : "=f"(y) : "f"(x)); return y; }
__device__ __forceinline__ uint32_t clk32() { uint64_t c; asm volatile("mov.u64 %0, %%clock64;" : "=l"(c) :: "memory"); return (uint32_t)c; }

__device__ __forceinline__ void mbar_init(uint32_t b, uint32_t n) { asm volatile("mbarrier.init.shared::cta.b64 [%0], %1;" :: "r"(b), "r"(n) : "memory"); }
__device__ __forceinline__ void mbar_arrive(uint32_t b) { asm volatile("mbarrier.arrive.shared::cta.b64 _, [%0];" :: "r"(b) : "memory"); }
__device__ __forceinline__ void mbar_expect(uint32_t b, uint32_t n) { asm volatile("mbarrier.arrive.expect_tx.shared::cta.b64 _, [%0], %1;" :: "r"(b), "r"(n) : "memory"); }
__device__ __forceinline__ uint32_t mbar_try(uint32_t b, uint32_t par) {
  uint32_t ok;
  asm volatile("{\n.reg .pred p;\nmbarrier.try_wait.parity.shared::cta.b64 p, [%1], %2;\nselp.u32 %0, 1, 0, p;\n}" : "=r"(ok) : "r"(b), "r"(par) : "memory");
  return ok;
}
__device__ __forceinline__ void mbar_wait(uint32_t b, uint32_t par) {
  asm volatile("{\n.reg .pred p;\n"
               "LOOP:\n"
               "mbarrier.try_wait.parity.shared::cta.b64 p, [%0], %1;\n"
               "@!p bra.uni LOOP;\n}" :: "r"(b), "r"(par) : "memory");
}
__device__ __forceinline__ void mbar_wait_safe(uint32_t b, uint32_t par) {
  uint32_t c = 0;
  while (!mbar_try(b, par)) { if (++c > 4000000u) __trap(); }
}
__device__ __forceinline__ bool elect_one() {
  uint32_t p;
  asm volatile("{\n.reg .pred p;\nelect.sync _|p, 0xffffffff;\nselp.u32 %0, 1, 0, p;\n}" : "=r"(p));
  return p;
}
__device__ __forceinline__ void sched_fence(uint32_t x, uint32_t y) { asm volatile("{\n.reg .pred p;\nsetp.eq.u32 p, %0, %1;\n@p trap;\n}" :: "r"(x), "r"(y) : "memory"); }
template <class T> __device__ __forceinline__ T opaque32(T x) { asm volatile("" : "+r"(x)); return x; }
template <class T> __device__ __forceinline__ T opaque64(T x) { asm volatile("" : "+l"(x)); return x; }
template <int ID, int N> __device__ __forceinline__ void bar_sync() { asm volatile("bar.sync %0, %1;" :: "n"(ID), "n"(N) : "memory"); }
template <int ID, int N> __device__ __forceinline__ void bar_arrive() { asm volatile("bar.arrive %0, %1;" :: "n"(ID), "n"(N) : "memory"); }
__device__ __forceinline__ void fence_async_smem() { asm volatile("fence.proxy.async.shared::cta;" ::: "memory"); }
__device__ __forceinline__ void fence_async_all() { asm volatile("fence.proxy.async;" ::: "memory"); }
__device__ __forceinline__ void fence_gpu() { asm volatile("fence.acq_rel.gpu;" ::: "memory"); }
__device__ __forceinline__ void red_add_u32(uint32_t* p, uint32_t v) { asm volatile("red.relaxed.gpu.global.add.u32 [%0], %1;" :: "l"(p), "r"(v) : "memory"); }
__device__ __forceinline__ uint32_t ld_acquire(const uint32_t* p) { uint32_t v; asm volatile("ld.acquire.gpu.global.u32 %0, [%1];" : "=r"(v) : "l"(p) : "memory"); return v; }
__device__ __forceinline__ void wait_flag(const uint32_t* p, uint32_t target) {
  uint32_t c = 0;
  while (ld_acquire(p) < target) { if (++c > 20000000u) __trap(); __nanosleep(20); }
}

__device__ __forceinline__ void wait_flag2(const uint32_t* p, uint32_t target) {
  asm volatile("{\n.reg .pred p;\n.reg .u32 v, c;\nmov.u32 c, 0;\nWL:\nld.acquire.gpu.global.u32 v, [%0];\nsetp.ge.u32 p, v, %1;\n@p bra WD;\n"
               "add.u32 c, c, 1;\nsetp.gt.u32 p, c, 20000000;\n@p trap;\nnanosleep.u32 20;\nbra WL;\nWD:\n}" :: "l"(p), "r"(target) : "memory");
}
__device__ __forceinline__ void tma2d(uint32_t dst, const CUtensorMap* m, int c0, int c1, uint32_t bar) {
  asm volatile("cp.async.bulk.tensor.2d.shared::cluster.global.mbarrier::complete_tx::bytes [%0], [%1, {%3, %4}], [%2];"
               :: "r"(dst), "l"(m), "r"(bar), "r"(c0), "r"(c1) : "memory");
}
__device__ __forceinline__ void tma2d_once(uint32_t dst, const CUtensorMap* m, int c0, int c1, uint32_t bar) {
  asm volatile("{\n.reg .b64 pol;\ncreatepolicy.fractional.L2::evict_first.b64 pol, 1.0;\n"
               "cp.async.bulk.tensor.2d.shared::cluster.global.mbarrier::complete_tx::bytes.L2::cache_hint [%0], [%1, {%3, %4}], [%2], pol;\n}"
               :: "r"(dst), "l"(m), "r"(bar), "r"(c0), "r"(c1) : "memory");
}
__device__ __forceinline__ void tma5d(uint32_t dst, const CUtensorMap* m, int n0, int kb, uint32_t bar) {
  asm volatile("cp.async.bulk.tensor.5d.shared::cluster.global.mbarrier::complete_tx::bytes [%0], [%1, {%3, %5, %5, %5, %4}], [%2];"
               :: "r"(dst), "l"(m), "r"(bar), "r"(n0), "r"(2 * kb), "r"(0) : "memory");
}
__device__ __forceinline__ void tma2d_prefetch(const CUtensorMap* m, int c0, int c1) {
  asm volatile("cp.async.bulk.prefetch.tensor.2d.L2.global [%0, {%1, %2}];" :: "l"(m), "r"(c0), "r"(c1) : "memory");
}
__device__ __forceinline__ void bulk_g2s(uint32_t dst, const void* src, uint32_t bytes, uint32_t bar) {
  asm volatile("cp.async.bulk.shared::cluster.global.mbarrier::complete_tx::bytes [%0], [%1], %2, [%3];"
               :: "r"(dst), "l"(src), "r"(bytes), "r"(bar) : "memory");
}
__device__ __forceinline__ void bulk_s2s(uint32_t dst, uint32_t src, uint32_t bytes, uint32_t bar) {
  asm volatile("cp.async.bulk.shared::cluster.shared::cta.mbarrier::complete_tx::bytes [%0], [%1], %2, [%3];"
               :: "r"(dst), "r"(src), "r"(bytes), "r"(bar) : "memory");
}
__device__ __forceinline__ void st_async1(uint32_t dst, uint32_t a, uint32_t bar) {
  asm volatile("st.async.shared::cluster.mbarrier::complete_tx::bytes.b32 [%0], %1, [%2];" :: "r"(dst), "r"(a), "r"(bar) : "memory");
}
__device__ __forceinline__ void st_async2(uint32_t dst, uint32_t a, uint32_t b, uint32_t bar) {
  asm volatile("st.async.shared::cluster.mbarrier::complete_tx::bytes.v2.b32 [%0], {%1, %2}, [%3];" :: "r"(dst), "r"(a), "r"(b), "r"(bar) : "memory");
}
__device__ __forceinline__ void st_async4(uint32_t dst, const uint32_t* r, uint32_t bar) {
  asm volatile("st.async.shared::cluster.mbarrier::complete_tx::bytes.v4.b32 [%0], {%1, %2, %3, %4}, [%5];"
               :: "r"(dst), "r"(r[0]), "r"(r[1]), "r"(r[2]), "r"(r[3]), "r"(bar) : "memory");
}
__device__ __forceinline__ void sts32(uint32_t a, uint32_t v) { asm volatile("st.shared.b32 [%0], %1;" :: "r"(a), "r"(v) : "memory"); }
__device__ __forceinline__ void sts64(uint32_t a, uint32_t x, uint32_t y) { asm volatile("st.shared.v2.b32 [%0], {%1, %2};" :: "r"(a), "r"(x), "r"(y) : "memory"); }
__device__ __forceinline__ void sts128(uint32_t a, uint32_t x, uint32_t y, uint32_t z, uint32_t w) {
  asm volatile("st.shared.v4.b32 [%0], {%1, %2, %3, %4};" :: "r"(a), "r"(x), "r"(y), "r"(z), "r"(w) : "memory");
}
__device__ __forceinline__ void lds128(uint32_t* r, uint32_t a) {
  asm volatile("ld.shared.v4.b32 {%0, %1, %2, %3}, [%4];" : "=r"(r[0]), "=r"(r[1]), "=r"(r[2]), "=r"(r[3]) : "r"(a) : "memory");
}
__device__ __forceinline__ uint32_t lds32(uint32_t a) { uint32_t r; asm volatile("ld.shared.b32 %0, [%1];" : "=r"(r) : "r"(a) : "memory"); return r; }
__device__ __forceinline__ void lds64(uint32_t* r, uint32_t a) {
  asm volatile("ld.shared.v2.b32 {%0, %1}, [%2];" : "=r"(r[0]), "=r"(r[1]) : "r"(a) : "memory");
}
__device__ __forceinline__ void lds128f(float* r, uint32_t a) {
  asm volatile("ld.shared.v4.f32 {%0, %1, %2, %3}, [%4];" : "=f"(r[0]), "=f"(r[1]), "=f"(r[2]), "=f"(r[3]) : "r"(a) : "memory");
}
__device__ __forceinline__ void lds64f(float* r, uint32_t a) {
  asm volatile("ld.shared.v2.f32 {%0, %1}, [%2];" : "=f"(r[0]), "=f"(r[1]) : "r"(a) : "memory");
}
__device__ __forceinline__ void ldsm4(uint32_t* r, uint32_t a) {
  asm volatile("ldmatrix.sync.aligned.m8n8.x4.shared.b16 {%0, %1, %2, %3}, [%4];" : "=r"(r[0]), "=r"(r[1]), "=r"(r[2]), "=r"(r[3]) : "r"(a) : "memory");
}
__device__ __forceinline__ void ldsm4t(uint32_t* r, uint32_t a) {
  asm volatile("ldmatrix.sync.aligned.m8n8.x4.trans.shared.b16 {%0, %1, %2, %3}, [%4];" : "=r"(r[0]), "=r"(r[1]), "=r"(r[2]), "=r"(r[3]) : "r"(a) : "memory");
}
__device__ __forceinline__ void ldsm2(uint32_t* r, uint32_t a) {
  asm volatile("ldmatrix.sync.aligned.m8n8.x2.shared.b16 {%0, %1}, [%2];" : "=r"(r[0]), "=r"(r[1]) : "r"(a) : "memory");
}
__device__ __forceinline__ void stsm4(uint32_t a, const uint32_t* r) {
  asm volatile("stmatrix.sync.aligned.m8n8.x4.shared.b16 [%0], {%1, %2, %3, %4};" :: "r"(a), "r"(r[0]), "r"(r[1]), "r"(r[2]), "r"(r[3]) : "memory");
}
__device__ __forceinline__ uint32_t hadd2(uint32_t a, uint32_t b) { uint32_t t; asm("add.rn.bf16x2 %0, %1, %2;" : "=r"(t) : "r"(a), "r"(b)); return t; }
__device__ __forceinline__ uint32_t hmax2(uint32_t a, uint32_t b) { uint32_t t; asm("max.bf16x2 %0, %1, %2;" : "=r"(t) : "r"(a), "r"(b)); return t; }
__device__ __forceinline__ void ldsm2t(uint32_t* r, uint32_t a) {
  asm volatile("ldmatrix.sync.aligned.m8n8.x2.trans.shared.b16 {%0, %1}, [%2];" : "=r"(r[0]), "=r"(r[1]) : "r"(a) : "memory");
}
__device__ __forceinline__ uint32_t movm(uint32_t x) { uint32_t y; asm volatile("movmatrix.sync.aligned.m8n8.trans.b16 %0, %1;" : "=r"(y) : "r"(x)); return y; }
__device__ __forceinline__ void hmma(float* d, uint32_t a0, uint32_t a1, uint32_t a2, uint32_t a3, uint32_t b0, uint32_t b1) {
  asm volatile("mma.sync.aligned.m16n8k16.row.col.f32.bf16.bf16.f32 {%0,%1,%2,%3}, {%4,%5,%6,%7}, {%8,%9}, {%0,%1,%2,%3};"
               : "+f"(d[0]), "+f"(d[1]), "+f"(d[2]), "+f"(d[3]) : "r"(a0), "r"(a1), "r"(a2), "r"(a3), "r"(b0), "r"(b1));
}
__device__ __forceinline__ void hmma0(float* d, uint32_t a0, uint32_t a1, uint32_t a2, uint32_t a3, uint32_t b0, uint32_t b1) {
  asm volatile("mma.sync.aligned.m16n8k16.row.col.f32.bf16.bf16.f32 {%0,%1,%2,%3}, {%4,%5,%6,%7}, {%8,%9}, {%10,%10,%10,%10};"
               : "=f"(d[0]), "=f"(d[1]), "=f"(d[2]), "=f"(d[3]) : "r"(a0), "r"(a1), "r"(a2), "r"(a3), "r"(b0), "r"(b1), "f"(0.f));
}
__device__ __forceinline__ void hmma_k8(float* d, uint32_t a0, uint32_t a1, uint32_t b0) {
  asm volatile("mma.sync.aligned.m16n8k8.row.col.f32.bf16.bf16.f32 {%0,%1,%2,%3}, {%4,%5}, {%6}, {%0,%1,%2,%3};"
               : "+f"(d[0]), "+f"(d[1]), "+f"(d[2]), "+f"(d[3]) : "r"(a0), "r"(a1), "r"(b0));
}
__host__ __device__ constexpr uint64_t mkdesc(uint32_t addr, uint32_t lbo, uint32_t sbo, uint32_t sw) {
  return (uint64_t)((addr & 0x3FFFF) >> 4) | ((uint64_t)(lbo >> 4) << 16) | ((uint64_t)(sbo >> 4) << 32) | ((uint64_t)sw << 62);
}
#define WG_FENCE() asm volatile("wgmma.fence.sync.aligned;" ::: "memory")
#define WG_COMMIT() asm volatile("wgmma.commit_group.sync.aligned;" ::: "memory")
#define WG_WAIT(n) asm volatile("wgmma.wait_group.sync.aligned " #n ";" ::: "memory")
template <int N> __device__ __forceinline__ void reg_fence(float* d) {
#pragma unroll
  for (int i = 0; i < N; i++) asm volatile("" : "+f"(d[i]) :: "memory");
}
template <int N> __device__ __forceinline__ void zero_regs(float* d) {
#pragma unroll
  for (int i = 0; i < N; i++) asm volatile("mov.b32 %0, 0;" : "=f"(d[i]));
}
template <int SD>
__device__ __forceinline__ void wg_rs32(float* d, uint32_t a0, uint32_t a1, uint32_t a2, uint32_t a3, uint64_t b) {
  asm volatile("wgmma.mma_async.sync.aligned.m64n32k16.f32.bf16.bf16 {%0,%1,%2,%3,%4,%5,%6,%7,%8,%9,%10,%11,%12,%13,%14,%15}, {%16,%17,%18,%19}, %20, %21, 1, 1, 0;"
               : "+f"(d[0]), "+f"(d[1]), "+f"(d[2]), "+f"(d[3]), "+f"(d[4]), "+f"(d[5]), "+f"(d[6]), "+f"(d[7]),
                 "+f"(d[8]), "+f"(d[9]), "+f"(d[10]), "+f"(d[11]), "+f"(d[12]), "+f"(d[13]), "+f"(d[14]), "+f"(d[15])
               : "r"(a0), "r"(a1), "r"(a2), "r"(a3), "l"(b), "n"(SD));
}
template <int TB>
__device__ __forceinline__ void wg_ss40(float* d, uint64_t a, uint64_t b) {
  asm volatile("wgmma.mma_async.sync.aligned.m64n40k16.f32.bf16.bf16 {%0,%1,%2,%3,%4,%5,%6,%7,%8,%9,%10,%11,%12,%13,%14,%15,%16,%17,%18,%19}, %20, %21, 1, 1, 1, 1, %22;"
               : "+f"(d[0]), "+f"(d[1]), "+f"(d[2]), "+f"(d[3]), "+f"(d[4]), "+f"(d[5]), "+f"(d[6]), "+f"(d[7]),
                 "+f"(d[8]), "+f"(d[9]), "+f"(d[10]), "+f"(d[11]), "+f"(d[12]), "+f"(d[13]), "+f"(d[14]), "+f"(d[15]),
                 "+f"(d[16]), "+f"(d[17]), "+f"(d[18]), "+f"(d[19])
               : "l"(a), "l"(b), "n"(TB));
}
__device__ __forceinline__ void wg_ss8(float* d, uint64_t a, uint64_t b) {
  asm volatile("wgmma.mma_async.sync.aligned.m64n8k16.f32.bf16.bf16 {%0,%1,%2,%3}, %4, %5, 1, 1, 1, 1, 0;"
               : "+f"(d[0]), "+f"(d[1]), "+f"(d[2]), "+f"(d[3]) : "l"(a), "l"(b));
}
template <int T>
__device__ __forceinline__ void wg_ss32(float* d, uint64_t a, uint64_t b) {
  asm volatile("wgmma.mma_async.sync.aligned.m64n32k16.f32.bf16.bf16 {%0,%1,%2,%3,%4,%5,%6,%7,%8,%9,%10,%11,%12,%13,%14,%15}, %16, %17, 1, 1, 1, %18, %18;"
               : "+f"(d[0]), "+f"(d[1]), "+f"(d[2]), "+f"(d[3]), "+f"(d[4]), "+f"(d[5]), "+f"(d[6]), "+f"(d[7]),
                 "+f"(d[8]), "+f"(d[9]), "+f"(d[10]), "+f"(d[11]), "+f"(d[12]), "+f"(d[13]), "+f"(d[14]), "+f"(d[15])
               : "l"(a), "l"(b), "n"(T));
}

constexpr int R_TAIL = 0;
constexpr int R_WO = 65536;
constexpr int R_QK = R_WO + 86016;
constexpr int R_P = R_QK + 10240;
constexpr int R_GA = R_P + 6400;
constexpr int R_M2 = R_GA + 16384;
constexpr int R_M1 = R_M2 + 7168;
constexpr int R_GB = R_M1 + 9216;
constexpr int R_VT = R_GB + 16384;
constexpr int R_VM = R_VT + 8192;
constexpr int R_XS = R_VM + 2048;
constexpr int R_OX = R_XS + 1280;
constexpr int R_BAR = R_OX + 2048;
constexpr int R_TRC = R_BAR + 256;
constexpr int R_SMEM = R_TRC + 1024;
constexpr int B_MB = 0, B_XS = 32, B_VM = 40, B_VT = 48, B_TS = 56, B_FA = 64, B_FB = 72, B_TAIL = 80, B_WO = 88, B_STG = 96, B_WM = 128, B_X = 136;
constexpr int NB_A = 1, NB_B = 2, NB_X = 3, NB_C = 4, NB_D = 5, NB_E = 6, NB_F = 7, NB_G = 8, NB_H = 9, NB_S = 10, NB_E2 = 11, NB_P = 12, NB_W0 = 13;

#define FIN 1
#define POLL_DELAY 750
#define POLL_DELAY1 700
#define POLL_STAG 150
#define POLL_K0 20
#define PF1 2
#define PF2 2
#define PF3 2
#define PF4 0
#define CLR_D 2
#define PADN 0
#define PFD 0
#define GO_EARLY 0
#define RF_FIRST 1
#define BX_I 5
#define NCH 4
#define TOP2 0
#define CX_I 13
#define ATT_LATE 0
#define V_FENCE 1
#define SELF_STAS 1
#define Q_FENCE 1
#define ND_K 3
#define TRACE(i)
#define TS(i)

__device__ __forceinline__ int rot_chunk(int c, int rank) {
  int G = c;
  if (c < 9) { G = c + 3 * rank; if (G >= 9) G -= 9; }
  return G;
}
__device__ __forceinline__ int wo_tile(int i, int rank) {
  if (i < 12) return 12 * rank + i;
  const int r = i - 12 + 9 * rank;
  return r < 16 ? 48 + r : 20 + r;
}
__device__ __forceinline__ void load_chunk(uint32_t dst, int seg, int G, uint32_t bar) {
  mbar_expect(bar, 4096);
  bulk_g2s(dst, g_h + (size_t)(seg * 16 + G) * 4096, 4096, bar);
}
__device__ __forceinline__ void load_red(uint32_t* v, const float* p) {
#pragma unroll
  for (int j = 0; j < 2; j++)
    asm volatile("ld.relaxed.gpu.global.v4.u32 {%0, %1, %2, %3}, [%4];"
                 : "=r"(v[4 * j]), "=r"(v[4 * j + 1]), "=r"(v[4 * j + 2]), "=r"(v[4 * j + 3]) : "l"(p + j * 256) : "memory");
}
__device__ __forceinline__ bool red_done(const uint32_t* v) { return __all_sync(0xffffffffu, (v[3] & v[7]) == 0x42000000u); }
__device__ __forceinline__ uint32_t finish_red(uint32_t* v, const float* p) {
  uint32_t tries = 0;
  if (__builtin_expect(!red_done(v), 0)) {
    do { if (++tries > 20000000u) __trap(); load_red(v, p); } while (!red_done(v));
  }
  return tries;
}
__device__ __forceinline__ void exp10(float* sv, const uint32_t* x) {
  constexpr float SC = 0.08838834764831845f * 1.4426950408889634f;
  uint32_t m2 = hmax2(hmax2(hmax2(x[0], x[1]), hmax2(x[2], x[3])), x[4]);
  m2 = hmax2(m2, __shfl_xor_sync(0xffffffffu, m2, 1));
  m2 = hmax2(m2, __shfl_xor_sync(0xffffffffu, m2, 2));
  const float nm = -fmaxf(bf_lo(m2), bf_hi(m2)) * SC;
#pragma unroll
  for (int j = 0; j < 5; j++) { sv[2 * j] = ex2(fmaf(bf_lo(x[j]), SC, nm)); sv[2 * j + 1] = ex2(fmaf(bf_hi(x[j]), SC, nm)); }
}

__device__ __forceinline__ uint32_t arm_size(int w, bool isC) {
  return w == 0 ? (isC ? 1280 : 640) : w == 1 ? (isC ? 0 : 2048) : w == 2 ? (isC ? 0 : 8192) : (isC ? 0 : 1792);
}
struct RDesc { uint64_t tok[32], tail_b[16], tail_a[32]; };

template <int WG>
__device__ __forceinline__ void r_main(const uint32_t (&W)[48][4], const RDesc& dsc, int head, uint32_t rank, int lane_, int w) {
  const uint32_t sb = (rank << 24) + 0x400, bars = sb + R_BAR;
  const uint32_t to1 = rank == 0 ? 2u << 24 : 0u - (1u << 24), to2 = rank == 2 ? 0u - (2u << 24) : 1u << 24;
  const bool isC = rank == 2;
  const int lane = opaque32(lane_), warp = WG * 4 + w;
  const int gl = rot_chunk(4 * (lane & 3) + w, rank);
  const int g0 = __shfl_sync(0xffffffffu, gl, 0), g1 = __shfl_sync(0xffffffffu, gl, 1), g2 = __shfl_sync(0xffffffffu, gl, 2);
  const uint32_t arm_bytes = arm_size(w, isC);

#define L16 opaque32(sb + opaque32(lane) * 16)
#define L8 opaque32(sb + opaque32(lane) * 8)
#define L4 opaque32(sb + opaque32(lane) * 4)
#define LV opaque32(sb + R_VT + ((opaque32(lane) >> 3) & 1) * 512 + (opaque32(lane) >> 4) * 128 + (opaque32(lane) & 7) * 16)
#define SLOT(st) opaque64(slot0 + ((st) & 3) * 12288 + ((st) & 4) * 32)
  float* const slot0 = opaque64(g_slot + (rank * 1024 + warp * 128 + lane) * 4);
  const uint32_t woa = opaque32(sb + R_WO + warp * 12288 + ((lane >> 4) * 8 + (lane & 7)) * 32 + ((((lane >> 3) ^ (lane >> 2)) & 1) << 4));
  const bool has_wo = WG == 0 || isC || w < 3;
  float acc[20];
  uint32_t pk[8] = {0u, 0u, 0u, 0u, 0u, 0u, 0u, 0u};

  auto forward = [&](auto rd, const uint32_t* v, int st, uint32_t tries) {
    constexpr int RD = decltype(rd)::value;
    uint32_t u[6];
#pragma unroll
    for (int j = 0; j < 6; j++) u[j] = movm(v[4 * (j / 3) + j % 3]);
    const bool all3 = RD == 0 || w < 3;
    if (RD == 0) {
      const uint32_t a = L16 + R_M1 + w * 768, a2 = L8 + R_M1 + 512 + w * 768;
      st_async4(a + to1 + 3072, u, bars + to1 + B_MB + 8); st_async2(a2 + to1 + 3072, u[4], u[5], bars + to1 + B_MB + 8);
      sts128(a, u[0], u[1], u[2], u[3]); sts64(a2, u[4], u[5]);
      __syncwarp();
      if (elect_one()) mbar_arrive(bars + B_MB);
      st_async4(a + to2 + 6144, u, bars + to2 + B_MB + 16); st_async2(a2 + to2 + 6144, u[4], u[5], bars + to2 + B_MB + 16);
    } else {
      const uint32_t a = L4 + R_M2 + rank * 2304 + w * 768;
#pragma unroll
      for (int j = 0; j < 6; j++) if (j < 2 || all3) st_async1(a + to1 + j * 128, u[j], bars + to1 + B_MB + 24);
#pragma unroll
      for (int j = 0; j < 6; j++) if (j < 2 || all3) st_async1(a + to2 + j * 128, u[j], bars + to2 + B_MB + 24);
      if (SELF_STAS) {
#pragma unroll
        for (int j = 0; j < 6; j++) if (j < 2 || all3) st_async1(a + j * 128, u[j], bars + B_MB + 24);
      } else {
#pragma unroll
        for (int j = 0; j < 6; j++) if (j < 2 || all3) sts32(a + j * 128, u[j]);
        __syncwarp();
        if (elect_one()) mbar_arrive(bars + B_MB + 24);
      }
    }
  };

  auto send_vt = [&]() {
    if (elect_one()) {
      const uint32_t src = sb + R_VT + warp * 1024;
      bulk_s2s(src + to1, src, 1024, bars + to1 + B_VT);
      bulk_s2s(src + to2, src, 1024, bars + to2 + B_VT);
    }
  };
  auto store_att = [&](int sg) {
    uint32_t* op = reinterpret_cast<uint32_t*>(g_att + (size_t)((sg >> 2) * 64 + head * 2 + rank) * 16384 + (2 * w * 16 + (sg & 3) * 4) * 128) + opaque32(lane);
#pragma unroll
    for (int j = 0; j < 8; j++) op[(j & 1) * 512 + (j >> 1) * 32] = pk[j];
  };

  if (WG == 0) bar_arrive<NB_G, 256>();
#pragma unroll 1
  for (int s = -1; s < NSEG - FIN; s++) {
    const uint32_t par = (s + 1) & 1;
    const uint32_t last = !FIN && s == NSEG - 1;
    TRACE(0);
    {
      float c[NCH][4];
      uint32_t b[3][6];
      const uint32_t ma = L16, m8 = L8;
#pragma unroll
      for (int i = 0; i < 18; i++) {
        if (i < 16) {
          if (i % 4 == 0 && !(i == 4 && TOP2)) mbar_wait(bars + B_MB + (i / 4) * 8, par ^ 1);
          if (i == 0 && TOP2) mbar_wait(bars + B_MB + 8, par ^ 1);
          if (i % 4 == 0) TRACE(1 + i / 4);
          if (i < 12) { lds128(b[i % 3], ma + R_M1 + i * 768); lds64(b[i % 3] + 4, m8 + R_M1 + 512 + i * 768); }
          else { ldsm4(b[i % 3], ma + R_M2 + 4096 + (i - 12) * 768); ldsm2(b[i % 3] + 4, ma + R_M2 + 4096 + 512 + (i - 12) * 768); }
          if (WG == 1 && i == BX_I) {
            bar_sync<NB_G, 256>();
            if (!last && elect_one()) load_chunk(sb + R_GB + w * 4096, s + 1, g0, bars + B_FB);
          }
          if (i == CX_I) {
            if (isC && s >= 0) send_vt();
            if (WG == 1 && ATT_LATE && !isC && s > 0) store_att(s - 1);
          }
          __syncwarp();
        }
        if (i >= 2) {
          const int j = i - 2;
#pragma unroll
          for (int q = 0; q < 3; q++) {
            const uint32_t* f = W[3 * j + q];
            if (3 * j + q < NCH) hmma0(c[3 * j + q], f[0], f[1], f[2], f[3], b[j % 3][2 * q], b[j % 3][2 * q + 1]);
            else hmma(c[(3 * j + q) % NCH], f[0], f[1], f[2], f[3], b[j % 3][2 * q], b[j % 3][2 * q + 1]);
          }
        }
        if (i == 14) zero_regs<16>(acc);
        if (i == 16) mbar_wait(bars + B_FA, last);
      }
#pragma unroll
      for (int j = 0; j < 4; j++) acc[16 + j] = NCH == 3 ? (c[0][j] + c[1][j]) + c[2][j] : (c[0][j] + c[1][j]) + (c[2][j] + c[NCH - 1][j]);
    }
    TRACE(5);
    bar_sync<NB_H, 256>();
    WG_FENCE();
#pragma unroll
    for (int k = 0; k < 16; k++) wg_ss40<0>(acc, dsc.tail_a[WG * 16 + k], dsc.tail_b[k]);
    WG_COMMIT();
    uint32_t vt[4][4];
    {
      const uint32_t a = opaque32(L4 + w * 256 + (isC ? WG * 1024 + R_VM : R_QK + 4096 + WG * 5120));
      const uint32_t qa = L16 + R_QK, xa = opaque32(LV + w * 2048 + (WG == 0 ? 0 : (opaque32(lane) & 8) * 64 + R_QK + 5120 - R_VT));
      const uint32_t d = opaque32(L4 + R_XS + rank * 640 + w * 256);
      if (s == 0) {
        mbar_wait_safe(bars + B_WO, 0);
        if (!GO_EARLY && WG == 1 && head == 0 && rank == 0 && w == 0 && elect_one()) red_add_u32(&g_flags[FL_GO], 1);
      }
      mbar_wait(bars + B_FB, last);
      if (WG == 0) mbar_wait(bars + B_VT, par);
      WG_WAIT(0);
      reg_fence<20>(acc);
      TRACE(6);
      const uint32_t p0 = pack2(acc[16], acc[17]), p1 = pack2(acc[18], acc[19]);
      sts32(a, p0); sts32(a + 128, p1);
      if (isC) {
        st_async1(a + to1, p0, bars + B_VM + to1); st_async1(a + to1 + 128, p1, bars + B_VM + to1);
        st_async1(a + to2, p0, bars + B_VM + to2); st_async1(a + to2 + 128, p1, bars + B_VM + to2);
      }
      if (WG == 0) {
        bar_arrive<NB_A, 256>();
        if (Q_FENCE && !isC) fence_async_smem();
#pragma unroll
        for (int i = 0; i < 4; i++) ldsm4(vt[i], xa + (i >> 1) * 1024 + (i & 1) * 256);
        bar_sync<NB_S, 256>();
      } else {
        bar_sync<NB_A, 256>();
        if (!isC) {
          if (w < 3) {
            uint32_t q[8], k[4][4];
            ldsm4t(q, qa + 4096); ldsm4t(k[0], xa); ldsm4t(k[1], xa + 256);
            ldsm4t(q + 4, qa + 4096 + 512); ldsm4t(k[2], xa + 512); ldsm4t(k[3], xa + 768);
            float x[4], y[4];
            hmma0(x, k[0][0], k[0][1], k[0][2], k[0][3], q[0], q[1]); hmma0(y, k[1][0], k[1][1], k[1][2], k[1][3], q[2], q[3]);
            hmma(x, k[2][0], k[2][1], k[2][2], k[2][3], q[4], q[5]); hmma(y, k[3][0], k[3][1], k[3][2], k[3][3], q[6], q[7]);
            const uint32_t s0 = pack2(x[0] + y[0], x[1] + y[1]), s1 = pack2(x[2] + y[2], x[3] + y[3]);
            st_async1(d + to1, s0, bars + B_XS + to1);
            st_async1(d + to2, s0, bars + B_XS + to2);
            if (w < 2) { st_async1(d + to1 + 128, s1, bars + B_XS + to1); st_async1(d + to2 + 128, s1, bars + B_XS + to2); sts32(d + 128, s1); }
            sts32(d, s0);
          }
        }
        bar_arrive<NB_S, 256>();
      }
    }
    if (WG == 1) {
      if (!last && elect_one()) load_chunk(sb + R_GA + w * 4096, s + 1, g1, bars + B_FA);
      {
        if (w > 0 && elect_one()) mbar_expect(bars + B_MB + 8 * w, w < 3 ? 3072 : SELF_STAS ? 28 * 256 : isC ? 18 * 256 : 19 * 256);
      }
      fence_async_smem();
      bar_sync<NB_B, 256>();
    }
    TRACE(7);
    WG_FENCE();
#pragma unroll
    for (int k = 0; k < 16; k++) wg_rs32<1>(acc, W[k][0], W[k][1], W[k][2], W[k][3], dsc.tok[16 + k]);
    WG_COMMIT();
    uint32_t wa[3][4];
    const uint32_t oxa = L16 + R_OX;
    if (WG == 0) {
      const uint32_t vma = oxa - (R_OX - R_VM) + w * 512, oa = opaque32(L4 + w * 512 + R_OX);
      TRACE(8);
      mbar_wait(bars + B_XS, par);
      TRACE(9);
      float sv[10];
      {
        uint32_t x[10];
        ldsm4t(x, oxa - (R_OX - R_XS)); ldsm4t(x + 4, oxa - (R_OX - R_XS) + 512); ldsm2t(x + 8, oxa - (R_OX - R_XS) + 1024);
        bar_arrive<NB_B, 256>();
#pragma unroll
        for (int j = 0; j < 5; j++) x[j] = hadd2(x[j], x[j + 5]);
        exp10(sv, x);
      }
      WG_WAIT(0);
      bar_arrive<NB_X, 256>();
      mbar_wait(bars + B_VM, par);
      uint32_t vm[4];
      ldsm4(vm, vma);
      uint32_t pb[5];
#pragma unroll
      for (int j = 0; j < 5; j++) pb[j] = pack2(sv[2 * j], sv[2 * j + 1]);
      TRACE(10);
      float o0[4], o1[4], sm[4];
      const uint32_t ONE = 0x3f803f80u;
      hmma0(o0, vt[0][0], vt[0][1], vt[0][2], vt[0][3], pb[0], pb[1]);
      hmma0(o1, vt[2][0], vt[2][1], vt[2][2], vt[2][3], pb[0], pb[1]);
      hmma0(sm, ONE, ONE, ONE, ONE, pb[0], pb[1]);
      hmma(sm, ONE, ONE, ONE, ONE, pb[2], pb[3]);
      hmma(o0, vt[1][0], vt[1][1], vt[1][2], vt[1][3], pb[2], pb[3]);
      hmma(o1, vt[3][0], vt[3][1], vt[3][2], vt[3][3], pb[2], pb[3]);
      hmma_k8(sm, ONE, ONE, pb[4]);
      hmma_k8(o0, vm[0], vm[1], pb[4]);
      hmma_k8(o1, vm[2], vm[3], pb[4]);
#pragma unroll
      for (int i = 0; i < 3; i++) ldsm4t(wa[i], woa + i * 4096);
      __syncwarp();
      const float i0 = rcp(sm[0]), i1 = rcp(sm[1]);
      sts32(oa, pack2(o0[0] * i0, o0[1] * i1)); sts32(oa + 128, pack2(o0[2] * i0, o0[3] * i1));
      sts32(oa + 256, pack2(o1[0] * i0, o1[1] * i1)); sts32(oa + 384, pack2(o1[2] * i0, o1[3] * i1));
      TRACE(11);
      bar_sync<NB_C, 128>();
    } else {
      if (!isC) {
        constexpr uint64_t dQ = mkdesc(0x400 + R_QK, 128, 1024, 0), dK = mkdesc(0x400 + R_QK + 5120, 128, 1024, 0);
        float sc[16];
        zero_regs<16>(sc);
        WG_FENCE();
#pragma unroll
        for (int k = 0; k < 4; k++) wg_ss32<1>(sc, dK + k * 16, dQ + k * 16);
        WG_COMMIT();
        const uint32_t top = rank == 0 ? to2 : to1, e = L4 + R_P + w * 256;
        WG_WAIT(0);
        bar_sync<NB_X, 256>();
        if (!last && elect_one()) load_chunk(sb + R_GB + w * 4096, s + 1, g2, bars + B_FB);
        reg_fence<16>(sc);
        if (w < 3) {
#pragma unroll
          for (int j = 0; j < 8; j++) {
            if ((j & 1) ? (j > 1 && (w == 0 || (w == 1 && j == 7))) : (j >= 4 || w != 1)) {
              const uint32_t t = pack2(sc[2 * j], sc[2 * j + 1]), o = (j >> 1) * 768 + (j & 1) * 128;
              st_async1(e + top + 3072 + o, t, bars + top + B_TS);
              sts32(e + o, t);
            }
          }
          __syncwarp();
          if (elect_one()) mbar_arrive(bars + B_TS);
        }
      } else {
        WG_WAIT(0);
        bar_sync<NB_X, 256>();
        if (!last && elect_one()) load_chunk(sb + R_GB + w * 4096, s + 1, g2, bars + B_FB);
      }
      TRACE(8);
      mbar_wait(bars + B_FA, 1);
      TRACE(11);
    }
    if (has_wo) {
      float* rslot = SLOT(s);
      uint32_t ob[4][4];
      float c[3][4];
      if (WG == 1) {
#pragma unroll
        for (int i = 0; i < 3; i++) ldsm4t(wa[i], woa + i * 4096);
        bar_sync<NB_D, 256>();
      }
      ldsm4t(ob[0], oxa);
      __syncwarp();
#pragma unroll
      for (int k = 0; k < 8; k++) {
        uint32_t nx[3][4];
        if ((k & 1) == 0 && k < 6) { ldsm4t(ob[(k >> 1) + 1], oxa + ((k >> 1) + 1) * 512); __syncwarp(); }
#pragma unroll
        for (int i = 0; i < 3; i++) {
          const uint32_t* o = ob[k >> 1] + (k & 1) * 2;
          if (k < 7) { ldsm4t(nx[i], woa + i * 4096 + (k + 1) * 512); if (i == 2) __syncwarp(); }
          if (k == 0) hmma0(c[i], wa[i][0], wa[i][1], wa[i][2], wa[i][3], o[0], o[1]);
          else hmma(c[i], wa[i][0], wa[i][1], wa[i][2], wa[i][3], o[0], o[1]);
#pragma unroll
          for (int q = 0; q < 4; q++) if (k < 7) wa[i][q] = nx[i][q];
        }
        if (k == ND_K && WG == 0) bar_arrive<NB_D, 256>();
      }
      const float* cv = &c[0][0];
      uint32_t r[6];
#pragma unroll
      for (int j = 0; j < 6; j++) r[j] = pack2(cv[2 * j], cv[2 * j + 1]);
      asm volatile("{\n.reg .pred p;\nsetp.lt.s32 p, %8, 0;\n@p bra.uni SKIP;\n"
                   "red.relaxed.gpu.global.add.noftz.v4.bf16x2 [%0], {%1, %2, %3, %7};\n"
                   "red.relaxed.gpu.global.add.noftz.v4.bf16x2 [%0+1024], {%4, %5, %6, %7};\nSKIP:\n}"
                   :: "l"(rslot), "r"(r[0]), "r"(r[1]), "r"(r[2]), "r"(r[3]), "r"(r[4]), "r"(r[5]), "r"(0x3f800000), "r"(s) : "memory");
    } else {
      bar_arrive<NB_D, 256>();
      if ((s & 3) == 0) {
        fence_gpu();
        if (s > 0 && elect_one()) red_add_u32(&g_flags[FL_ATT + 2 * (s - 4)], 1);
      }
      if (PFD && head < 8 && (PFD > 90 || s + PFD < NSEG) && elect_one())
        asm volatile("cp.async.bulk.prefetch.L2.global [%0], 4096;" :: "l"(g_h + (size_t)((PFD > 90 ? 0 : s + PFD) * 16 + head * 2 + rank) * 4096) : "memory");
      if (rank == 0 || head < 16)
        reinterpret_cast<uint4*>(g_slot)[((s + CLR_D) & 3) * 3072 + ((s + CLR_D) & 4) * 8 + rank * 2048 + head * 64 + opaque32(lane)] = make_uint4(0, 0, 0, 0);
    }
    const uint32_t t_red = clk32();
    uint32_t v[8];
    const float* slot = SLOT(s);
    TRACE(13);
    if (WG == 0) {
      if (!isC) {
        const int ln = opaque32(lane), kg = w - (ln >> 3);
        const uint32_t r16 = sb + R_P + w * 768 + (ln & 7) * 16;
        const uint32_t ta = r16 + (kg >= 0 ? kg * 128 : 640);
        const int dg = (ln >> 2) - 2 * (ln & 3);
        const uint32_t keep = dg > 0 ? 0xffffffffu : dg == 0 ? 0x0000ffffu : 0u;
        mbar_wait(bars + B_TS, par);
        uint32_t x[6], y[4];
        ldsm4t(x, ta); ldsm4t(y, ta + 3072); ldsm2t(x + 4, r16 + 512 + ((ln >> 3) & 1) * 3072);
#pragma unroll
        for (int j = 0; j < 5; j++) x[j] = hadd2(x[j], j < 4 ? y[j] : x[5]);
        x[0] = (x[0] & keep) | (0xff80ff80u & ~keep);
        float sv[10];
        exp10(sv, x);
        float sum = (((sv[0] + sv[1]) + (sv[2] + sv[3])) + ((sv[4] + sv[5]) + (sv[6] + sv[7]))) + (sv[8] + sv[9]);
        sum += __shfl_xor_sync(0xffffffffu, sum, 1);
        sum += __shfl_xor_sync(0xffffffffu, sum, 2);
        const float inv = rcp(sum);
#pragma unroll
        for (int j = 0; j < 5; j++) x[j] = pack2(sv[2 * j] * inv, sv[2 * j + 1] * inv);
        stsm4(r16 + (kg & 3) * 128, x);
        sts32(sb + ln * 4 + w * 768 + R_P + 512, x[4]);
        fence_async_smem();
        bar_arrive<NB_P, 256>();
      }
      while (clk32() - t_red < POLL_DELAY) {}
      load_red(v, slot);
      bar_sync<NB_E, 256>();
    } else {
      mbar_wait(bars + B_FB, 1);
    }
    TRACE(14);
    float ao[16];
    if (WG == 1) zero_regs<16>(ao);
    WG_FENCE();
#pragma unroll
    for (int k = 0; k < 32; k++) {
      if (WG == 0 && k == 16) WG_COMMIT();
      wg_rs32<1>(acc, W[16 + k][0], W[16 + k][1], W[16 + k][2], W[16 + k][3], dsc.tok[k]);
    }
    WG_COMMIT();
    TRACE(12);
    if (WG == 1) {
      if (!isC) {
        constexpr uint64_t dP = mkdesc(0x400 + R_P, 128, 768, 0);
        const uint64_t dV = mkdesc(0x400 + R_VT, 128, 512, 0) + rank * 256, dM = mkdesc(0x400 + R_VM, 0, 128, 0) + rank * 64;
        bar_sync<NB_P, 256>();
        WG_FENCE();
        wg_ss32<0>(ao, dV, dP); wg_ss32<0>(ao, dV + 16, dP + 16); wg_ss32<0>(ao, dM, dP + 32);
        WG_COMMIT();
      }
      bar_arrive<NB_E, 256>();
      if (elect_one()) mbar_expect(bars + B_XS + 8 * w, arm_bytes);
      while (clk32() - t_red < POLL_DELAY1) {}
      load_red(v, slot);
      bar_arrive<NB_W0, 128>();
    } else {
      WG_WAIT(1);
      bar_arrive<NB_F, 256>();
      sched_fence(head, 100);
      v[3] = opaque32(v[3]);
      const uint32_t tries = finish_red(v, slot);
      forward(std::integral_constant<int, 0>(), v, s, tries);
      TRACE(16);
    }
    WG_WAIT(0);
    reg_fence<16>(acc);
    if (WG == 0) bar_arrive<NB_G, 256>();
    TRACE(15);
    {
      uint32_t pq[8];
#pragma unroll
      for (int j = 0; j < 8; j++) pq[j] = pack2(acc[2 * j], acc[2 * j + 1]);
      if (WG == 1) {
        reg_fence<16>(ao);
#pragma unroll
        for (int j = 0; j < 8; j++) pk[j] = pack2(ao[2 * j], ao[2 * j + 1]);
      }
      if (!isC) {
        const uint32_t q = L4 + w * 256 + R_QK + WG * 5120;
#pragma unroll
        for (int j = 0; j < 8; j++) sts32(q + (j >> 1) * 1024 + (j & 1) * 128, pq[j]);
        if (WG == 1 && !ATT_LATE && s >= 0) store_att(s);
      } else {
        const uint32_t a = LV + warp * 1024;
        stsm4(a, pq); stsm4(a + 256, pq + 4);
      }
    }
    TRACE(17);
    if (WG == 1) {
      auto refill = [&]() {
        bar_sync<NB_F, 256>();
        if (s < NSEG - 2 && elect_one()) load_chunk(sb + R_GA + w * 4096, s + 2, 12 + w, bars + B_FA);
      };
      if (RF_FIRST) refill();
      if (has_wo) { v[3] = opaque32(v[3]); const uint32_t tries = finish_red(v, slot); forward(std::integral_constant<int, 1>(), v, s, tries); }
      if (!RF_FIRST) refill();
      TRACE(16);
    }
    if (isC && V_FENCE) { fence_async_smem(); __syncwarp(); }
    TRACE(18);
  }
  {
    constexpr uint32_t par = NSEG & 1;
    if (WG == 1 || isC) {
      float c[NCH][4], m[4];
      uint32_t b[3][6];
      const uint32_t ma = L16, m8 = L8;
#pragma unroll
      for (int i = 0; i < 18; i++) {
        if (i < 16) {
          if (i % 4 == 0) mbar_wait(bars + B_MB + (i / 4) * 8, par ^ 1);
          if (i < 12) { lds128(b[i % 3], ma + R_M1 + i * 768); lds64(b[i % 3] + 4, m8 + R_M1 + 512 + i * 768); }
          else { ldsm4(b[i % 3], ma + R_M2 + 4096 + (i - 12) * 768); ldsm2(b[i % 3] + 4, ma + R_M2 + 4096 + 512 + (i - 12) * 768); }
          if (i == CX_I && isC) send_vt();
          __syncwarp();
        }
        if (i >= 2) {
          const int j = i - 2;
#pragma unroll
          for (int q = 0; q < 3; q++) {
            const uint32_t* f = W[3 * j + q];
            if (3 * j + q < NCH) hmma0(c[3 * j + q], f[0], f[1], f[2], f[3], b[j % 3][2 * q], b[j % 3][2 * q + 1]);
            else hmma(c[(3 * j + q) % NCH], f[0], f[1], f[2], f[3], b[j % 3][2 * q], b[j % 3][2 * q + 1]);
          }
        }
      }
#pragma unroll
      for (int j = 0; j < 4; j++) m[j] = NCH == 3 ? (c[0][j] + c[1][j]) + c[2][j] : (c[0][j] + c[1][j]) + (c[2][j] + c[NCH - 1][j]);
      if (isC) bar_sync<NB_H, 256>();
      WG_FENCE();
#pragma unroll
      for (int k = 0; k < 16; k++) wg_ss8(m, dsc.tail_a[WG * 16 + k], dsc.tail_b[k] + 1024);
      WG_COMMIT();
      const uint32_t a = opaque32(L4 + w * 256 + (isC ? WG * 1024 + R_VM : R_QK + 4096 + WG * 5120));
      WG_WAIT(0);
      reg_fence<4>(m);
      const uint32_t p0 = pack2(m[0], m[1]), p1 = pack2(m[2], m[3]);
      if (isC) {
        st_async1(a + to1, p0, bars + B_VM + to1); st_async1(a + to1 + 128, p1, bars + B_VM + to1);
        st_async1(a + to2, p0, bars + B_VM + to2); st_async1(a + to2 + 128, p1, bars + B_VM + to2);
      } else {
        sts32(a, p0); sts32(a + 128, p1);
      }
    }
    if (WG == 1) bar_sync<NB_G, 256>();
    if (isC) {
      asm volatile("barrier.cluster.arrive.relaxed.aligned;" ::: "memory");
    } else if (WG == 1) {
      constexpr uint64_t dQ = mkdesc(0x400 + R_QK, 128, 1024, 0), dK = mkdesc(0x400 + R_QK + 5120, 128, 1024, 0);
      float sc[16];
      zero_regs<16>(sc);
      fence_async_smem();
      bar_sync<NB_B, 256>();
      WG_FENCE();
#pragma unroll
      for (int k = 0; k < 4; k++) wg_ss32<1>(sc, dK + k * 16, dQ + k * 16);
      WG_COMMIT();
      const uint32_t top = rank == 0 ? to2 : to1, e = L4 + R_P + w * 256;
      WG_WAIT(0);
      reg_fence<16>(sc);
      if (w < 3) {
#pragma unroll
        for (int j = 0; j < 8; j++) {
          if ((j & 1) ? (j > 1 && (w == 0 || (w == 1 && j == 7))) : (j >= 4 || w != 1)) {
            const uint32_t t = pack2(sc[2 * j], sc[2 * j + 1]), o = (j >> 1) * 768 + (j & 1) * 128;
            st_async1(e + top + 3072 + o, t, bars + top + B_TS);
            sts32(e + o, t);
          }
        }
        __syncwarp();
        if (elect_one()) mbar_arrive(bars + B_TS);
      }
      constexpr uint64_t dP = mkdesc(0x400 + R_P, 128, 768, 0);
      const uint64_t dV = mkdesc(0x400 + R_VT, 128, 512, 0) + rank * 256, dM = mkdesc(0x400 + R_VM, 0, 128, 0) + rank * 64;
      float ao[16];
      zero_regs<16>(ao);
      mbar_wait(bars + B_VT, par);
      mbar_wait(bars + B_VM, par);
      asm volatile("barrier.cluster.arrive.relaxed.aligned;" ::: "memory");
      bar_sync<NB_P, 256>();
      WG_FENCE();
      wg_ss32<0>(ao, dV, dP); wg_ss32<0>(ao, dV + 16, dP + 16); wg_ss32<0>(ao, dM, dP + 32);
      WG_COMMIT();
      WG_WAIT(0);
      reg_fence<16>(ao);
#pragma unroll
      for (int j = 0; j < 8; j++) pk[j] = pack2(ao[2 * j], ao[2 * j + 1]);
      store_att(NSEG - 1);
      bar_sync<NB_C, 128>();
      if (w == 0 && elect_one()) { fence_gpu(); red_add_u32(&g_flags[FL_ATT + 8 * 15], 1); }
    } else {
      fence_async_smem();
      bar_arrive<NB_B, 256>();
      const int ln = opaque32(lane), kg = w - (ln >> 3);
      const uint32_t r16 = sb + R_P + w * 768 + (ln & 7) * 16;
      const uint32_t ta = r16 + (kg >= 0 ? kg * 128 : 640);
      const int dg = (ln >> 2) - 2 * (ln & 3);
      const uint32_t keep = dg > 0 ? 0xffffffffu : dg == 0 ? 0x0000ffffu : 0u;
      mbar_wait(bars + B_TS, par);
      asm volatile("barrier.cluster.arrive.relaxed.aligned;" ::: "memory");
      uint32_t x[6], y[4];
      ldsm4t(x, ta); ldsm4t(y, ta + 3072); ldsm2t(x + 4, r16 + 512 + ((ln >> 3) & 1) * 3072);
#pragma unroll
      for (int j = 0; j < 5; j++) x[j] = hadd2(x[j], j < 4 ? y[j] : x[5]);
      x[0] = (x[0] & keep) | (0xff80ff80u & ~keep);
      float sv[10];
      exp10(sv, x);
      float sum = (((sv[0] + sv[1]) + (sv[2] + sv[3])) + ((sv[4] + sv[5]) + (sv[6] + sv[7]))) + (sv[8] + sv[9]);
      sum += __shfl_xor_sync(0xffffffffu, sum, 1);
      sum += __shfl_xor_sync(0xffffffffu, sum, 2);
      const float inv = rcp(sum);
#pragma unroll
      for (int j = 0; j < 5; j++) x[j] = pack2(sv[2 * j] * inv, sv[2 * j + 1] * inv);
      stsm4(r16 + (kg & 3) * 128, x);
      sts32(sb + ln * 4 + w * 768 + R_P + 512, x[4]);
      fence_async_smem();
      bar_arrive<NB_P, 256>();
    }
    asm volatile("barrier.cluster.wait.aligned;" ::: "memory");
  }
#undef L16
#undef L8
#undef L4
#undef SLOT
#undef LV
}

__global__ void __cluster_dims__(3, 1, 1) __launch_bounds__(256, 1)
kernel_R(const __grid_constant__ CUtensorMap tmq, const __grid_constant__ CUtensorMap tmk, const __grid_constant__ CUtensorMap tmv,
         const __grid_constant__ CUtensorMap tmo, const __grid_constant__ CUtensorMap tmm, const __nv_bfloat16* __restrict__ x,
         const __nv_bfloat16* __restrict__ mem0, const __nv_bfloat16* __restrict__ cvec, const __grid_constant__ RDesc dsc) {
  extern __shared__ __align__(1024) uint8_t smem[];
  const uint32_t sb = smem_u32(smem);
  uint32_t rank; asm("mov.u32 %0, %%cluster_ctarank;" : "=r"(rank));
  rank = __shfl_sync(0xffffffffu, rank, 0);
  const int cta = blockIdx.x, head = __shfl_sync(0xffffffffu, cta / 3, 0);
  const int tid = threadIdx.x, lane = tid & 31;
  const int warp = __shfl_sync(0xffffffffu, tid >> 5, 0);
  const int wg = warp >> 2, w = warp & 3;
  const uint32_t bars = sb + R_BAR;
  const CUtensorMap* tmw = rank == 2 ? &tmv : (wg == 0 ? &tmq : &tmk);
  const int fcol = head * 128 + (rank == 2 ? wg * 64 : (int)rank * 64);

  asm volatile("griddepcontrol.launch_dependents;");
  uint32_t W[48][4];
  {
    if (sb != (rank << 24) + 0x400) __trap();
    if (tid == 0) {
      sts64(bars + 248, rank, head);
      mbar_init(bars + B_MB, 4); mbar_init(bars + B_MB + 8, 1); mbar_init(bars + B_MB + 16, 1); mbar_init(bars + B_MB + 24, SELF_STAS ? 1 : rank == 2 ? 5 : 4);
      for (int i = B_XS; i <= B_X; i += 8) mbar_init(bars + i, i == B_FA || i == B_FB || (i == B_TS && rank < 2) ? 4 : 1);
      asm volatile("fence.mbarrier_init.release.cluster;" ::: "memory");
      fence_async_smem();
    }
    __syncthreads();
    asm volatile("barrier.cluster.arrive.relaxed.aligned;" ::: "memory");
    TS(0);
    const int nwm = rank == 0 ? 6 : 5, wm0 = rank == 0 ? 0 : 5 * rank + 1, nrg = cta < 64 ? 3 : 2;
    if (elect_one()) {
      if (warp == 0) { mbar_expect(bars + B_WM, nwm * 8192); mbar_expect(bars + B_X, nrg * 16384); }
      if (warp < nwm) tma2d_once(sb + R_GA + warp * 8192, &tmm, head * 64, (wm0 + warp) * 64, bars + B_WM);
#pragma unroll 1
      for (int r = 0; r < nrg; r++) bulk_g2s(sb + R_TAIL + (r * 8 + warp) * 2064, x + (size_t)((cta + 96 * r) * 8 + warp) * D_, 2048, bars + B_X);
      if (w == 0) mbar_expect(bars + B_STG + wg * 16, 49152);
      if (w < 2) tma2d_once(sb + R_WO + wg * 49152 + w * 8192, tmw, fcol, rot_chunk(w, rank) * 64, bars + B_STG + wg * 16);
    }
    float* scr = reinterpret_cast<float*>(smem + R_VT);
#pragma unroll 1
    for (int i = tid; i < nwm * 64; i += 256) {
      const float c = __bfloat162float(cvec[wm0 * 64 + i]);
      scr[i] = __bfloat162float(__float2bfloat16(c / (1.f + __expf(-c))));
    }
    if (tid < 128) {
      uint32_t e[4] = {0u, 0u, 0u, 0u};
      if (cta >= 72 && (tid & 32)) {
        const uint16_t* mp = reinterpret_cast<const uint16_t*>(mem0) + 2 * (lane & 3) * D_ + (lane >> 2);
#pragma unroll
        for (int q = 0; q < 3; q++) {
          const int n = 3 * (tid >> 6) + q, col = wo_tile(3 * (cta & 7) + (n >> 1), (cta - 72) >> 3) * 16 + 8 * (n & 1);
          e[q] = mp[col] | (uint32_t)mp[col + D_] << 16;
        }
        e[3] = 0x42000000u;
      }
      reinterpret_cast<uint4*>(g_slot)[cta * 128 + tid] = make_uint4(e[0], e[1], e[2], e[3]);
    }
    __syncthreads();
    TS(1);
    mbar_wait_safe(bars + B_WM, 0);
    if (elect_one()) tma2d_once(sb + R_WO + wg * 49152 + (2 + w) * 8192, tmw, fcol, rot_chunk(2 + w, rank) * 64, bars + B_STG + wg * 16);
    {
      float a[8];
#pragma unroll
      for (int j = 0; j < 8; j++) a[j] = 0.f;
#pragma unroll 2
      for (int i = 0; i < 2 * nwm; i++) {
        uint32_t u[4];
        lds128(u, sb + R_GA + i * 4096 + tid * 16);
        const float sc = scr[i * 32 + (tid >> 3)];
#pragma unroll
        for (int j = 0; j < 4; j++) { a[2 * j] += sc * bf_lo(u[j]); a[2 * j + 1] += sc * bf_hi(u[j]); }
      }
#pragma unroll
      for (int j = 0; j < 8; j++) { a[j] += __shfl_xor_sync(0xffffffffu, a[j], 8); a[j] += __shfl_xor_sync(0xffffffffu, a[j], 16); }
      if (lane < 8) {
        sts128(sb + R_VT + 1536 + warp * 256 + lane * 32, __float_as_uint(a[0]), __float_as_uint(a[1]), __float_as_uint(a[2]), __float_as_uint(a[3]));
        sts128(sb + R_VT + 1552 + warp * 256 + lane * 32, __float_as_uint(a[4]), __float_as_uint(a[5]), __float_as_uint(a[6]), __float_as_uint(a[7]));
      }
    }
    __syncthreads();
    TS(2);
    if (warp == 7) {
      float t0 = 0.f, t1 = 0.f;
#pragma unroll
      for (int i = 0; i < 8; i++) { float t[2]; lds64f(t, sb + R_VT + 1536 + i * 256 + lane * 8); t0 += t[0]; t1 += t[1]; }
      reinterpret_cast<float2*>(g_modp + rank * 2048 + head * 64)[lane] = make_float2(t0, t1);
      fence_gpu();
      __syncwarp();
      if (lane == 0) red_add_u32(&g_flags[FL_S1], 1);
      __syncwarp();
    }
    mbar_wait_safe(bars + B_X, 0);
#pragma unroll 1
    for (int r = 0; r < nrg; r++) {
      float f[32];
#pragma unroll
      for (int i = 0; i < 4; i++) {
        uint32_t u[4];
        lds128(u, sb + R_TAIL + (r * 8 + warp) * 2064 + i * 512 + lane * 16);
#pragma unroll
        for (int j = 0; j < 4; j++) { f[8 * i + 2 * j] = bf_lo(u[j]); f[8 * i + 2 * j + 1] = bf_hi(u[j]); }
      }
      float t = 0.f;
#pragma unroll
      for (int i = 0; i < 32; i++) t += f[i];
#pragma unroll
      for (int o = 1; o < 32; o <<= 1) t += __shfl_xor_sync(0xffffffffu, t, o);
      const float mean = t * (1.f / D_);
      t = 0.f;
#pragma unroll
      for (int i = 0; i < 32; i++) t = fmaf(f[i] - mean, f[i] - mean, t);
#pragma unroll
      for (int o = 1; o < 32; o <<= 1) t += __shfl_xor_sync(0xffffffffu, t, o);
      const float rstd = rsqrtf(t * (1.f / D_) + 1e-5f);
      if (lane == 0) sts64(sb + R_VT + 3584 + (r * 8 + warp) * 8, __float_as_uint(rstd), __float_as_uint(-mean * rstd));
    }
    TS(3);
    if (w < PF1 && elect_one()) tma2d_prefetch(tmw, fcol, rot_chunk(6 + w, rank) * 64);
    if (tid == 0) wait_flag(&g_flags[FL_S1], 96);
    __syncthreads();
    TS(4);
    {
      float4 p[6];
#pragma unroll
      for (int i = 0; i < 6; i++) p[i] = __ldcg(reinterpret_cast<const float4*>(g_modp + (i >> 1) * 2048) + 2 * tid + (i & 1));
      if (w < PF2 && elect_one()) tma2d_prefetch(tmw, fcol, (9 + w) * 64);
      sts128(sb + R_VT + 5120 + tid * 16, pack2(p[0].x + p[2].x + p[4].x, p[0].y + p[2].y + p[4].y), pack2(p[0].z + p[2].z + p[4].z, p[0].w + p[2].w + p[4].w),
             pack2(p[1].x + p[3].x + p[5].x, p[1].y + p[3].y + p[5].y), pack2(p[1].z + p[3].z + p[5].z, p[1].w + p[3].w + p[5].w));
    }
    __syncthreads();
#pragma unroll 2
    for (int it = 0; it < 4 * nrg; it++) {
      const int r = it >> 2, rg = cta + 96 * r, c = 16 * warp + (lane >> 3) + 4 * (it & 3);
      uint32_t a[4], b[4], u[4], o[4];
      float t[2];
      lds128(u, sb + R_TAIL + (r * 8 + (lane & 7)) * 2064 + c * 16);
      lds128(a, sb + R_VT + 5120 + c * 16); lds128(b, sb + R_VT + 7168 + c * 16);
      lds64f(t, sb + R_VT + 3584 + (r * 8 + (lane & 7)) * 8);
#pragma unroll
      for (int j = 0; j < 4; j++)
        o[j] = pack2(fmaf(fmaf(bf_lo(u[j]), t[0], t[1]), 1.f + bf_lo(b[j]), bf_lo(a[j])), fmaf(fmaf(bf_hi(u[j]), t[0], t[1]), 1.f + bf_hi(b[j]), bf_hi(a[j])));
      *reinterpret_cast<uint4*>(g_h + (size_t)(rg >> 2) * 65536 + (lane & 7) * 16 + (c & 7) * 128 +
                                (c < 96 ? (c >> 3) * 4096 + (rg & 3) * 1024 : 49152 + (rg & 3) * 4096 + ((c >> 3) - 12) * 1024)) =
          make_uint4(o[0], o[1], o[2], o[3]);
    }
    TS(5);
    __syncthreads();
    TS(6);
    if (w < PF3 && elect_one()) tma2d_once(sb + R_TAIL + warp * 8192, tmw, fcol, 768 + w * 64, bars + B_TAIL);
    if (warp == 3 && lane == 0) { fence_gpu(); red_add_u32(&g_flags[FL_S2], 1); }
    __syncwarp();

    const uint32_t a0 = opaque32(sb + R_WO + wg * 49152 + ((lane >> 4) * 8 + (lane & 7)) * 128 + (((2 * w + ((lane >> 3) & 1)) ^ (lane & 7)) << 4));
    mbar_wait_safe(bars + B_STG + wg * 16, 0);
    TS(7);
#pragma unroll
    for (int i = 0; i < 24; i++) ldsm4t(W[i], a0 + i * 2048);
    if (tid == 0) wait_flag(&g_flags[FL_S2], 96);
    __syncthreads();
    asm volatile("fence.proxy.async.global;" ::: "memory");
    if (elect_one()) {
      if (wg == 0) load_chunk(sb + R_GA + w * 4096, 0, 12 + w, bars + B_FA);
      if (w == 0) mbar_expect(bars + B_STG + wg * 16 + 8, 49152);
#pragma unroll 1
      for (int c = w; c < 6; c += 4) tma2d_once(sb + R_WO + wg * 49152 + c * 8192, tmw, fcol, rot_chunk(6 + c, rank) * 64, bars + B_STG + wg * 16 + 8);
      if (warp == 0) mbar_expect(bars + B_TAIL, 65536);
      if (w >= PF3) tma2d_once(sb + R_TAIL + warp * 8192, tmw, fcol, 768 + w * 64, bars + B_TAIL);
      if (wg == 1) mbar_expect(bars + B_XS + 8 * w, w == 2 ? 0 : arm_size(w, rank == 2));
#pragma unroll 1
      for (int i = warp; i < PF4; i += 8) tma2d_prefetch(&tmo, 16 * wo_tile(i, rank), head * 128);
    }
    TS(8);
    mbar_wait_safe(bars + B_STG + wg * 16 + 8, 0);
    TS(9);
#pragma unroll
    for (int i = 0; i < 24; i++) ldsm4t(W[24 + i], a0 + i * 2048);
    __syncthreads();
    if (elect_one()) {
      const int n = rank == 2 ? 22 : 21;
      if (warp == 0) mbar_expect(bars + B_WO, n * 4096);
#pragma unroll 1
      for (int i = warp; i < n; i += 8) tma2d(sb + R_WO + i * 4096, &tmo, 16 * wo_tile(i, rank), head * 128, bars + B_WO);
    }
    sts32(sb + R_P + warp * 768 + 640 + lane * 4, wg == 0 ? 0u : 0xff80ff80u);
    mbar_wait_safe(bars + B_TAIL, 0);
    if (GO_EARLY && cta == GO_EARLY - 1 && tid == 0) red_add_u32(&g_flags[FL_GO], 1);
    asm volatile("barrier.cluster.wait.aligned;\nbarrier.cluster.arrive.relaxed.aligned;\nbarrier.cluster.wait.aligned;" ::: "memory");
  }
  uint32_t rh[2];
  lds64(rh, bars + 248);
  rh[0] = __shfl_sync(0xffffffffu, rh[0], 0); rh[1] = __shfl_sync(0xffffffffu, rh[1], 0);
  if (wg == 0) r_main<0>(W, dsc, rh[1], rh[0], lane, w);
  else r_main<1>(W, dsc, rh[1], rh[0], lane, w);
}

template <int TA, bool FIRST> __device__ __forceinline__ void wg_ss256(float* d, uint64_t a, uint64_t b) {
  if (FIRST)
    asm volatile("wgmma.mma_async.sync.aligned.m64n256k16.f32.bf16.bf16 {%0,%1,%2,%3,%4,%5,%6,%7,%8,%9,%10,%11,%12,%13,%14,%15,%16,%17,%18,%19,%20,%21,%22,%23,%24,%25,%26,%27,%28,%29,%30,%31,%32,%33,%34,%35,%36,%37,%38,%39,%40,%41,%42,%43,%44,%45,%46,%47,%48,%49,%50,%51,%52,%53,%54,%55,%56,%57,%58,%59,%60,%61,%62,%63,%64,%65,%66,%67,%68,%69,%70,%71,%72,%73,%74,%75,%76,%77,%78,%79,%80,%81,%82,%83,%84,%85,%86,%87,%88,%89,%90,%91,%92,%93,%94,%95,%96,%97,%98,%99,%100,%101,%102,%103,%104,%105,%106,%107,%108,%109,%110,%111,%112,%113,%114,%115,%116,%117,%118,%119,%120,%121,%122,%123,%124,%125,%126,%127}, %128, %129, 0, 1, 1, %130, 1;"
               : "=f"(d[0]), "=f"(d[1]), "=f"(d[2]), "=f"(d[3]), "=f"(d[4]), "=f"(d[5]), "=f"(d[6]), "=f"(d[7]),
                 "=f"(d[8]), "=f"(d[9]), "=f"(d[10]), "=f"(d[11]), "=f"(d[12]), "=f"(d[13]), "=f"(d[14]), "=f"(d[15]),
                 "=f"(d[16]), "=f"(d[17]), "=f"(d[18]), "=f"(d[19]), "=f"(d[20]), "=f"(d[21]), "=f"(d[22]), "=f"(d[23]),
                 "=f"(d[24]), "=f"(d[25]), "=f"(d[26]), "=f"(d[27]), "=f"(d[28]), "=f"(d[29]), "=f"(d[30]), "=f"(d[31]),
                 "=f"(d[32]), "=f"(d[33]), "=f"(d[34]), "=f"(d[35]), "=f"(d[36]), "=f"(d[37]), "=f"(d[38]), "=f"(d[39]),
                 "=f"(d[40]), "=f"(d[41]), "=f"(d[42]), "=f"(d[43]), "=f"(d[44]), "=f"(d[45]), "=f"(d[46]), "=f"(d[47]),
                 "=f"(d[48]), "=f"(d[49]), "=f"(d[50]), "=f"(d[51]), "=f"(d[52]), "=f"(d[53]), "=f"(d[54]), "=f"(d[55]),
                 "=f"(d[56]), "=f"(d[57]), "=f"(d[58]), "=f"(d[59]), "=f"(d[60]), "=f"(d[61]), "=f"(d[62]), "=f"(d[63]),
                 "=f"(d[64]), "=f"(d[65]), "=f"(d[66]), "=f"(d[67]), "=f"(d[68]), "=f"(d[69]), "=f"(d[70]), "=f"(d[71]),
                 "=f"(d[72]), "=f"(d[73]), "=f"(d[74]), "=f"(d[75]), "=f"(d[76]), "=f"(d[77]), "=f"(d[78]), "=f"(d[79]),
                 "=f"(d[80]), "=f"(d[81]), "=f"(d[82]), "=f"(d[83]), "=f"(d[84]), "=f"(d[85]), "=f"(d[86]), "=f"(d[87]),
                 "=f"(d[88]), "=f"(d[89]), "=f"(d[90]), "=f"(d[91]), "=f"(d[92]), "=f"(d[93]), "=f"(d[94]), "=f"(d[95]),
                 "=f"(d[96]), "=f"(d[97]), "=f"(d[98]), "=f"(d[99]), "=f"(d[100]), "=f"(d[101]), "=f"(d[102]), "=f"(d[103]),
                 "=f"(d[104]), "=f"(d[105]), "=f"(d[106]), "=f"(d[107]), "=f"(d[108]), "=f"(d[109]), "=f"(d[110]), "=f"(d[111]),
                 "=f"(d[112]), "=f"(d[113]), "=f"(d[114]), "=f"(d[115]), "=f"(d[116]), "=f"(d[117]), "=f"(d[118]), "=f"(d[119]),
                 "=f"(d[120]), "=f"(d[121]), "=f"(d[122]), "=f"(d[123]), "=f"(d[124]), "=f"(d[125]), "=f"(d[126]), "=f"(d[127])
               : "l"(a), "l"(b), "n"(TA));
  else
    asm volatile("wgmma.mma_async.sync.aligned.m64n256k16.f32.bf16.bf16 {%0,%1,%2,%3,%4,%5,%6,%7,%8,%9,%10,%11,%12,%13,%14,%15,%16,%17,%18,%19,%20,%21,%22,%23,%24,%25,%26,%27,%28,%29,%30,%31,%32,%33,%34,%35,%36,%37,%38,%39,%40,%41,%42,%43,%44,%45,%46,%47,%48,%49,%50,%51,%52,%53,%54,%55,%56,%57,%58,%59,%60,%61,%62,%63,%64,%65,%66,%67,%68,%69,%70,%71,%72,%73,%74,%75,%76,%77,%78,%79,%80,%81,%82,%83,%84,%85,%86,%87,%88,%89,%90,%91,%92,%93,%94,%95,%96,%97,%98,%99,%100,%101,%102,%103,%104,%105,%106,%107,%108,%109,%110,%111,%112,%113,%114,%115,%116,%117,%118,%119,%120,%121,%122,%123,%124,%125,%126,%127}, %128, %129, 1, 1, 1, %130, 1;"
               : "+f"(d[0]), "+f"(d[1]), "+f"(d[2]), "+f"(d[3]), "+f"(d[4]), "+f"(d[5]), "+f"(d[6]), "+f"(d[7]),
                 "+f"(d[8]), "+f"(d[9]), "+f"(d[10]), "+f"(d[11]), "+f"(d[12]), "+f"(d[13]), "+f"(d[14]), "+f"(d[15]),
                 "+f"(d[16]), "+f"(d[17]), "+f"(d[18]), "+f"(d[19]), "+f"(d[20]), "+f"(d[21]), "+f"(d[22]), "+f"(d[23]),
                 "+f"(d[24]), "+f"(d[25]), "+f"(d[26]), "+f"(d[27]), "+f"(d[28]), "+f"(d[29]), "+f"(d[30]), "+f"(d[31]),
                 "+f"(d[32]), "+f"(d[33]), "+f"(d[34]), "+f"(d[35]), "+f"(d[36]), "+f"(d[37]), "+f"(d[38]), "+f"(d[39]),
                 "+f"(d[40]), "+f"(d[41]), "+f"(d[42]), "+f"(d[43]), "+f"(d[44]), "+f"(d[45]), "+f"(d[46]), "+f"(d[47]),
                 "+f"(d[48]), "+f"(d[49]), "+f"(d[50]), "+f"(d[51]), "+f"(d[52]), "+f"(d[53]), "+f"(d[54]), "+f"(d[55]),
                 "+f"(d[56]), "+f"(d[57]), "+f"(d[58]), "+f"(d[59]), "+f"(d[60]), "+f"(d[61]), "+f"(d[62]), "+f"(d[63]),
                 "+f"(d[64]), "+f"(d[65]), "+f"(d[66]), "+f"(d[67]), "+f"(d[68]), "+f"(d[69]), "+f"(d[70]), "+f"(d[71]),
                 "+f"(d[72]), "+f"(d[73]), "+f"(d[74]), "+f"(d[75]), "+f"(d[76]), "+f"(d[77]), "+f"(d[78]), "+f"(d[79]),
                 "+f"(d[80]), "+f"(d[81]), "+f"(d[82]), "+f"(d[83]), "+f"(d[84]), "+f"(d[85]), "+f"(d[86]), "+f"(d[87]),
                 "+f"(d[88]), "+f"(d[89]), "+f"(d[90]), "+f"(d[91]), "+f"(d[92]), "+f"(d[93]), "+f"(d[94]), "+f"(d[95]),
                 "+f"(d[96]), "+f"(d[97]), "+f"(d[98]), "+f"(d[99]), "+f"(d[100]), "+f"(d[101]), "+f"(d[102]), "+f"(d[103]),
                 "+f"(d[104]), "+f"(d[105]), "+f"(d[106]), "+f"(d[107]), "+f"(d[108]), "+f"(d[109]), "+f"(d[110]), "+f"(d[111]),
                 "+f"(d[112]), "+f"(d[113]), "+f"(d[114]), "+f"(d[115]), "+f"(d[116]), "+f"(d[117]), "+f"(d[118]), "+f"(d[119]),
                 "+f"(d[120]), "+f"(d[121]), "+f"(d[122]), "+f"(d[123]), "+f"(d[124]), "+f"(d[125]), "+f"(d[126]), "+f"(d[127])
               : "l"(a), "l"(b), "n"(TA));
}
template <int TA, bool FIRST> __device__ __forceinline__ void wg_ss128(float* d, uint64_t a, uint64_t b) {
  if (FIRST)
    asm volatile("wgmma.mma_async.sync.aligned.m64n128k16.f32.bf16.bf16 {%0,%1,%2,%3,%4,%5,%6,%7,%8,%9,%10,%11,%12,%13,%14,%15,%16,%17,%18,%19,%20,%21,%22,%23,%24,%25,%26,%27,%28,%29,%30,%31,%32,%33,%34,%35,%36,%37,%38,%39,%40,%41,%42,%43,%44,%45,%46,%47,%48,%49,%50,%51,%52,%53,%54,%55,%56,%57,%58,%59,%60,%61,%62,%63}, %64, %65, 0, 1, 1, %66, 1;"
               : "=f"(d[0]), "=f"(d[1]), "=f"(d[2]), "=f"(d[3]), "=f"(d[4]), "=f"(d[5]), "=f"(d[6]), "=f"(d[7]),
                 "=f"(d[8]), "=f"(d[9]), "=f"(d[10]), "=f"(d[11]), "=f"(d[12]), "=f"(d[13]), "=f"(d[14]), "=f"(d[15]),
                 "=f"(d[16]), "=f"(d[17]), "=f"(d[18]), "=f"(d[19]), "=f"(d[20]), "=f"(d[21]), "=f"(d[22]), "=f"(d[23]),
                 "=f"(d[24]), "=f"(d[25]), "=f"(d[26]), "=f"(d[27]), "=f"(d[28]), "=f"(d[29]), "=f"(d[30]), "=f"(d[31]),
                 "=f"(d[32]), "=f"(d[33]), "=f"(d[34]), "=f"(d[35]), "=f"(d[36]), "=f"(d[37]), "=f"(d[38]), "=f"(d[39]),
                 "=f"(d[40]), "=f"(d[41]), "=f"(d[42]), "=f"(d[43]), "=f"(d[44]), "=f"(d[45]), "=f"(d[46]), "=f"(d[47]),
                 "=f"(d[48]), "=f"(d[49]), "=f"(d[50]), "=f"(d[51]), "=f"(d[52]), "=f"(d[53]), "=f"(d[54]), "=f"(d[55]),
                 "=f"(d[56]), "=f"(d[57]), "=f"(d[58]), "=f"(d[59]), "=f"(d[60]), "=f"(d[61]), "=f"(d[62]), "=f"(d[63])
               : "l"(a), "l"(b), "n"(TA));
  else
    asm volatile("wgmma.mma_async.sync.aligned.m64n128k16.f32.bf16.bf16 {%0,%1,%2,%3,%4,%5,%6,%7,%8,%9,%10,%11,%12,%13,%14,%15,%16,%17,%18,%19,%20,%21,%22,%23,%24,%25,%26,%27,%28,%29,%30,%31,%32,%33,%34,%35,%36,%37,%38,%39,%40,%41,%42,%43,%44,%45,%46,%47,%48,%49,%50,%51,%52,%53,%54,%55,%56,%57,%58,%59,%60,%61,%62,%63}, %64, %65, 1, 1, 1, %66, 1;"
               : "+f"(d[0]), "+f"(d[1]), "+f"(d[2]), "+f"(d[3]), "+f"(d[4]), "+f"(d[5]), "+f"(d[6]), "+f"(d[7]),
                 "+f"(d[8]), "+f"(d[9]), "+f"(d[10]), "+f"(d[11]), "+f"(d[12]), "+f"(d[13]), "+f"(d[14]), "+f"(d[15]),
                 "+f"(d[16]), "+f"(d[17]), "+f"(d[18]), "+f"(d[19]), "+f"(d[20]), "+f"(d[21]), "+f"(d[22]), "+f"(d[23]),
                 "+f"(d[24]), "+f"(d[25]), "+f"(d[26]), "+f"(d[27]), "+f"(d[28]), "+f"(d[29]), "+f"(d[30]), "+f"(d[31]),
                 "+f"(d[32]), "+f"(d[33]), "+f"(d[34]), "+f"(d[35]), "+f"(d[36]), "+f"(d[37]), "+f"(d[38]), "+f"(d[39]),
                 "+f"(d[40]), "+f"(d[41]), "+f"(d[42]), "+f"(d[43]), "+f"(d[44]), "+f"(d[45]), "+f"(d[46]), "+f"(d[47]),
                 "+f"(d[48]), "+f"(d[49]), "+f"(d[50]), "+f"(d[51]), "+f"(d[52]), "+f"(d[53]), "+f"(d[54]), "+f"(d[55]),
                 "+f"(d[56]), "+f"(d[57]), "+f"(d[58]), "+f"(d[59]), "+f"(d[60]), "+f"(d[61]), "+f"(d[62]), "+f"(d[63])
               : "l"(a), "l"(b), "n"(TA));
}
template <int TA, bool FIRST> __device__ __forceinline__ void wg_ss64(float* d, uint64_t a, uint64_t b) {
  if (FIRST)
    asm volatile("wgmma.mma_async.sync.aligned.m64n64k16.f32.bf16.bf16 {%0,%1,%2,%3,%4,%5,%6,%7,%8,%9,%10,%11,%12,%13,%14,%15,%16,%17,%18,%19,%20,%21,%22,%23,%24,%25,%26,%27,%28,%29,%30,%31}, %32, %33, 0, 1, 1, %34, 1;"
               : "=f"(d[0]), "=f"(d[1]), "=f"(d[2]), "=f"(d[3]), "=f"(d[4]), "=f"(d[5]), "=f"(d[6]), "=f"(d[7]),
                 "=f"(d[8]), "=f"(d[9]), "=f"(d[10]), "=f"(d[11]), "=f"(d[12]), "=f"(d[13]), "=f"(d[14]), "=f"(d[15]),
                 "=f"(d[16]), "=f"(d[17]), "=f"(d[18]), "=f"(d[19]), "=f"(d[20]), "=f"(d[21]), "=f"(d[22]), "=f"(d[23]),
                 "=f"(d[24]), "=f"(d[25]), "=f"(d[26]), "=f"(d[27]), "=f"(d[28]), "=f"(d[29]), "=f"(d[30]), "=f"(d[31])
               : "l"(a), "l"(b), "n"(TA));
  else
    asm volatile("wgmma.mma_async.sync.aligned.m64n64k16.f32.bf16.bf16 {%0,%1,%2,%3,%4,%5,%6,%7,%8,%9,%10,%11,%12,%13,%14,%15,%16,%17,%18,%19,%20,%21,%22,%23,%24,%25,%26,%27,%28,%29,%30,%31}, %32, %33, 1, 1, 1, %34, 1;"
               : "+f"(d[0]), "+f"(d[1]), "+f"(d[2]), "+f"(d[3]), "+f"(d[4]), "+f"(d[5]), "+f"(d[6]), "+f"(d[7]),
                 "+f"(d[8]), "+f"(d[9]), "+f"(d[10]), "+f"(d[11]), "+f"(d[12]), "+f"(d[13]), "+f"(d[14]), "+f"(d[15]),
                 "+f"(d[16]), "+f"(d[17]), "+f"(d[18]), "+f"(d[19]), "+f"(d[20]), "+f"(d[21]), "+f"(d[22]), "+f"(d[23]),
                 "+f"(d[24]), "+f"(d[25]), "+f"(d[26]), "+f"(d[27]), "+f"(d[28]), "+f"(d[29]), "+f"(d[30]), "+f"(d[31])
               : "l"(a), "l"(b), "n"(TA));
}

constexpr int H_STAGE = 49152, H_NST = 4;
constexpr int H_STG = H_NST * H_STAGE;
constexpr int H_VEC = H_STG + 16384;
constexpr int H_BAR = H_VEC + 6144;
constexpr int H_SMEM = H_BAR + 256;
constexpr int HB_FULL = 0, HB_EMPTY = 32, HB_IFULL = 64, HB_IEMPTY = 80, HB_ITEM = 96, HB_INC = 104;
enum { IT_END = 0, IT_MOD = 1, IT_XT = 2, IT_OUT = 3, IT_UV = 4, IT_F1 = 5, IT_F2 = 6 };
constexpr int MAX_ITEMS = 1400;
#define D_MOD 4
#define D_UV 2
#define R_LATE 1
#define CH_FENCE 1
#define CH_FENCE1 1
#define N_UV1 20
#define FINE 1
#define B_EARLY 1
#define XT_GO 0
struct HList { uint32_t n; uint32_t it[MAX_ITEMS]; };
#define HT(i)

__device__ __forceinline__ uint32_t tile_lane(int warp, int lane) { return warp * 1024 + (lane >> 2) * 64 + (((lane & 3) ^ (lane >> 3)) << 4); }
__device__ __forceinline__ constexpr uint32_t tile_off(int c, int h) { return (c >> 1) * 16384 + (c & 1) * 8192 + h * 512; }

__device__ __forceinline__ void h_pass(uint32_t sb, int nst, uint32_t& st, uint32_t& ph, bool leader) {
#pragma unroll 1
  for (int i = 0; i < nst; i++) {
    mbar_wait(sb + H_BAR + HB_FULL + st * 8, ph);
    if (leader) mbar_arrive(sb + H_BAR + HB_EMPTY + st * 8);
    if (++st == H_NST) { st = 0; ph ^= 1; }
  }
}
template <int BN, int TA, class PRE>
__device__ __forceinline__ void h_mainloop(float* acc, uint32_t sb, int nst, uint32_t& st, uint32_t& ph, int wg, bool leader, bool fixed_a, PRE pre) {
  constexpr int KS = BN == 64 ? 8 : 4;
  constexpr uint32_t BOFF = BN == 64 ? 32768 : 16384;
  const uint64_t da0 = fixed_a ? mkdesc(sb + H_STG, 16, 0, 2) : TA ? mkdesc(sb + wg * 1024, 2048, 128, 0) : mkdesc(sb + wg * 4096, 16, 512, 2);
  const uint64_t db0 = mkdesc(sb + BOFF, 8192, 1024, 1);
  const uint32_t kh = fixed_a ? 32 : 512;
  uint32_t prev = 0;
  auto stage = [&](auto first, int i) {
    constexpr bool FIRST = decltype(first)::value;
    mbar_wait(sb + H_BAR + HB_FULL + st * 8, ph);
    if (FIRST) HT(1);
    const uint64_t da = da0 + (fixed_a ? i * 64 : st * (H_STAGE >> 4)), db = db0 + st * (H_STAGE >> 4);
    WG_FENCE();
#pragma unroll
    for (int k = 0; k < KS; k++) {
      const uint64_t a = da + (k >> 2) * 1024 + (TA ? (k & 3) * 256 : ((k >> 1) & 1) * kh + (k & 1) * 2), b = db + k * 128;
      if (FIRST && k == 0) { if (BN == 256) wg_ss256<TA, true>(acc, a, b); else if (BN == 128) wg_ss128<TA, true>(acc, a, b); else wg_ss64<TA, true>(acc, a, b); }
      else { if (BN == 256) wg_ss256<TA, false>(acc, a, b); else if (BN == 128) wg_ss128<TA, false>(acc, a, b); else wg_ss64<TA, false>(acc, a, b); }
    }
    WG_COMMIT();
  };
  stage(std::true_type(), 0);
  pre();
  prev = st;
  if (++st == H_NST) { st = 0; ph ^= 1; }
#pragma unroll 1
  for (int i = 1; i < nst; i++) {
    stage(std::false_type(), i);
    WG_WAIT(1);
    if (leader) mbar_arrive(sb + H_BAR + HB_EMPTY + prev * 8);
    prev = st;
    if (++st == H_NST) { st = 0; ph ^= 1; }
  }
  WG_WAIT(0);
  HT(2);
  reg_fence<BN / 2>(acc);
  if (leader) mbar_arrive(sb + H_BAR + HB_EMPTY + prev * 8);
}

template <int BN, bool FINAL>
__device__ __forceinline__ bool h_residual(uint32_t sb, uint32_t va, int mt, int n0, uint32_t& st, uint32_t& ph, int warp, int lane, __nv_bfloat16* out,
                                           int part = 0, int lgp = 0) {
  const size_t toff = (size_t)(mt * 16 + (n0 >> 6)) * 16384 + tile_lane(warp, lane);
  uint4 r[BN / 16];
  auto load_r = [&]() {
#pragma unroll
    for (int i = 0; i < BN / 16; i++) r[i] = __ldcg(reinterpret_cast<const uint4*>(g_x1 + toff + tile_off(i >> 1, i & 1)));
  };
  if (!R_LATE) load_r();
  float acc[BN / 2];
  h_mainloop<BN, FINAL ? 0 : 1>(acc, sb, ((FINAL ? 56 : 64) / (BN == 64 ? 2 : 1)) >> lgp, st, ph, warp >> 2, (warp & 3) == 0 && lane == 0, false,
                                [&]() { if (R_LATE) load_r(); });
  if (BN == 64 && lgp > 0) {
    const int tile = (FINAL * 4 + (mt & 3)) * 16 + (n0 >> 6);
    float4* ws = reinterpret_cast<float4*>(g_ws) + (size_t)tile * 8192 + warp * 32 + lane;
#pragma unroll
    for (int i = 0; i < 8; i++) ws[part * 2048 + i * 256] = make_float4(acc[4 * i], acc[4 * i + 1], acc[4 * i + 2], acc[4 * i + 3]);
    bar_sync<1, 256>();
    if (warp == 0 && lane == 0) { fence_gpu(); const uint32_t t = atomicAdd(&g_flags[FL_SPL + tile], 1); fence_gpu(); sts32(sb + H_BAR + HB_INC + 8, t); }
    bar_sync<1, 256>();
    if (lds32(sb + H_BAR + HB_INC + 8) != (1u << lgp) - 1) return false;
#pragma unroll 1
    for (int p = 1; p < (1 << lgp); p++) {
      float4 o[8];
#pragma unroll
      for (int i = 0; i < 8; i++) o[i] = __ldcg(ws + (part ^ p) * 2048 + i * 256);
#pragma unroll
      for (int i = 0; i < 8; i++) { acc[4 * i] += o[i].x; acc[4 * i + 1] += o[i].y; acc[4 * i + 2] += o[i].z; acc[4 * i + 3] += o[i].w; }
    }
  }
  float sm[4] = {0.f, 0.f, 0.f, 0.f};
  const uint32_t stg = sb + H_STG + warp * 2048;
#pragma unroll
  for (int c = 0; c < BN / 32; c++) {
    uint32_t y[2][4] = {{r[2 * c].x, r[2 * c].y, r[2 * c].z, r[2 * c].w}, {r[2 * c + 1].x, r[2 * c + 1].y, r[2 * c + 1].z, r[2 * c + 1].w}}, z[2][4];
#pragma unroll
    for (int j = 0; j < 4; j++) {
      const uint32_t gt = lds32(va + c * 64 + j * 16 + (lane & 3) * 4);
      const uint32_t cb = FINAL ? 0 : lds32(va + 512 + c * 64 + j * 16 + (lane & 3) * 4);
#pragma unroll
      for (int h = 0; h < 2; h++) {
        const float* a = acc + c * 16 + j * 4 + h * 2;
        y[h][j] = pack2(fmaf(bf_lo(gt), a[0], bf_lo(y[h][j])), fmaf(bf_hi(gt), a[1], bf_hi(y[h][j])));
        if (!FINAL) {
          const float p = bf_lo(y[h][j]), q = bf_hi(y[h][j]);
          sm[2 * h] += p + q;
          sm[2 * h + 1] = fmaf(p, p, fmaf(q, q, sm[2 * h + 1]));
          z[h][j] = pack2(fmaf(p, bf_lo(cb), p), fmaf(q, bf_hi(cb), q));
        }
      }
    }
    if (!FINAL) {
#pragma unroll
      for (int h = 0; h < 2; h++) {
        const size_t o = toff + tile_off(c, h);
        *reinterpret_cast<uint4*>(g_x1 + o) = make_uint4(y[h][0], y[h][1], y[h][2], y[h][3]);
        *reinterpret_cast<uint4*>(g_h2 + o) = make_uint4(z[h][0], z[h][1], z[h][2], z[h][3]);
      }
    } else {
#pragma unroll
      for (int h = 0; h < 2; h++) stsm4(stg + (h * 8 + (lane & 7)) * 128 + ((((c & 1) * 4 + (lane >> 3)) ^ (lane & 7)) << 4), y[h]);
      if (c & 1) {
        __syncwarp();
#pragma unroll
        for (int j = 0; j < 4; j++) {
          const int rr = 4 * j + (lane >> 3);
          uint32_t v[4];
          lds128(v, stg + rr * 128 + (((lane & 7) ^ (rr & 7)) << 4));
          *reinterpret_cast<uint4*>(out + (size_t)(mt * 128 + warp * 16 + rr) * D_ + n0 + (c >> 1) * 64 + (lane & 7) * 8) = make_uint4(v[0], v[1], v[2], v[3]);
        }
        __syncwarp();
      }
    }
    if (CH_FENCE && c + 1 < BN / 32) sched_fence(lane, 100);
  }
  if (!FINAL) {
#pragma unroll
    for (int j = 0; j < 4; j++) { sm[j] += __shfl_xor_sync(0xffffffffu, sm[j], 1); sm[j] += __shfl_xor_sync(0xffffffffu, sm[j], 2); }
    const int t = lane & 3;
    const float sv = t == 0 ? sm[0] : t == 1 ? sm[1] : t == 2 ? sm[2] : sm[3];
    asm volatile("red.relaxed.gpu.global.add.f32 [%0], %1;" :: "l"(g_stat + (mt * 128 + warp * 16 + (t >> 1) * 8 + (lane >> 2)) * 2 + (t & 1)), "f"(sv) : "memory");
  }
  return true;
}

__device__ __forceinline__ float silu_mul(float hg, float u) {
  float t; asm("tanh.approx.f32 %0, %1;" : "=f"(t) : "f"(hg));
  const float h = hg * u;
  return fmaf(h, t, h);
}

template <int BN>
__device__ __forceinline__ void h_swiglu(const float* acc, uint32_t va, int mt, int kb0, int warp, int lane) {
  uint8_t* ap = g_act + (size_t)(mt * 56 + kb0) * 16384 + tile_lane(warp, lane);
  float rs[2], nm[2], rh[2];
#pragma unroll
  for (int h = 0; h < 2; h++) {
    float t[2];
    lds64f(t, va + 2048 + (warp * 16 + h * 8 + (lane >> 2)) * 8);
    const float mean = t[0] * (1.f / D_);
    rs[h] = rsqrtf(fmaxf(t[1] * (1.f / D_) - mean * mean, 0.f) + 1e-5f);
    nm[h] = -mean * rs[h];
    rh[h] = 0.5f * rs[h];
  }
#pragma unroll
  for (int c = 0; c < BN / 64; c++) {
    uint32_t y[2][4];
#pragma unroll
    for (int j = 0; j < 4; j++) {
      const float* g = acc + 16 * c + 4 * j; const float* u = g + BN / 4;
      float p[4], q[4], o[4];
      lds128f(p, va + (4 * c + j) * 128 + (lane & 3) * 32); lds128f(q, va + (4 * c + j) * 128 + (lane & 3) * 32 + 16);
#pragma unroll
      for (int e = 0; e < 4; e++)
        o[e] = silu_mul(fmaf(rh[e >> 1], g[e], fmaf(nm[e >> 1], p[e & 1], p[2 + (e & 1)])), fmaf(rs[e >> 1], u[e], fmaf(nm[e >> 1], q[e & 1], q[2 + (e & 1)])));
      y[0][j] = pack2(o[0], o[1]); y[1][j] = pack2(o[2], o[3]);
    }
#pragma unroll
    for (int h = 0; h < 2; h++)
      *reinterpret_cast<uint4*>(ap + tile_off(c, h)) = make_uint4(y[h][0], y[h][1], y[h][2], y[h][3]);
    if (CH_FENCE1 && c + 1 < BN / 64) sched_fence(lane, 100);
  }
}

__global__ void __launch_bounds__(384, 1)
kernel_H(const __grid_constant__ CUtensorMap tmo, const __grid_constant__ CUtensorMap tm1, const __grid_constant__ CUtensorMap tm3,
         const __grid_constant__ CUtensorMap tm2, const __grid_constant__ CUtensorMap tmm, const __nv_bfloat16* __restrict__ x,
         const __nv_bfloat16* __restrict__ cvec, __nv_bfloat16* __restrict__ out, const __grid_constant__ HList list) {
  extern __shared__ __align__(1024) uint8_t smem[];
  constexpr uint32_t sb = 0x400, bars = sb + H_BAR;
  const int tid = threadIdx.x, lane = tid & 31;
  const int warp = __shfl_sync(0xffffffffu, tid >> 5, 0);
  if (tid == 0) {
    if (smem_u32(smem) != sb) __trap();
    for (int i = 0; i < H_NST; i++) { mbar_init(bars + HB_FULL + i * 8, 1); mbar_init(bars + HB_EMPTY + i * 8, 2); }
    for (int i = 0; i < 2; i++) { mbar_init(bars + HB_IFULL + i * 8, 1); mbar_init(bars + HB_IEMPTY + i * 8, 3); }
    fence_async_smem();
  }
  __syncthreads();
  if (warp >= 8) {
    asm volatile("setmaxnreg.dec.sync.aligned.u32 40;");
    if (warp == 8) {
      uint32_t st = 0, ph = 1;
#pragma unroll 1
      for (uint32_t n = 0;; n++) {
        uint32_t q = 0;
        if (lane == 0) q = atomicAdd(&g_flags[FL_HEAD], 1);
        q = __shfl_sync(0xffffffffu, q, 0);
        const uint32_t it = q < list.n ? list.it[q] : 0;
        const int type = it & 7, mt = (it >> 3) & 15, idx = (it >> 7) & 63, sz = (it >> 13) & 3, part = (it >> 15) & 3, lgp = (it >> 17) & 3;
        int f = FL_GO; uint32_t target = 1, first = 0;
        if (type == IT_OUT) { f = lane == 0 ? FL_ATT + 8 * mt : lane == 1 ? FL_XT + 8 * mt : FL_MOD; target = lane == 0 ? 64 : lane == 1 ? 2 : 12; first = 3; }
        else if (type == IT_F1) { f = lane < 8 ? FL_OUT + 8 * mt + lane : FL_UV; target = lane < 8 ? 2 : 28; }
        else if (type == IT_F2) { f = lane < 8 ? FL_F1 + 8 * mt + lane : FL_MODB; target = lane < 8 ? 8 : 4; }
        else if (type == IT_UV) { f = FL_MOD; target = 12; first = 1; }
        else if (type == IT_MOD || (XT_GO && type == IT_XT)) first = 1;
        const int gsh = type == IT_F1 ? 1 : type == IT_F2 ? 3 : 6;
        if (type >= IT_F1) first = FINE ? 1u << ((part * (56 >> lgp)) >> gsh) : type == IT_F1 ? 255u : 127u;
        uint32_t have = 0;
        auto need = [&](int g) {
          if (!((have >> g) & 1)) {
            if (lane == g) wait_flag2(&g_flags[f], target);
            __syncwarp();
            asm volatile("fence.proxy.async.global;" ::: "memory");
            have |= 1u << g;
          }
        };
        const bool has_a = type == IT_OUT || type >= IT_F1;
        auto publish = [&]() {
          mbar_wait(bars + HB_IEMPTY + (n & 1) * 8, ((n >> 1) & 1) ^ 1);
          if (elect_one()) {
            sts32(bars + HB_ITEM + (n & 1) * 4, it | (q << 19));
            mbar_arrive(bars + HB_IFULL + (n & 1) * 8);
          }
        };
        if (B_EARLY && has_a) publish();
        {
          uint32_t c = 0;
          while (first && ((have = __ballot_sync(0xffffffffu, ld_acquire(&g_flags[f]) >= target)) & first) != first) { if (++c > 20000000u) __trap(); __nanosleep(20); }
          asm volatile("fence.proxy.async.global;" ::: "memory");
        }
        if (!(B_EARLY && has_a)) publish();
        if (type == IT_END) break;
        if (type != IT_XT) {
          const uint8_t* ap = type == IT_OUT ? g_att + (size_t)mt * 64 * 16384 : type == IT_F1 ? g_h2 + (size_t)mt * 16 * 16384 : g_act + (size_t)mt * 56 * 16384;
          const int nkb = (type == IT_OUT ? 64 : type == IT_F2 ? 56 : 16) >> lgp;
          const uint32_t abytes = has_a ? (sz == 2 ? 32768 : 16384) : 0, bytes = (sz == 0 ? 32768 : 16384) + abytes;
          const int dk = sz == 2 ? 1 : 0;
#pragma unroll 1
          for (int kb = part * nkb; kb < (part + 1) * nkb; kb += 1 + dk) {
            const uint32_t d = sb + st * H_STAGE, fb = bars + HB_FULL + st * 8;
            mbar_wait(bars + HB_EMPTY + st * 8, ph);
            if (has_a) need(kb >> gsh);
            if (has_a && kb + 1 + dk >= (part + 1) * nkb) {
              need(8);
              if (elect_one()) {
                const bool f1 = type == IT_F1;
                const int c0 = f1 ? idx * (128 >> sz) : idx * (256 >> sz);
                const uint32_t v = sb + H_VEC + (n & 1) * 3072;
                const uint32_t n0 = (f1 ? 2048 : 512) >> sz, n1 = f1 ? 1024 : n0;
                asm volatile("mbarrier.expect_tx.relaxed.cta.shared::cta.b64 [%0], %1;" :: "r"(fb), "r"(n0 + n1) : "memory");
                bulk_g2s(v, f1 ? (const void*)(g_uv + c0 * 4) : (const void*)(g_mod + (type == IT_OUT ? 2 : 5) * D_ + c0), n0, fb);
                bulk_g2s(v + (f1 ? 2048 : 512), f1 ? (const void*)(g_stat + mt * 256) : (const void*)(g_mod + 4 * D_ + c0), n1, fb);
              }
            }
            if (elect_one()) {
              mbar_expect(fb, bytes);
              if (has_a) bulk_g2s(d, ap + (size_t)kb * 16384, abytes, fb);
            }
            if (++st == H_NST) { st = 0; ph ^= 1; }
          }
        }
      }
    } else if (warp >= 10) {
      const int hb = warp - 10;
      uint32_t st = 0, ph = 1;
#pragma unroll 1
      for (uint32_t n = 0;; n++) {
        mbar_wait(bars + HB_IFULL + (n & 1) * 8, (n >> 1) & 1);
        const uint32_t it = __shfl_sync(0xffffffffu, lds32(bars + HB_ITEM + (n & 1) * 4), 0);
        const int type = it & 7, idx = (it >> 7) & 63, sz = (it >> 13) & 3, part = (it >> 15) & 3, lgp = (it >> 17) & 3;
        if (type == IT_END) break;
        if (elect_one()) mbar_arrive(bars + HB_IEMPTY + (n & 1) * 8);
        if (type == IT_XT) continue;
        const bool ffn1 = type == IT_F1 || type == IT_UV;
        const int nkb = (type == IT_OUT ? 64 : type == IT_F2 ? 56 : 16) >> lgp;
        const CUtensorMap* tb = type == IT_OUT ? &tmo : ffn1 ? &tm1 : type == IT_F2 ? &tm2 : &tmm;
        const CUtensorMap* tc = ffn1 ? &tm3 : tb;
        const int c0 = ffn1 ? idx * (128 >> sz) : idx * (256 >> sz) + (type == IT_MOD ? 2048 : 0), c2 = ffn1 ? c0 : c0 + 128;
        const int dk = sz == 2 ? 1 : 0;
        const CUtensorMap* t0 = hb == 1 && sz == 1 ? tc : tb;
        const int ca = hb == 0 || sz == 2 || (sz == 1 && ffn1) ? c0 : c0 + 64;
        const uint32_t off = (sz == 2 ? 32768 : 16384) + hb * 8192;
        const uint32_t cold = type == IT_MOD ? D_MOD : type == IT_UV ? D_UV : H_NST;
#pragma unroll 1
        for (int kb = part * nkb; kb < (part + 1) * nkb; kb += 1 + dk) {
          const uint32_t d = sb + st * H_STAGE + off, fb = bars + HB_FULL + st * 8;
          mbar_wait(bars + HB_EMPTY + st * 8, ph);
          if (cold < H_NST) mbar_wait(bars + HB_FULL + ((st - cold) & 3) * 8, st >= cold ? ph ^ 1 : ph);
          if (elect_one()) {
            tma5d(d, t0, ca, kb + hb * dk, fb);
            if (sz == 0) tma5d(d + 16384, tc, c2 + hb * 64, kb, fb);
          }
          if (++st == H_NST) { st = 0; ph ^= 1; }
        }
      }
    } else if (warp == 9) {
#pragma unroll 1
      for (uint32_t n = 0;; n++) {
        mbar_wait(bars + HB_IFULL + (n & 1) * 8, (n >> 1) & 1);
        const uint32_t itq = lds32(bars + HB_ITEM + (n & 1) * 4);
        const int type = itq & 7, mt = (itq >> 3) & 15;
        if (type == IT_END) break;
        if (n & 1) bar_sync<3, 288>(); else bar_sync<2, 288>();
        if (lane == 0) {
          const uint32_t inc = lds32(bars + HB_INC + (n & 1) * 4);
          mbar_arrive(bars + HB_IEMPTY + (n & 1) * 8);
          if (inc) {
            fence_gpu();
            const int idx = (itq >> 7) & 63, sz = (itq >> 13) & 3;
            uint32_t* fl = &g_flags[type == IT_MOD ? (idx < 12 ? FL_MOD : FL_MODB) : type == IT_UV ? FL_UV : type == IT_XT ? FL_XT + 8 * mt
                                    : type == IT_OUT ? FL_OUT + 8 * mt + ((2 * idx) >> sz) : FL_F1 + 8 * mt + (idx >> (2 + sz))];
            red_add_u32(fl, inc);
            if (type == IT_OUT && sz == 0) red_add_u32(fl + 1, inc);
          }
        }
        __syncwarp();
      }
      asm volatile("griddepcontrol.wait;" ::: "memory");
      uint32_t k = 0;
      if (lane == 0) { fence_gpu(); k = atomicAdd(&g_flags[FL_EXIT], 1); }
      k = __shfl_sync(0xffffffffu, k, 0);
      if (k == gridDim.x - 1) {
        fence_gpu();
        for (int i = lane; i < 1024; i += 32) g_flags[i] = 0;
      }
    }
  } else {
    asm volatile("setmaxnreg.inc.sync.aligned.u32 232;");
    const int wg = warp >> 2;
    const bool leader = (tid & 127) == 0;
    uint32_t st = 0, ph = 0;
#pragma unroll 1
    for (uint32_t n = 0;; n++) {
      mbar_wait(bars + HB_IFULL + (n & 1) * 8, (n >> 1) & 1);
      const uint32_t itq = __shfl_sync(0xffffffffu, lds32(bars + HB_ITEM + (n & 1) * 4), 0);
      const int type = itq & 7, mt = (itq >> 3) & 15, idx = (itq >> 7) & 63, sz = (itq >> 13) & 3, part = (itq >> 15) & 3, lgp = (itq >> 17) & 3;
      uint32_t inc = type == IT_OUT ? 2 : type == IT_F1 ? 2 >> sz : type != IT_F2;
      if (type == IT_END) break;
      HT(0);
      const uint32_t va = sb + H_VEC + (n & 1) * 3072;
      if (type == IT_OUT) {
        if (sz == 0) h_residual<256, false>(sb, va, mt, idx * 256, st, ph, warp, lane, out);
        else if (sz == 1) h_residual<128, false>(sb, va, mt, idx * 128, st, ph, warp, lane, out);
        else inc = h_residual<64, false>(sb, va, mt, idx * 64, st, ph, warp, lane, out, part, lgp);
      } else if (type == IT_F2) {
        if (sz == 0) h_residual<256, true>(sb, va, mt, idx * 256, st, ph, warp, lane, out);
        else if (sz == 1) h_residual<128, true>(sb, va, mt, idx * 128, st, ph, warp, lane, out);
        else h_residual<64, true>(sb, va, mt, idx * 64, st, ph, warp, lane, out, part, lgp);
      } else if (type == IT_XT) {
        const int rg = idx * 8 + warp;
        const uint32_t* xp = reinterpret_cast<const uint32_t*>(x + (size_t)(mt * 128 + rg * 8 + (lane >> 2)) * D_) + (lane & 3);
        uint8_t* tp = g_x1 + (size_t)mt * 262144 + rg * 512 + tile_lane(0, lane);
        if (lane < 16) g_stat[(mt * 128 + rg * 8) * 2 + lane] = 0.f;
#pragma unroll 1
        for (int b = 0; b < 2; b++) {
          uint32_t v[64];
#pragma unroll
          for (int i = 0; i < 64; i++) v[i] = __ldg(xp + 256 * b + 4 * i);
#pragma unroll
          for (int i = 0; i < 16; i++)
            *reinterpret_cast<uint4*>(tp + tile_off(16 * b + i, 0)) = make_uint4(v[4 * i], v[4 * i + 1], v[4 * i + 2], v[4 * i + 3]);
        }
      } else if (sz == 1) {
        float acc[64];
        h_mainloop<128, 0>(acc, sb, 16, st, ph, wg, leader, false, []() {});
        h_swiglu<128>(acc, va, mt, idx, warp, lane);
      } else {
        if (type != IT_F1) {
          bar_sync<1, 256>();
          for (int i = tid; i < D_; i += 256) {
            __nv_bfloat16* p = reinterpret_cast<__nv_bfloat16*>(smem + H_STG + (i >> 5) * 512 + ((i >> 1) & 3) * 16) + ((i >> 3) & 3) * 2 + (i & 1);
            if (type == IT_UV) {
              p[0] = __float2bfloat16(1.f); p[32] = __ldcg(g_mod + 4 * D_ + i); p[64 + ((i & 2) ? -8 : 8)] = __ldcg(g_mod + 3 * D_ + i);
            }
            else { const float c = __bfloat162float(cvec[i]); p[0] = __float2bfloat16(c / (1.f + __expf(-c))); }
          }
          fence_async_smem();
          bar_sync<1, 256>();
        }
        if (type != IT_F1 && wg == 1) {
          h_pass(sb, 16, st, ph, leader);
        } else {
          float acc[128];
          h_mainloop<256, 0>(acc, sb, 16, st, ph, wg, leader, type != IT_F1, []() {});
          if (type == IT_F1) {
            h_swiglu<256>(acc, va, mt, idx * 2, warp, lane);
          } else if (warp == 0) {
#pragma unroll
            for (int j = 0; j < 32; j++) {
              if (type == IT_MOD) {
                if (lane < 4) reinterpret_cast<uint32_t*>(g_mod + 2048 + idx * 256)[j * 4 + lane] = pack2(acc[4 * j], acc[4 * j + 1]);
              } else {
                const float a = acc[4 * j] + __shfl_down_sync(0xffffffffu, acc[4 * j], 4), b = acc[4 * j + 1] + __shfl_down_sync(0xffffffffu, acc[4 * j + 1], 4);
                float2* up = reinterpret_cast<float2*>(g_uv + idx * 512 + ((j & 15) * 4 + (lane & 3)) * 8 + (j >> 4) * 4);
                const float sc = j < 16 ? 0.5f : 1.f;
                if (lane < 4) up[0] = make_float2(sc * a, sc * b);
                else if ((lane >> 2) == 2) up[1] = make_float2(sc * acc[4 * j], sc * acc[4 * j + 1]);
              }
            }
          }
        }
      }
      if (tid == 0) sts32(bars + HB_INC + (n & 1) * 4, inc);
      if (n & 1) bar_arrive<3, 288>(); else bar_arrive<2, 288>();
    }
  }
}

const uint32_t h_items[] = {
  2, 130, 10, 138, 18, 146, 26, 154, 34, 162, 42, 170, 50, 178, 58, 186, 66, 194, 74, 202, 82, 210, 90, 218,
  98, 226, 106, 234, 114, 242, 122, 250, 1, 129, 257, 385, 513, 641, 769, 897, 1025, 1153, 1281, 1409, 4, 132, 260, 388,
  516, 644, 772, 900, 1028, 1156, 1284, 1412, 1540, 1668, 1796, 1924, 2052, 2180, 2308, 16387, 2436, 16515, 16643, 16771, 16899, 17027, 17155, 17283,
  17411, 17539, 17667, 17795, 17923, 18051, 18179, 18307, 2564, 2692, 2820, 2948, 3076, 3204, 3332, 1537, 3460, 1665, 1793, 1921, 16395, 16523, 16651, 16779,
  16907, 17035, 17163, 17291, 17419, 17547, 17675, 17803, 17931, 18059, 18187, 18315, 8211, 8339, 8467, 8595, 8723, 5, 133, 261, 389, 517, 645, 773,
  901, 1029, 1157, 1285, 1413, 1541, 1669, 1797, 1925, 2053, 2181, 2309, 2437, 8851, 8979, 9107, 2565, 2693, 2821, 2949, 3077, 3205, 3333, 3461,
  13, 141, 269, 781, 909, 1037, 1165, 1293, 1421, 1549, 1677, 1805, 1933, 2061, 2189, 2317, 2445, 397, 8219, 525, 8347, 653, 8475, 2573,
  2701, 2829, 8603, 2957, 3085, 8731, 3213, 3341, 17691, 3469, 8198, 8326, 8454, 8582, 17819, 2837, 8710, 8838, 17947, 8966, 18075, 9094, 3093, 18203,
  21, 3221, 18331, 16419, 3349, 16547, 16675, 3477, 16803, 1173, 16931, 1301, 17059, 1429, 2965, 1557, 17187, 1685, 17315, 2197, 17443, 1813, 17571, 2325,
  17699, 1941, 149, 2453, 277, 2069, 405, 2581, 533, 2709, 661, 29, 789, 157, 917, 285, 1045, 413, 17827, 541, 17955, 669, 18083, 797,
  18211, 925, 18339, 1053, 14, 1181, 142, 1309, 270, 1437, 398, 1565, 1693, 1821, 8235, 8363, 8491, 8619, 8747, 8875, 1949, 9003, 9131, 2077,
  2205, 2333, 3229, 2461, 3357, 2589, 3485, 2717, 8243, 2845, 8371, 2973, 8499, 3101, 8627, 8755, 8883, 9011, 9139, 37, 165, 293, 421, 549,
  677, 805, 933, 1061, 1189, 1317, 1445, 1573, 1701, 1829, 1957, 8251, 8379, 8507, 8635, 8763, 8891, 9019, 9147, 2085, 2213, 2341, 2469, 2597,
  2725, 2853, 2981, 3109, 3237, 3365, 3493, 45, 173, 301, 429, 557, 685, 813, 941, 1069, 1453, 1197, 1581, 1325, 9027, 1709, 1837, 1965,
  8259, 8387, 8515, 8643, 8771, 8899, 693, 9155, 2093, 2221, 2349, 2477, 2605, 2733, 2861, 2989, 3117, 3245, 9163, 2101, 2229, 3373, 3501, 53,
  181, 309, 437, 565, 821, 949, 1077, 1205, 1333, 1461, 1589, 1717, 1845, 1973, 8267, 8395, 8523, 8651, 8779, 8907, 9035, 2357, 2485, 2613,
  2741, 2869, 2997, 3125, 3253, 3381, 3509, 61, 189, 317, 445, 573, 701, 829, 957, 1085, 1213, 1341, 1469, 1597, 1725, 2493, 8275, 1853,
  8403, 1981, 8531, 2109, 8659, 2237, 8787, 2365, 8915, 9043, 9171, 2621, 2749, 2877, 3005, 3133, 3261, 3389, 3517, 1733, 69, 453, 197, 1861,
  325, 581, 709, 837, 1477, 965, 1605, 1093, 1989, 1221, 2117, 1349, 12869, 12997, 2245, 2501, 8283, 8411, 8539, 2629, 8667, 2757, 8795, 2885,
  8923, 9179, 3269, 3397, 1229, 3525, 973, 77, 205, 333, 461, 589, 1357, 717, 845, 1101, 3013, 9051, 3141, 1485, 1613, 1741, 1869, 1997,
  8675, 8291, 8803, 8419, 8931, 8547, 9059, 341, 3277, 85, 22, 469, 3405, 597, 3533, 725, 853, 981, 1109, 1237, 1365, 1493, 9187, 2125,
  2253, 2893, 2381, 2509, 3021, 213, 2637, 3149, 2765, 1621, 1749, 1877, 2005, 2133, 2261, 8427, 8299, 2389, 8555, 2517, 8683, 2645, 8811, 2773,
  8939, 2901, 9067, 3029, 9195, 150, 278, 406, 30, 158, 430, 286, 414, 38, 46, 166, 174, 294, 302, 422, 54, 182, 310, 438,
  8307, 8435, 8563, 8691, 8819, 8947, 9075, 9203, 278651, 311419, 344187, 376955, 278779, 311547, 344315, 377083, 180987, 312315, 148347, 345083, 181115, 148731, 181499, 148859,
  3157, 62, 148987, 149243, 278907, 3285, 190, 318, 149115, 311675, 148219, 344443, 279547, 181627, 1757, 377211, 181755, 181883, 1885, 147963, 2013, 180731, 2141, 2269,
  2397, 101, 2525, 182011, 148091, 180859, 3165, 149371, 182139, 280571, 313339, 346107, 279675, 377851, 378875, 312443, 345211, 377979, 446, 2653, 2781, 2909, 3037, 3293,
  3421, 3549, 3413, 733, 229, 989, 741, 1117, 1245, 869, 997, 1373, 1125, 1501, 1253, 1509, 3541, 93, 1629, 221, 349, 477, 1381, 605,
  357, 485, 861, 613, 1637, 1893, 2021, 2149, 2277, 2405, 2533, 2661, 2789, 12269, 2917, 3045, 12397, 3173, 12525, 3301, 12653, 3429, 12781, 12909,
  3557, 13037, 8301, 8429, 13165, 13293, 1765, 8557, 8685, 13421, 13549, 8813, 13677, 9069, 13805, 9197, 13933, 8941, 14061, 9325, 9453, 14189, 14317, 9581,
  9709, 14445, 14573, 9837, 10861, 10989, 11117, 11245, 11373, 11501, 11629, 9965, 14701, 14829, 10093, 10221, 14957, 15213, 15341, 10605, 10733, 15085, 11757, 10349,
  8573, 11885, 10477, 8701, 12013, 2549, 12141, 2677, 8317, 2805, 2933, 8262, 8390, 8518, 8646, 8774, 9030, 9158, 8902, 9038, 9166, 8270, 8398, 8526,
  8654, 8782, 3061, 8910, 3189, 3317, 117, 245, 373, 501, 629, 757, 3445, 3573, 1269, 1397, 1525, 8445, 8829, 8957, 9085, 9213, 9341, 9469,
  9597, 9725, 9853, 10621, 9981, 10109, 10749, 11645, 10237, 11773, 12029, 10365, 11901, 12157, 12285, 10493, 885, 12413, 1653, 1781, 1013, 1909, 1141, 12541,
  2037, 12669, 2165, 12797, 2293, 12925, 2421, 13053, 13181, 13309, 13565, 13437, 13693, 13821, 10877, 11005, 11133, 11517, 13949, 14077, 14205, 14333, 14461, 14589,
  14717, 14845, 14973, 8278, 8406, 8534, 15101, 8662, 15229, 8790, 15357, 9174, 8918, 11261, 8286, 9046, 8542, 11389, 8414, 8670, 8798, 8926, 9054, 9182,
  147558, 180326, 147686, 180454, 147814, 180582, 16870, 16998, 17126, 17254, 17382, 17510, 17638, 17766, 17894, 18022, 18150, 18278, 18406, 16494, 16622, 16750, 16878, 17006,
  17134, 17390, 17518, 17646, 17774, 17902, 18030, 18158, 17262, 18414, 18286, 16894, 17022, 17150, 17278, 17534, 17662, 17790, 18046, 18174, 278774, 16510, 16638, 311542,
  16766, 18302, 344310, 18430, 147574, 17918, 377078, 17406, 180342, 147830, 180598, 148470, 181238, 182006, 149366, 182134, 148598, 181366, 148726, 148854, 181494, 181622, 147958, 180726,
  148086, 180854, 148214, 180982, 148342, 181110, 148982, 181750, 149110, 181878, 149238, 149494, 182262,
};
void build_list(HList& l) {
  l.n = sizeof(h_items) / sizeof(h_items[0]);
  for (uint32_t i = 0; i < l.n; i++) l.it[i] = h_items[i];
}

typedef CUresult (*EncodeFn)(CUtensorMap*, CUtensorMapDataType, cuuint32_t, void*, const cuuint64_t*, const cuuint64_t*,
                             const cuuint32_t*, const cuuint32_t*, CUtensorMapInterleave, CUtensorMapSwizzle,
                             CUtensorMapL2promotion, CUtensorMapFloatOOBfill);

#define PROMO_W CU_TENSOR_MAP_L2_PROMOTION_L2_128B
#define PROMO_O CU_TENSOR_MAP_L2_PROMOTION_L2_128B
#define PROMO_M CU_TENSOR_MAP_L2_PROMOTION_L2_128B
#define PROMO_H CU_TENSOR_MAP_L2_PROMOTION_L2_128B
void make_map(EncodeFn fn, CUtensorMap* m, const void* p, uint64_t cols, uint64_t rows, uint32_t bc, uint32_t br, CUtensorMapSwizzle sw,
              CUtensorMapL2promotion promo) {
  cuuint64_t dims[2] = {cols, rows};
  cuuint64_t strides[1] = {cols * 2};
  cuuint32_t box[2] = {bc, br};
  cuuint32_t es[2] = {1, 1};
  fn(m, CU_TENSOR_MAP_DATA_TYPE_BFLOAT16, 2, const_cast<void*>(p), dims, strides, box, es, CU_TENSOR_MAP_INTERLEAVE_NONE, sw,
     promo, CU_TENSOR_MAP_FLOAT_OOB_FILL_NONE);
}

void make_map_perm(EncodeFn fn, CUtensorMap* m, const void* p, uint64_t cols, uint64_t rows, bool perm) {
  cuuint64_t dims[5] = {cols, 2, 4, 4, rows / 32};
  cuuint64_t strides[4] = {cols * 2, cols * 2 * (perm ? 8 : 2), cols * 2 * (perm ? 2 : 8), cols * 2 * 32};
  cuuint32_t box[5] = {64, 2, 4, 4, 2};
  cuuint32_t es[5] = {1, 1, 1, 1, 1};
  fn(m, CU_TENSOR_MAP_DATA_TYPE_BFLOAT16, 5, const_cast<void*>(p), dims, strides, box, es, CU_TENSOR_MAP_INTERLEAVE_NONE,
     CU_TENSOR_MAP_SWIZZLE_128B, PROMO_H, CU_TENSOR_MAP_FLOAT_OOB_FILL_NONE);
}

}

extern "C" void kernel_launch(void* const* d_in, const int* in_sizes, int n_in, void* d_out, int out_size) {
  const __nv_bfloat16* x = (const __nv_bfloat16*)d_in[0];
  const __nv_bfloat16* mem0 = (const __nv_bfloat16*)d_in[1];
  const __nv_bfloat16* cvec = (const __nv_bfloat16*)d_in[11];
  static EncodeFn enc = nullptr;
  if (!enc) {
    cudaDriverEntryPointQueryResult qr;
    void* fp = nullptr;
    cudaGetDriverEntryPoint("cuTensorMapEncodeTiled", &fp, cudaEnableDefault, &qr);
    enc = (EncodeFn)fp;
    cudaFuncSetAttribute(kernel_R, cudaFuncAttributeMaxDynamicSharedMemorySize, R_SMEM);
    cudaFuncSetAttribute(kernel_H, cudaFuncAttributeMaxDynamicSharedMemorySize, H_SMEM);
  }
  CUtensorMap tmq, tmk, tmv, tmo, tmm;
  make_map(enc, &tmm, d_in[12], 6144, 1024, 64, 64, CU_TENSOR_MAP_SWIZZLE_NONE, PROMO_M);
  make_map(enc, &tmq, d_in[2], 4096, 1024, 64, 64, CU_TENSOR_MAP_SWIZZLE_128B, PROMO_W);
  make_map(enc, &tmk, d_in[3], 4096, 1024, 64, 64, CU_TENSOR_MAP_SWIZZLE_128B, PROMO_W);
  make_map(enc, &tmv, d_in[4], 4096, 1024, 64, 64, CU_TENSOR_MAP_SWIZZLE_128B, PROMO_W);
  make_map(enc, &tmo, d_in[5], 1024, 4096, 16, 128, CU_TENSOR_MAP_SWIZZLE_32B, PROMO_O);
  RDesc dsc;
  for (int k = 0; k < 32; k++) {
    dsc.tok[k] = mkdesc(0x400 + (k < 16 ? R_GA : R_GB) + ((k & 15) >> 2) * 4096 + (k & 3) * 256, 128, 1024, 0);
    dsc.tail_a[k] = mkdesc(0x400 + R_TAIL + k * 2048, 1024, 1024, 1);
    if (k < 16) dsc.tail_b[k] = mkdesc(0x400 + R_GA + k * 256, 128, 4096, 0);
  }
  kernel_R<<<96, 256, R_SMEM, cudaStreamPerThread>>>(tmq, tmk, tmv, tmo, tmm, x, mem0, cvec, dsc);

  CUtensorMap ho, h1, h3, h2, hm;
  make_map_perm(enc, &ho, d_in[5], 1024, 4096, false);
  make_map_perm(enc, &h1, d_in[8], F_, 1024, true);
  make_map_perm(enc, &h3, d_in[9], F_, 1024, true);
  make_map_perm(enc, &h2, d_in[10], 1024, F_, true);
  make_map_perm(enc, &hm, d_in[12], 6144, 1024, true);
  HList list;
  build_list(list);
  cudaLaunchConfig_t cfg = {};
#define H_GRID 132
  cfg.gridDim = dim3(H_GRID); cfg.blockDim = dim3(384); cfg.dynamicSmemBytes = H_SMEM; cfg.stream = cudaStreamPerThread;
  cudaLaunchAttribute at[1];
  at[0].id = cudaLaunchAttributeProgrammaticStreamSerialization;
  at[0].val.programmaticStreamSerializationAllowed = 1;
  cfg.attrs = at;
  cfg.numAttrs = 1;
  cudaLaunchKernelEx(&cfg, kernel_H, ho, h1, h3, h2, hm, x, cvec, (__nv_bfloat16*)d_out, list);
}
```

```cpp
#include <cuda_runtime.h>
#include <cuda_bf16.h>
#include <cuda.h>
#include <stdint.h>
#include <type_traits>

namespace {

constexpr int S_ = 2048, D_ = 1024, NSEG = 64, F_ = 3584;

__device__ __align__(1024) uint8_t g_h[S_ * D_ * 2];
__device__ __align__(1024) uint8_t g_att[S_ * 4096 * 2];
__device__ __align__(1024) uint8_t g_x1[S_ * D_ * 2];
__device__ __align__(1024) uint8_t g_h2[S_ * D_ * 2];
__device__ __align__(1024) uint8_t g_act[S_ * F_ * 2];
__device__ __align__(1024) float g_ws[12 * 16 * 4 * 8192];
__device__ __align__(1024) float g_stat[S_ * 2];
__device__ __align__(1024) float g_uv[F_ * 4];
__device__ __align__(1024) float g_slot[4 * 3 * 8 * 4 * 32 * 4];
__device__ __align__(128) __nv_bfloat16 g_mod[6 * D_];
__device__ __align__(128) float g_modp[3 * 2 * D_];
__device__ __align__(128) uint32_t g_flags[1024];
constexpr int FL_S1 = 0, FL_S2 = 32, FL_MOD = 64, FL_HEAD = 96, FL_EXIT = 128, FL_UV = 160, FL_GO = 192, FL_MODB = 224, FL_MODA = 240, FL_ATT = 256, FL_XT = 384, FL_OUT = 512, FL_F1 = 640, FL_SPL = 768;

#define EVF 1
__device__ __forceinline__ uint32_t smem_u32(const void* p) { return (uint32_t)__cvta_generic_to_shared(p); }
__device__ __forceinline__ uint32_t mapa(uint32_t a, uint32_t r) { uint32_t o; asm("mapa.shared::cluster.u32 %0, %1, %2;" : "=r"(o) : "r"(a), "r"(r)); return o; }
__device__ __forceinline__ uint32_t pack2(float a, float b) { uint32_t r; asm("cvt.rn.bf16x2.f32 %0, %1, %2;" : "=r"(r) : "f"(b), "f"(a)); return r; }
__device__ __forceinline__ float bf_lo(uint32_t w) { return __uint_as_float(w << 16); }
__device__ __forceinline__ float bf_hi(uint32_t w) { return __uint_as_float(w & 0xffff0000u); }
__device__ __forceinline__ float ex2(float x) { float y; asm("ex2.approx.ftz.f32 %0, %1;" : "=f"(y) : "f"(x)); return y; }
__device__ __forceinline__ float rcp(float x) { float y; asm("rcp.approx.ftz.f32 %0, %1;" : "=f"(y) : "f"(x)); return y; }
__device__ __forceinline__ uint32_t clk32() { uint64_t c; asm volatile("mov.u64 %0, %%clock64;" : "=l"(c) :: "memory"); return (uint32_t)c; }

__device__ __forceinline__ void mbar_init(uint32_t b, uint32_t n) { asm volatile("mbarrier.init.shared::cta.b64 [%0], %1;" :: "r"(b), "r"(n) : "memory"); }
__device__ __forceinline__ void mbar_arrive(uint32_t b) { asm volatile("mbarrier.arrive.shared::cta.b64 _, [%0];" :: "r"(b) : "memory"); }
__device__ __forceinline__ void mbar_expect(uint32_t b, uint32_t n) { asm volatile("mbarrier.arrive.expect_tx.shared::cta.b64 _, [%0], %1;" :: "r"(b), "r"(n) : "memory"); }
__device__ __forceinline__ uint32_t mbar_try(uint32_t b, uint32_t par) {
  uint32_t ok;
  asm volatile("{\n.reg .pred p;\nmbarrier.try_wait.parity.shared::cta.b64 p, [%1], %2;\nselp.u32 %0, 1, 0, p;\n}" : "=r"(ok) : "r"(b), "r"(par) : "memory");
  return ok;
}
__device__ __forceinline__ void mbar_wait(uint32_t b, uint32_t par) {
  asm volatile("{\n.reg .pred p;\n"
               "LOOP:\n"
               "mbarrier.try_wait.parity.shared::cta.b64 p, [%0], %1;\n"
               "@!p bra.uni LOOP;\n}" :: "r"(b), "r"(par) : "memory");
}
__device__ __forceinline__ void mbar_wait_safe(uint32_t b, uint32_t par) {
  uint32_t c = 0;
  while (!mbar_try(b, par)) { if (++c > 4000000u) __trap(); }
}
__device__ __forceinline__ bool elect_one() {
  uint32_t p;
  asm volatile("{\n.reg .pred p;\nelect.sync _|p, 0xffffffff;\nselp.u32 %0, 1, 0, p;\n}" : "=r"(p));
  return p;
}
__device__ __forceinline__ void sched_fence(uint32_t x, uint32_t y) { asm volatile("{\n.reg .pred p;\nsetp.eq.u32 p, %0, %1;\n@p trap;\n}" :: "r"(x), "r"(y) : "memory"); }
template <class T> __device__ __forceinline__ T opaque32(T x) { asm volatile("" : "+r"(x)); return x; }
template <class T> __device__ __forceinline__ T opaque64(T x) { asm volatile("" : "+l"(x)); return x; }
template <int ID, int N> __device__ __forceinline__ void bar_sync() { asm volatile("bar.sync %0, %1;" :: "n"(ID), "n"(N) : "memory"); }
template <int ID, int N> __device__ __forceinline__ void bar_arrive() { asm volatile("bar.arrive %0, %1;" :: "n"(ID), "n"(N) : "memory"); }
__device__ __forceinline__ void fence_async_smem() { asm volatile("fence.proxy.async.shared::cta;" ::: "memory"); }
__device__ __forceinline__ void fence_async_all() { asm volatile("fence.proxy.async;" ::: "memory"); }
__device__ __forceinline__ void fence_gpu() { asm volatile("fence.acq_rel.gpu;" ::: "memory"); }
__device__ __forceinline__ void red_add_u32(uint32_t* p, uint32_t v) { asm volatile("red.relaxed.gpu.global.add.u32 [%0], %1;" :: "l"(p), "r"(v) : "memory"); }
__device__ __forceinline__ uint32_t ld_acquire(const uint32_t* p) { uint32_t v; asm volatile("ld.acquire.gpu.global.u32 %0, [%1];" : "=r"(v) : "l"(p) : "memory"); return v; }
__device__ __forceinline__ void wait_flag(const uint32_t* p, uint32_t target) {
  uint32_t c = 0;
  while (ld_acquire(p) < target) { if (++c > 20000000u) __trap(); __nanosleep(20); }
}

__device__ __forceinline__ void wait_flag2(const uint32_t* p, uint32_t target) {
  asm volatile("{\n.reg .pred p;\n.reg .u32 v, c;\nmov.u32 c, 0;\nWL:\nld.acquire.gpu.global.u32 v, [%0];\nsetp.ge.u32 p, v, %1;\n@p bra WD;\n"
               "add.u32 c, c, 1;\nsetp.gt.u32 p, c, 20000000;\n@p trap;\nnanosleep.u32 20;\nbra WL;\nWD:\n}" :: "l"(p), "r"(target) : "memory");
}
__device__ __forceinline__ void tma2d(uint32_t dst, const CUtensorMap* m, int c0, int c1, uint32_t bar) {
  asm volatile("cp.async.bulk.tensor.2d.shared::cluster.global.mbarrier::complete_tx::bytes [%0], [%1, {%3, %4}], [%2];"
               :: "r"(dst), "l"(m), "r"(bar), "r"(c0), "r"(c1) : "memory");
}
__device__ __forceinline__ void tma2d_once(uint32_t dst, const CUtensorMap* m, int c0, int c1, uint32_t bar) {
  asm volatile("{\n.reg .b64 pol;\ncreatepolicy.fractional.L2::evict_first.b64 pol, 1.0;\n"
               "cp.async.bulk.tensor.2d.shared::cluster.global.mbarrier::complete_tx::bytes.L2::cache_hint [%0], [%1, {%3, %4}], [%2], pol;\n}"
               :: "r"(dst), "l"(m), "r"(bar), "r"(c0), "r"(c1) : "memory");
}
__device__ __forceinline__ void tma5d(uint32_t dst, const CUtensorMap* m, int n0, int kb, uint32_t bar) {
  asm volatile("cp.async.bulk.tensor.5d.shared::cluster.global.mbarrier::complete_tx::bytes [%0], [%1, {%3, %5, %5, %5, %4}], [%2];"
               :: "r"(dst), "l"(m), "r"(bar), "r"(n0), "r"(2 * kb), "r"(0) : "memory");
}
__device__ __forceinline__ void tma2d_prefetch(const CUtensorMap* m, int c0, int c1) {
  asm volatile("cp.async.bulk.prefetch.tensor.2d.L2.global [%0, {%1, %2}];" :: "l"(m), "r"(c0), "r"(c1) : "memory");
}
__device__ __forceinline__ void bulk_g2s(uint32_t dst, const void* src, uint32_t bytes, uint32_t bar) {
  asm volatile("cp.async.bulk.shared::cluster.global.mbarrier::complete_tx::bytes [%0], [%1], %2, [%3];"
               :: "r"(dst), "l"(src), "r"(bytes), "r"(bar) : "memory");
}
__device__ __forceinline__ void bulk_s2s(uint32_t dst, uint32_t src, uint32_t bytes, uint32_t bar) {
  asm volatile("cp.async.bulk.shared::cluster.shared::cta.mbarrier::complete_tx::bytes [%0], [%1], %2, [%3];"
               :: "r"(dst), "r"(src), "r"(bytes), "r"(bar) : "memory");
}
__device__ __forceinline__ void st_async1(uint32_t dst, uint32_t a, uint32_t bar) {
  asm volatile("st.async.shared::cluster.mbarrier::complete_tx::bytes.b32 [%0], %1, [%2];" :: "r"(dst), "r"(a), "r"(bar) : "memory");
}
__device__ __forceinline__ void st_async2(uint32_t dst, uint32_t a, uint32_t b, uint32_t bar) {
  asm volatile("st.async.shared::cluster.mbarrier::complete_tx::bytes.v2.b32 [%0], {%1, %2}, [%3];" :: "r"(dst), "r"(a), "r"(b), "r"(bar) : "memory");
}
__device__ __forceinline__ void st_async4(uint32_t dst, const uint32_t* r, uint32_t bar) {
  asm volatile("st.async.shared::cluster.mbarrier::complete_tx::bytes.v4.b32 [%0], {%1, %2, %3, %4}, [%5];"
               :: "r"(dst), "r"(r[0]), "r"(r[1]), "r"(r[2]), "r"(r[3]), "r"(bar) : "memory");
}
__device__ __forceinline__ void sts32(uint32_t a, uint32_t v) { asm volatile("st.shared.b32 [%0], %1;" :: "r"(a), "r"(v) : "memory"); }
__device__ __forceinline__ void sts64(uint32_t a, uint32_t x, uint32_t y) { asm volatile("st.shared.v2.b32 [%0], {%1, %2};" :: "r"(a), "r"(x), "r"(y) : "memory"); }
__device__ __forceinline__ void sts128(uint32_t a, uint32_t x, uint32_t y, uint32_t z, uint32_t w) {
  asm volatile("st.shared.v4.b32 [%0], {%1, %2, %3, %4};" :: "r"(a), "r"(x), "r"(y), "r"(z), "r"(w) : "memory");
}
__device__ __forceinline__ void lds128(uint32_t* r, uint32_t a) {
  asm volatile("ld.shared.v4.b32 {%0, %1, %2, %3}, [%4];" : "=r"(r[0]), "=r"(r[1]), "=r"(r[2]), "=r"(r[3]) : "r"(a) : "memory");
}
__device__ __forceinline__ uint32_t lds32(uint32_t a) { uint32_t r; asm volatile("ld.shared.b32 %0, [%1];" : "=r"(r) : "r"(a) : "memory"); return r; }
__device__ __forceinline__ void lds64(uint32_t* r, uint32_t a) {
  asm volatile("ld.shared.v2.b32 {%0, %1}, [%2];" : "=r"(r[0]), "=r"(r[1]) : "r"(a) : "memory");
}
__device__ __forceinline__ void lds128f(float* r, uint32_t a) {
  asm volatile("ld.shared.v4.f32 {%0, %1, %2, %3}, [%4];" : "=f"(r[0]), "=f"(r[1]), "=f"(r[2]), "=f"(r[3]) : "r"(a) : "memory");
}
__device__ __forceinline__ void lds64f(float* r, uint32_t a) {
  asm volatile("ld.shared.v2.f32 {%0, %1}, [%2];" : "=f"(r[0]), "=f"(r[1]) : "r"(a) : "memory");
}
__device__ __forceinline__ void ldsm4(uint32_t* r, uint32_t a) {
  asm volatile("ldmatrix.sync.aligned.m8n8.x4.shared.b16 {%0, %1, %2, %3}, [%4];" : "=r"(r[0]), "=r"(r[1]), "=r"(r[2]), "=r"(r[3]) : "r"(a) : "memory");
}
__device__ __forceinline__ void ldsm4t(uint32_t* r, uint32_t a) {
  asm volatile("ldmatrix.sync.aligned.m8n8.x4.trans.shared.b16 {%0, %1, %2, %3}, [%4];" : "=r"(r[0]), "=r"(r[1]), "=r"(r[2]), "=r"(r[3]) : "r"(a) : "memory");
}
__device__ __forceinline__ void ldsm2(uint32_t* r, uint32_t a) {
  asm volatile("ldmatrix.sync.aligned.m8n8.x2.shared.b16 {%0, %1}, [%2];" : "=r"(r[0]), "=r"(r[1]) : "r"(a) : "memory");
}
__device__ __forceinline__ void stsm4(uint32_t a, const uint32_t* r) {
  asm volatile("stmatrix.sync.aligned.m8n8.x4.shared.b16 [%0], {%1, %2, %3, %4};" :: "r"(a), "r"(r[0]), "r"(r[1]), "r"(r[2]), "r"(r[3]) : "memory");
}
__device__ __forceinline__ uint32_t hadd2(uint32_t a, uint32_t b) { uint32_t t; asm("add.rn.bf16x2 %0, %1, %2;" : "=r"(t) : "r"(a), "r"(b)); return t; }
__device__ __forceinline__ uint32_t hmax2(uint32_t a, uint32_t b) { uint32_t t; asm("max.bf16x2 %0, %1, %2;" : "=r"(t) : "r"(a), "r"(b)); return t; }
__device__ __forceinline__ void ldsm2t(uint32_t* r, uint32_t a) {
  asm volatile("ldmatrix.sync.aligned.m8n8.x2.trans.shared.b16 {%0, %1}, [%2];" : "=r"(r[0]), "=r"(r[1]) : "r"(a) : "memory");
}
__device__ __forceinline__ uint32_t movm(uint32_t x) { uint32_t y; asm volatile("movmatrix.sync.aligned.m8n8.trans.b16 %0, %1;" : "=r"(y) : "r"(x)); return y; }
__device__ __forceinline__ void hmma(float* d, uint32_t a0, uint32_t a1, uint32_t a2, uint32_t a3, uint32_t b0, uint32_t b1) {
  asm volatile("mma.sync.aligned.m16n8k16.row.col.f32.bf16.bf16.f32 {%0,%1,%2,%3}, {%4,%5,%6,%7}, {%8,%9}, {%0,%1,%2,%3};"
               : "+f"(d[0]), "+f"(d[1]), "+f"(d[2]), "+f"(d[3]) : "r"(a0), "r"(a1), "r"(a2), "r"(a3), "r"(b0), "r"(b1));
}
__device__ __forceinline__ void hmma0(float* d, uint32_t a0, uint32_t a1, uint32_t a2, uint32_t a3, uint32_t b0, uint32_t b1) {
  asm volatile("mma.sync.aligned.m16n8k16.row.col.f32.bf16.bf16.f32 {%0,%1,%2,%3}, {%4,%5,%6,%7}, {%8,%9}, {%10,%10,%10,%10};"
               : "=f"(d[0]), "=f"(d[1]), "=f"(d[2]), "=f"(d[3]) : "r"(a0), "r"(a1), "r"(a2), "r"(a3), "r"(b0), "r"(b1), "f"(0.f));
}
__device__ __forceinline__ void hmma_k8(float* d, uint32_t a0, uint32_t a1, uint32_t b0) {
  asm volatile("mma.sync.aligned.m16n8k8.row.col.f32.bf16.bf16.f32 {%0,%1,%2,%3}, {%4,%5}, {%6}, {%0,%1,%2,%3};"
               : "+f"(d[0]), "+f"(d[1]), "+f"(d[2]), "+f"(d[3]) : "r"(a0), "r"(a1), "r"(b0));
}
__host__ __device__ constexpr uint64_t mkdesc(uint32_t addr, uint32_t lbo, uint32_t sbo, uint32_t sw) {
  return (uint64_t)((addr & 0x3FFFF) >> 4) | ((uint64_t)(lbo >> 4) << 16) | ((uint64_t)(sbo >> 4) << 32) | ((uint64_t)sw << 62);
}
#define WG_FENCE() asm volatile("wgmma.fence.sync.aligned;" ::: "memory")
#define WG_COMMIT() asm volatile("wgmma.commit_group.sync.aligned;" ::: "memory")
#define WG_WAIT(n) asm volatile("wgmma.wait_group.sync.aligned " #n ";" ::: "memory")
template <int N> __device__ __forceinline__ void reg_fence(float* d) {
#pragma unroll
  for (int i = 0; i < N; i++) asm volatile("" : "+f"(d[i]) :: "memory");
}
template <int N> __device__ __forceinline__ void zero_regs(float* d) {
#pragma unroll
  for (int i = 0; i < N; i++) asm volatile("mov.b32 %0, 0;" : "=f"(d[i]));
}
template <int SD>
__device__ __forceinline__ void wg_rs32(float* d, uint32_t a0, uint32_t a1, uint32_t a2, uint32_t a3, uint64_t b) {
  asm volatile("wgmma.mma_async.sync.aligned.m64n32k16.f32.bf16.bf16 {%0,%1,%2,%3,%4,%5,%6,%7,%8,%9,%10,%11,%12,%13,%14,%15}, {%16,%17,%18,%19}, %20, %21, 1, 1, 0;"
               : "+f"(d[0]), "+f"(d[1]), "+f"(d[2]), "+f"(d[3]), "+f"(d[4]), "+f"(d[5]), "+f"(d[6]), "+f"(d[7]),
                 "+f"(d[8]), "+f"(d[9]), "+f"(d[10]), "+f"(d[11]), "+f"(d[12]), "+f"(d[13]), "+f"(d[14]), "+f"(d[15])
               : "r"(a0), "r"(a1), "r"(a2), "r"(a3), "l"(b), "n"(SD));
}
template <int TB>
__device__ __forceinline__ void wg_ss40(float* d, uint64_t a, uint64_t b) {
  asm volatile("wgmma.mma_async.sync.aligned.m64n40k16.f32.bf16.bf16 {%0,%1,%2,%3,%4,%5,%6,%7,%8,%9,%10,%11,%12,%13,%14,%15,%16,%17,%18,%19}, %20, %21, 1, 1, 1, 1, %22;"
               : "+f"(d[0]), "+f"(d[1]), "+f"(d[2]), "+f"(d[3]), "+f"(d[4]), "+f"(d[5]), "+f"(d[6]), "+f"(d[7]),
                 "+f"(d[8]), "+f"(d[9]), "+f"(d[10]), "+f"(d[11]), "+f"(d[12]), "+f"(d[13]), "+f"(d[14]), "+f"(d[15]),
                 "+f"(d[16]), "+f"(d[17]), "+f"(d[18]), "+f"(d[19])
               : "l"(a), "l"(b), "n"(TB));
}
__device__ __forceinline__ void wg_ss8(float* d, uint64_t a, uint64_t b) {
  asm volatile("wgmma.mma_async.sync.aligned.m64n8k16.f32.bf16.bf16 {%0,%1,%2,%3}, %4, %5, 1, 1, 1, 1, 0;"
               : "+f"(d[0]), "+f"(d[1]), "+f"(d[2]), "+f"(d[3]) : "l"(a), "l"(b));
}
template <int T>
__device__ __forceinline__ void wg_ss32(float* d, uint64_t a, uint64_t b) {
  asm volatile("wgmma.mma_async.sync.aligned.m64n32k16.f32.bf16.bf16 {%0,%1,%2,%3,%4,%5,%6,%7,%8,%9,%10,%11,%12,%13,%14,%15}, %16, %17, 1, 1, 1, %18, %18;"
               : "+f"(d[0]), "+f"(d[1]), "+f"(d[2]), "+f"(d[3]), "+f"(d[4]), "+f"(d[5]), "+f"(d[6]), "+f"(d[7]),
                 "+f"(d[8]), "+f"(d[9]), "+f"(d[10]), "+f"(d[11]), "+f"(d[12]), "+f"(d[13]), "+f"(d[14]), "+f"(d[15])
               : "l"(a), "l"(b), "n"(T));
}

constexpr int R_TAIL = 0;
constexpr int R_WO = 65536;
constexpr int R_QK = R_WO + 86016;
constexpr int R_P = R_QK + 10240;
constexpr int R_GA = R_P + 6400;
constexpr int R_M2 = R_GA + 16384;
constexpr int R_M1 = R_M2 + 7168;
constexpr int R_GB = R_M1 + 9216;
constexpr int R_VT = R_GB + 16384;
constexpr int R_VM = R_VT + 8192;
constexpr int R_XS = R_VM + 2048;
constexpr int R_OX = R_XS + 1280;
constexpr int R_BAR = R_OX + 2048;
constexpr int R_TRC = R_BAR + 256;
constexpr int R_SMEM = R_TRC + 1024;
constexpr int B_MB = 0, B_XS = 32, B_VM = 40, B_VT = 48, B_TS = 56, B_FA = 64, B_FB = 72, B_TAIL = 80, B_WO = 88, B_STG = 96, B_WM = 128, B_X = 136;
constexpr int NB_A = 1, NB_B = 2, NB_X = 3, NB_C = 4, NB_D = 5, NB_E = 6, NB_F = 7, NB_G = 8, NB_H = 9, NB_S = 10, NB_E2 = 11, NB_P = 12, NB_W0 = 13;

#define FIN 1
#define POLL_DELAY 750
#define POLL_DELAY1 700
#define POLL_STAG 150
#define POLL_K0 20
#define PF1 2
#define PF2 2
#define PF3 2
#define PF4 0
#define CLR_D 2
#define PADN 0
#define PFD 0
#define GO_EARLY 0
#define RF_FIRST 1
#define BX_I 5
#define NCH 4
#define TOP2 0
#define CX_I 13
#define ATT_LATE 0
#define V_FENCE 1
#define SELF_STAS 1
#define Q_FENCE 1
#define ND_K 3
#define TRACE(i)
#define TS(i)

__device__ __forceinline__ int rot_chunk(int c, int rank) {
  int G = c;
  if (c < 9) { G = c + 3 * rank; if (G >= 9) G -= 9; }
  return G;
}
__device__ __forceinline__ int wo_tile(int i, int rank) {
  if (i < 12) return 12 * rank + i;
  const int r = i - 12 + 9 * rank;
  return r < 16 ? 48 + r : 20 + r;
}
__device__ __forceinline__ void load_chunk(uint32_t dst, int seg, int G, uint32_t bar) {
  mbar_expect(bar, 4096);
  bulk_g2s(dst, g_h + (size_t)(seg * 16 + G) * 4096, 4096, bar);
}
__device__ __forceinline__ void load_red(uint32_t* v, const float* p) {
#pragma unroll
  for (int j = 0; j < 2; j++)
    asm volatile("ld.relaxed.gpu.global.v4.u32 {%0, %1, %2, %3}, [%4];"
                 : "=r"(v[4 * j]), "=r"(v[4 * j + 1]), "=r"(v[4 * j + 2]), "=r"(v[4 * j + 3]) : "l"(p + j * 256) : "memory");
}
__device__ __forceinline__ bool red_done(const uint32_t* v) { return __all_sync(0xffffffffu, (v[3] & v[7]) == 0x42000000u); }
__device__ __forceinline__ uint32_t finish_red(uint32_t* v, const float* p) {
  uint32_t tries = 0;
  if (__builtin_expect(!red_done(v), 0)) {
    do { if (++tries > 20000000u) __trap(); load_red(v, p); } while (!red_done(v));
  }
  return tries;
}
__device__ __forceinline__ void exp10(float* sv, const uint32_t* x) {
  constexpr float SC = 0.08838834764831845f * 1.4426950408889634f;
  uint32_t m2 = hmax2(hmax2(hmax2(x[0], x[1]), hmax2(x[2], x[3])), x[4]);
  m2 = hmax2(m2, __shfl_xor_sync(0xffffffffu, m2, 1));
  m2 = hmax2(m2, __shfl_xor_sync(0xffffffffu, m2, 2));
  const float nm = -fmaxf(bf_lo(m2), bf_hi(m2)) * SC;
#pragma unroll
  for (int j = 0; j < 5; j++) { sv[2 * j] = ex2(fmaf(bf_lo(x[j]), SC, nm)); sv[2 * j + 1] = ex2(fmaf(bf_hi(x[j]), SC, nm)); }
}

__device__ __forceinline__ uint32_t arm_size(int w, bool isC) {
  return w == 0 ? (isC ? 1280 : 640) : w == 1 ? (isC ? 0 : 2048) : w == 2 ? (isC ? 0 : 8192) : (isC ? 0 : 1792);
}
struct RDesc { uint64_t tok[32], tail_b[16], tail_a[32]; };

template <int WG>
__device__ __forceinline__ void r_main(const uint32_t (&W)[48][4], const RDesc& dsc, int head, uint32_t rank, int lane_, int w) {
  const uint32_t sb = (rank << 24) + 0x400, bars = sb + R_BAR;
  const uint32_t to1 = rank == 0 ? 2u << 24 : 0u - (1u << 24), to2 = rank == 2 ? 0u - (2u << 24) : 1u << 24;
  const bool isC = rank == 2;
  const int lane = opaque32(lane_), warp = WG * 4 + w;
  const int gl = rot_chunk(4 * (lane & 3) + w, rank);
  const int g0 = __shfl_sync(0xffffffffu, gl, 0), g1 = __shfl_sync(0xffffffffu, gl, 1), g2 = __shfl_sync(0xffffffffu, gl, 2);
  const uint32_t arm_bytes = arm_size(w, isC);

#define L16 opaque32(sb + opaque32(lane) * 16)
#define L8 opaque32(sb + opaque32(lane) * 8)
#define L4 opaque32(sb + opaque32(lane) * 4)
#define LV opaque32(sb + R_VT + ((opaque32(lane) >> 3) & 1) * 512 + (opaque32(lane) >> 4) * 128 + (opaque32(lane) & 7) * 16)
#define SLOT(st) opaque64(slot0 + ((st) & 3) * 12288 + ((st) & 4) * 32)
  float* const slot0 = opaque64(g_slot + (rank * 1024 + warp * 128 + lane) * 4);
  const uint32_t woa = opaque32(sb + R_WO + warp * 12288 + ((lane >> 4) * 8 + (lane & 7)) * 32 + ((((lane >> 3) ^ (lane >> 2)) & 1) << 4));
  const bool has_wo = WG == 0 || isC || w < 3;
  float acc[20];
  uint32_t pk[8] = {0u, 0u, 0u, 0u, 0u, 0u, 0u, 0u};

  auto forward = [&](auto rd, const uint32_t* v, int st, uint32_t tries) {
    constexpr int RD = decltype(rd)::value;
    uint32_t u[6];
#pragma unroll
    for (int j = 0; j < 6; j++) u[j] = movm(v[4 * (j / 3) + j % 3]);
    const bool all3 = RD == 0 || w < 3;
    if (RD == 0) {
      const uint32_t a = L16 + R_M1 + w * 768, a2 = L8 + R_M1 + 512 + w * 768;
      st_async4(a + to1 + 3072, u, bars + to1 + B_MB + 8); st_async2(a2 + to1 + 3072, u[4], u[5], bars + to1 + B_MB + 8);
      sts128(a, u[0], u[1], u[2], u[3]); sts64(a2, u[4], u[5]);
      __syncwarp();
      if (elect_one()) mbar_arrive(bars + B_MB);
      st_async4(a + to2 + 6144, u, bars + to2 + B_MB + 16); st_async2(a2 + to2 + 6144, u[4], u[5], bars + to2 + B_MB + 16);
    } else {
      const uint32_t a = L4 + R_M2 + rank * 2304 + w * 768;
#pragma unroll
      for (int j = 0; j < 6; j++) if (j < 2 || all3) st_async1(a + to1 + j * 128, u[j], bars + to1 + B_MB + 24);
#pragma unroll
      for (int j = 0; j < 6; j++) if (j < 2 || all3) st_async1(a + to2 + j * 128, u[j], bars + to2 + B_MB + 24);
      if (SELF_STAS) {
#pragma unroll
        for (int j = 0; j < 6; j++) if (j < 2 || all3) st_async1(a + j * 128, u[j], bars + B_MB + 24);
      } else {
#pragma unroll
        for (int j = 0; j < 6; j++) if (j < 2 || all3) sts32(a + j * 128, u[j]);
        __syncwarp();
        if (elect_one()) mbar_arrive(bars + B_MB + 24);
      }
    }
  };

  auto send_vt = [&]() {
    if (elect_one()) {
      const uint32_t src = sb + R_VT + warp * 1024;
      bulk_s2s(src + to1, src, 1024, bars + to1 + B_VT);
      bulk_s2s(src + to2, src, 1024, bars + to2 + B_VT);
    }
  };
  auto store_att = [&](int sg) {
    uint32_t* op = reinterpret_cast<uint32_t*>(g_att + (size_t)((sg >> 2) * 64 + head * 2 + rank) * 16384 + (2 * w * 16 + (sg & 3) * 4) * 128) + opaque32(lane);
#pragma unroll
    for (int j = 0; j < 8; j++) op[(j & 1) * 512 + (j >> 1) * 32] = pk[j];
  };

  if (WG == 0) bar_arrive<NB_G, 256>();
#pragma unroll 1
  for (int s = -1; s < NSEG - FIN; s++) {
    const uint32_t par = (s + 1) & 1;
    const uint32_t last = !FIN && s == NSEG - 1;
    TRACE(0);
    {
      float c[NCH][4];
      uint32_t b[3][6];
      const uint32_t ma = L16, m8 = L8;
#pragma unroll
      for (int i = 0; i < 18; i++) {
        if (i < 16) {
          if (i % 4 == 0 && !(i == 4 && TOP2)) mbar_wait(bars + B_MB + (i / 4) * 8, par ^ 1);
          if (i == 0 && TOP2) mbar_wait(bars + B_MB + 8, par ^ 1);
          if (i % 4 == 0) TRACE(1 + i / 4);
          if (i < 12) { lds128(b[i % 3], ma + R_M1 + i * 768); lds64(b[i % 3] + 4, m8 + R_M1 + 512 + i * 768); }
          else { ldsm4(b[i % 3], ma + R_M2 + 4096 + (i - 12) * 768); ldsm2(b[i % 3] + 4, ma + R_M2 + 4096 + 512 + (i - 12) * 768); }
          if (WG == 1 && i == BX_I) {
            bar_sync<NB_G, 256>();
            if (!last && elect_one()) load_chunk(sb + R_GB + w * 4096, s + 1, g0, bars + B_FB);
          }
          if (i == CX_I) {
            if (isC && s >= 0) send_vt();
            if (WG == 1 && ATT_LATE && !isC && s > 0) store_att(s - 1);
          }
          __syncwarp();
        }
        if (i >= 2) {
          const int j = i - 2;
#pragma unroll
          for (int q = 0; q < 3; q++) {
            const uint32_t* f = W[3 * j + q];
            if (3 * j + q < NCH) hmma0(c[3 * j + q], f[0], f[1], f[2], f[3], b[j % 3][2 * q], b[j % 3][2 * q + 1]);
            else hmma(c[(3 * j + q) % NCH], f[0], f[1], f[2], f[3], b[j % 3][2 * q], b[j % 3][2 * q + 1]);
          }
        }
        if (i == 14) zero_regs<16>(acc);
        if (i == 16) mbar_wait(bars + B_FA, last);
      }
#pragma unroll
      for (int j = 0; j < 4; j++) acc[16 + j] = NCH == 3 ? (c[0][j] + c[1][j]) + c[2][j] : (c[0][j] + c[1][j]) + (c[2][j] + c[NCH - 1][j]);
    }
    TRACE(5);
    bar_sync<NB_H, 256>();
    WG_FENCE();
#pragma unroll
    for (int k = 0; k < 16; k++) wg_ss40<0>(acc, dsc.tail_a[WG * 16 + k], dsc.tail_b[k]);
    WG_COMMIT();
    uint32_t vt[4][4];
    {
      const uint32_t a = opaque32(L4 + w * 256 + (isC ? WG * 1024 + R_VM : R_QK + 4096 + WG * 5120));
      const uint32_t qa = L16 + R_QK, xa = opaque32(LV + w * 2048 + (WG == 0 ? 0 : (opaque32(lane) & 8) * 64 + R_QK + 5120 - R_VT));
      const uint32_t d = opaque32(L4 + R_XS + rank * 640 + w * 256);
      if (s == 0) {
        mbar_wait_safe(bars + B_WO, 0);
        if (!GO_EARLY && WG == 1 && head == 0 && rank == 0 && w == 0 && elect_one()) red_add_u32(&g_flags[FL_GO], 1);
      }
      mbar_wait(bars + B_FB, last);
      if (WG == 0) mbar_wait(bars + B_VT, par);
      WG_WAIT(0);
      reg_fence<20>(acc);
      TRACE(6);
      const uint32_t p0 = pack2(acc[16], acc[17]), p1 = pack2(acc[18], acc[19]);
      sts32(a, p0); sts32(a + 128, p1);
      if (isC) {
        st_async1(a + to1, p0, bars + B_VM + to1); st_async1(a + to1 + 128, p1, bars + B_VM + to1);
        st_async1(a + to2, p0, bars + B_VM + to2); st_async1(a + to2 + 128, p1, bars + B_VM + to2);
      }
      if (WG == 0) {
        bar_arrive<NB_A, 256>();
        if (Q_FENCE && !isC) fence_async_smem();
#pragma unroll
        for (int i = 0; i < 4; i++) ldsm4(vt[i], xa + (i >> 1) * 1024 + (i & 1) * 256);
        bar_sync<NB_S, 256>();
      } else {
        bar_sync<NB_A, 256>();
        if (!isC) {
          if (w < 3) {
            uint32_t q[8], k[4][4];
            ldsm4t(q, qa + 4096); ldsm4t(k[0], xa); ldsm4t(k[1], xa + 256);
            ldsm4t(q + 4, qa + 4096 + 512); ldsm4t(k[2], xa + 512); ldsm4t(k[3], xa + 768);
            float x[4], y[4];
            hmma0(x, k[0][0], k[0][1], k[0][2], k[0][3], q[0], q[1]); hmma0(y, k[1][0], k[1][1], k[1][2], k[1][3], q[2], q[3]);
            hmma(x, k[2][0], k[2][1], k[2][2], k[2][3], q[4], q[5]); hmma(y, k[3][0], k[3][1], k[3][2], k[3][3], q[6], q[7]);
            const uint32_t s0 = pack2(x[0] + y[0], x[1] + y[1]), s1 = pack2(x[2] + y[2], x[3] + y[3]);
            st_async1(d + to1, s0, bars + B_XS + to1);
            st_async1(d + to2, s0, bars + B_XS + to2);
            if (w < 2) { st_async1(d + to1 + 128, s1, bars + B_XS + to1); st_async1(d + to2 + 128, s1, bars + B_XS + to2); sts32(d + 128, s1); }
            sts32(d, s0);
          }
        }
        bar_arrive<NB_S, 256>();
      }
    }
    if (WG == 1) {
      if (!last && elect_one()) load_chunk(sb + R_GA + w * 4096, s + 1, g1, bars + B_FA);
      {
        if (w > 0 && elect_one()) mbar_expect(bars + B_MB + 8 * w, w < 3 ? 3072 : SELF_STAS ? 28 * 256 : isC ? 18 * 256 : 19 * 256);
      }
      fence_async_smem();
      bar_sync<NB_B, 256>();
    }
    TRACE(7);
    WG_FENCE();
#pragma unroll
    for (int k = 0; k < 16; k++) wg_rs32<1>(acc, W[k][0], W[k][1], W[k][2], W[k][3], dsc.tok[16 + k]);
    WG_COMMIT();
    uint32_t wa[3][4];
    const uint32_t oxa = L16 + R_OX;
    if (WG == 0) {
      const uint32_t vma = oxa - (R_OX - R_VM) + w * 512, oa = opaque32(L4 + w * 512 + R_OX);
      TRACE(8);
      mbar_wait(bars + B_XS, par);
      TRACE(9);
      float sv[10];
      {
        uint32_t x[10];
        ldsm4t(x, oxa - (R_OX - R_XS)); ldsm4t(x + 4, oxa - (R_OX - R_XS) + 512); ldsm2t(x + 8, oxa - (R_OX - R_XS) + 1024);
        bar_arrive<NB_B, 256>();
#pragma unroll
        for (int j = 0; j < 5; j++) x[j] = hadd2(x[j], x[j + 5]);
        exp10(sv, x);
      }
      WG_WAIT(0);
      bar_arrive<NB_X, 256>();
      mbar_wait(bars + B_VM, par);
      uint32_t vm[4];
      ldsm4(vm, vma);
      uint32_t pb[5];
#pragma unroll
      for (int j = 0; j < 5; j++) pb[j] = pack2(sv[2 * j], sv[2 * j + 1]);
      TRACE(10);
      float o0[4], o1[4], sm[4];
      const uint32_t ONE = 0x3f803f80u;
      hmma0(o0, vt[0][0], vt[0][1], vt[0][2], vt[0][3], pb[0], pb[1]);
      hmma0(o1, vt[2][0], vt[2][1], vt[2][2], vt[2][3], pb[0], pb[1]);
      hmma0(sm, ONE, ONE, ONE, ONE, pb[0], pb[1]);
      hmma(sm, ONE, ONE, ONE, ONE, pb[2], pb[3]);
      hmma(o0, vt[1][0], vt[1][1], vt[1][2], vt[1][3], pb[2], pb[3]);
      hmma(o1, vt[3][0], vt[3][1], vt[3][2], vt[3][3], pb[2], pb[3]);
      hmma_k8(sm, ONE, ONE, pb[4]);
      hmma_k8(o0, vm[0], vm[1], pb[4]);
      hmma_k8(o1, vm[2], vm[3], pb[4]);
#pragma unroll
      for (int i = 0; i < 3; i++) ldsm4t(wa[i], woa + i * 4096);
      __syncwarp();
      const float i0 = rcp(sm[0]), i1 = rcp(sm[1]);
      sts32(oa, pack2(o0[0] * i0, o0[1] * i1)); sts32(oa + 128, pack2(o0[2] * i0, o0[3] * i1));
      sts32(oa + 256, pack2(o1[0] * i0, o1[1] * i1)); sts32(oa + 384, pack2(o1[2] * i0, o1[3] * i1));
      TRACE(11);
      bar_sync<NB_C, 128>();
    } else {
      if (!isC) {
        constexpr uint64_t dQ = mkdesc(0x400 + R_QK, 128, 1024, 0), dK = mkdesc(0x400 + R_QK + 5120, 128, 1024, 0);
        float sc[16];
        zero_regs<16>(sc);
        WG_FENCE();
#pragma unroll
        for (int k = 0; k < 4; k++) wg_ss32<1>(sc, dK + k * 16, dQ + k * 16);
        WG_COMMIT();
        const uint32_t top = rank == 0 ? to2 : to1, e = L4 + R_P + w * 256;
        WG_WAIT(0);
        bar_sync<NB_X, 256>();
        if (!last && elect_one()) load_chunk(sb + R_GB + w * 4096, s + 1, g2, bars + B_FB);
        reg_fence<16>(sc);
        if (w < 3) {
#pragma unroll
          for (int j = 0; j < 8; j++) {
            if ((j & 1) ? (j > 1 && (w == 0 || (w == 1 && j == 7))) : (j >= 4 || w != 1)) {
              const uint32_t t = pack2(sc[2 * j], sc[2 * j + 1]), o = (j >> 1) * 768 + (j & 1) * 128;
              st_async1(e + top + 3072 + o, t, bars + top + B_TS);
              sts32(e + o, t);
            }
          }
          __syncwarp();
          if (elect_one()) mbar_arrive(bars + B_TS);
        }
      } else {
        WG_WAIT(0);
        bar_sync<NB_X, 256>();
        if (!last && elect_one()) load_chunk(sb + R_GB + w * 4096, s + 1, g2, bars + B_FB);
      }
      TRACE(8);
      mbar_wait(bars + B_FA, 1);
      TRACE(11);
    }
    if (has_wo) {
      float* rslot = SLOT(s);
      uint32_t ob[4][4];
      float c[3][4];
      if (WG == 1) {
#pragma unroll
        for (int i = 0; i < 3; i++) ldsm4t(wa[i], woa + i * 4096);
        bar_sync<NB_D, 256>();
      }
      ldsm4t(ob[0], oxa);
      __syncwarp();
#pragma unroll
      for (int k = 0; k < 8; k++) {
        uint32_t nx[3][4];
        if ((k & 1) == 0 && k < 6) { ldsm4t(ob[(k >> 1) + 1], oxa + ((k >> 1) + 1) * 512); __syncwarp(); }
#pragma unroll
        for (int i = 0; i < 3; i++) {
          const uint32_t* o = ob[k >> 1] + (k & 1) * 2;
          if (k < 7) { ldsm4t(nx[i], woa + i * 4096 + (k + 1) * 512); if (i == 2) __syncwarp(); }
          if (k == 0) hmma0(c[i], wa[i][0], wa[i][1], wa[i][2], wa[i][3], o[0], o[1]);
          else hmma(c[i], wa[i][0], wa[i][1], wa[i][2], wa[i][3], o[0], o[1]);
#pragma unroll
          for (int q = 0; q < 4; q++) if (k < 7) wa[i][q] = nx[i][q];
        }
        if (k == ND_K && WG == 0) bar_arrive<NB_D, 256>();
      }
      const float* cv = &c[0][0];
      uint32_t r[6];
#pragma unroll
      for (int j = 0; j < 6; j++) r[j] = pack2(cv[2 * j], cv[2 * j + 1]);
      asm volatile("{\n.reg .pred p;\nsetp.lt.s32 p, %8, 0;\n@p bra.uni SKIP;\n"
                   "red.relaxed.gpu.global.add.noftz.v4.bf16x2 [%0], {%1, %2, %3, %7};\n"
                   "red.relaxed.gpu.global.add.noftz.v4.bf16x2 [%0+1024], {%4, %5, %6, %7};\nSKIP:\n}"
                   :: "l"(rslot), "r"(r[0]), "r"(r[1]), "r"(r[2]), "r"(r[3]), "r"(r[4]), "r"(r[5]), "r"(0x3f800000), "r"(s) : "memory");
    } else {
      bar_arrive<NB_D, 256>();
      if ((s & 3) == 0) {
        fence_gpu();
        if (s > 0 && elect_one()) red_add_u32(&g_flags[FL_ATT + 2 * (s - 4)], 1);
      }
      if (PFD && head < 8 && (PFD > 90 || s + PFD < NSEG) && elect_one())
        asm volatile("cp.async.bulk.prefetch.L2.global [%0], 4096;" :: "l"(g_h + (size_t)((PFD > 90 ? 0 : s + PFD) * 16 + head * 2 + rank) * 4096) : "memory");
      if (rank == 0 || head < 16)
        reinterpret_cast<uint4*>(g_slot)[((s + CLR_D) & 3) * 3072 + ((s + CLR_D) & 4) * 8 + rank * 2048 + head * 64 + opaque32(lane)] = make_uint4(0, 0, 0, 0);
    }
    const uint32_t t_red = clk32();
    uint32_t v[8];
    const float* slot = SLOT(s);
    TRACE(13);
    if (WG == 0) {
      if (!isC) {
        const int ln = opaque32(lane), kg = w - (ln >> 3);
        const uint32_t r16 = sb + R_P + w * 768 + (ln & 7) * 16;
        const uint32_t ta = r16 + (kg >= 0 ? kg * 128 : 640);
        const int dg = (ln >> 2) - 2 * (ln & 3);
        const uint32_t keep = dg > 0 ? 0xffffffffu : dg == 0 ? 0x0000ffffu : 0u;
        mbar_wait(bars + B_TS, par);
        uint32_t x[6], y[4];
        ldsm4t(x, ta); ldsm4t(y, ta + 3072); ldsm2t(x + 4, r16 + 512 + ((ln >> 3) & 1) * 3072);
#pragma unroll
        for (int j = 0; j < 5; j++) x[j] = hadd2(x[j], j < 4 ? y[j] : x[5]);
        x[0] = (x[0] & keep) | (0xff80ff80u & ~keep);
        float sv[10];
        exp10(sv, x);
        float sum = (((sv[0] + sv[1]) + (sv[2] + sv[3])) + ((sv[4] + sv[5]) + (sv[6] + sv[7]))) + (sv[8] + sv[9]);
        sum += __shfl_xor_sync(0xffffffffu, sum, 1);
        sum += __shfl_xor_sync(0xffffffffu, sum, 2);
        const float inv = rcp(sum);
#pragma unroll
        for (int j = 0; j < 5; j++) x[j] = pack2(sv[2 * j] * inv, sv[2 * j + 1] * inv);
        stsm4(r16 + (kg & 3) * 128, x);
        sts32(sb + ln * 4 + w * 768 + R_P + 512, x[4]);
        fence_async_smem();
        bar_arrive<NB_P, 256>();
      }
      while (clk32() - t_red < POLL_DELAY) {}
      load_red(v, slot);
      bar_sync<NB_E, 256>();
    } else {
      mbar_wait(bars + B_FB, 1);
    }
    TRACE(14);
    float ao[16];
    if (WG == 1) zero_regs<16>(ao);
    WG_FENCE();
#pragma unroll
    for (int k = 0; k < 32; k++) {
      if (WG == 0 && k == 16) WG_COMMIT();
      wg_rs32<1>(acc, W[16 + k][0], W[16 + k][1], W[16 + k][2], W[16 + k][3], dsc.tok[k]);
    }
    WG_COMMIT();
    TRACE(12);
    if (WG == 1) {
      if (!isC) {
        constexpr uint64_t dP = mkdesc(0x400 + R_P, 128, 768, 0);
        const uint64_t dV = mkdesc(0x400 + R_VT, 128, 512, 0) + rank * 256, dM = mkdesc(0x400 + R_VM, 0, 128, 0) + rank * 64;
        bar_sync<NB_P, 256>();
        WG_FENCE();
        wg_ss32<0>(ao, dV, dP); wg_ss32<0>(ao, dV + 16, dP + 16); wg_ss32<0>(ao, dM, dP + 32);
        WG_COMMIT();
      }
      bar_arrive<NB_E, 256>();
      if (elect_one()) mbar_expect(bars + B_XS + 8 * w, arm_bytes);
      while (clk32() - t_red < POLL_DELAY1) {}
      load_red(v, slot);
      bar_arrive<NB_W0, 128>();
    } else {
      WG_WAIT(1);
      bar_arrive<NB_F, 256>();
      sched_fence(head, 100);
      v[3] = opaque32(v[3]);
      const uint32_t tries = finish_red(v, slot);
      forward(std::integral_constant<int, 0>(), v, s, tries);
      TRACE(16);
    }
    WG_WAIT(0);
    reg_fence<16>(acc);
    if (WG == 0) bar_arrive<NB_G, 256>();
    TRACE(15);
    {
      uint32_t pq[8];
#pragma unroll
      for (int j = 0; j < 8; j++) pq[j] = pack2(acc[2 * j], acc[2 * j + 1]);
      if (WG == 1) {
        reg_fence<16>(ao);
#pragma unroll
        for (int j = 0; j < 8; j++) pk[j] = pack2(ao[2 * j], ao[2 * j + 1]);
      }
      if (!isC) {
        const uint32_t q = L4 + w * 256 + R_QK + WG * 5120;
#pragma unroll
        for (int j = 0; j < 8; j++) sts32(q + (j >> 1) * 1024 + (j & 1) * 128, pq[j]);
        if (WG == 1 && !ATT_LATE && s >= 0) store_att(s);
      } else {
        const uint32_t a = LV + warp * 1024;
        stsm4(a, pq); stsm4(a + 256, pq + 4);
      }
    }
    TRACE(17);
    if (WG == 1) {
      auto refill = [&]() {
        bar_sync<NB_F, 256>();
        if (s < NSEG - 2 && elect_one()) load_chunk(sb + R_GA + w * 4096, s + 2, 12 + w, bars + B_FA);
      };
      if (RF_FIRST) refill();
      if (has_wo) { v[3] = opaque32(v[3]); const uint32_t tries = finish_red(v, slot); forward(std::integral_constant<int, 1>(), v, s, tries); }
      if (!RF_FIRST) refill();
      TRACE(16);
    }
    if (isC && V_FENCE) { fence_async_smem(); __syncwarp(); }
    TRACE(18);
  }
  {
    constexpr uint32_t par = NSEG & 1;
    if (WG == 1 || isC) {
      float c[NCH][4], m[4];
      uint32_t b[3][6];
      const uint32_t ma = L16, m8 = L8;
#pragma unroll
      for (int i = 0; i < 18; i++) {
        if (i < 16) {
          if (i % 4 == 0) mbar_wait(bars + B_MB + (i / 4) * 8, par ^ 1);
          if (i < 12) { lds128(b[i % 3], ma + R_M1 + i * 768); lds64(b[i % 3] + 4, m8 + R_M1 + 512 + i * 768); }
          else { ldsm4(b[i % 3], ma + R_M2 + 4096 + (i - 12) * 768); ldsm2(b[i % 3] + 4, ma + R_M2 + 4096 + 512 + (i - 12) * 768); }
          if (i == CX_I && isC) send_vt();
          __syncwarp();
        }
        if (i >= 2) {
          const int j = i - 2;
#pragma unroll
          for (int q = 0; q < 3; q++) {
            const uint32_t* f = W[3 * j + q];
            if (3 * j + q < NCH) hmma0(c[3 * j + q], f[0], f[1], f[2], f[3], b[j % 3][2 * q], b[j % 3][2 * q + 1]);
            else hmma(c[(3 * j + q) % NCH], f[0], f[1], f[2], f[3], b[j % 3][2 * q], b[j % 3][2 * q + 1]);
          }
        }
      }
#pragma unroll
      for (int j = 0; j < 4; j++) m[j] = NCH == 3 ? (c[0][j] + c[1][j]) + c[2][j] : (c[0][j] + c[1][j]) + (c[2][j] + c[NCH - 1][j]);
      if (isC) bar_sync<NB_H, 256>();
      WG_FENCE();
#pragma unroll
      for (int k = 0; k < 16; k++) wg_ss8(m, dsc.tail_a[WG * 16 + k], dsc.tail_b[k] + 1024);
      WG_COMMIT();
      const uint32_t a = opaque32(L4 + w * 256 + (isC ? WG * 1024 + R_VM : R_QK + 4096 + WG * 5120));
      WG_WAIT(0);
      reg_fence<4>(m);
      const uint32_t p0 = pack2(m[0], m[1]), p1 = pack2(m[2], m[3]);
      if (isC) {
        st_async1(a + to1, p0, bars + B_VM + to1); st_async1(a + to1 + 128, p1, bars + B_VM + to1);
        st_async1(a + to2, p0, bars + B_VM + to2); st_async1(a + to2 + 128, p1, bars + B_VM + to2);
      } else {
        sts32(a, p0); sts32(a + 128, p1);
      }
    }
    if (WG == 1) bar_sync<NB_G, 256>();
    if (isC) {
      asm volatile("barrier.cluster.arrive.relaxed.aligned;" ::: "memory");
    } else if (WG == 1) {
      constexpr uint64_t dQ = mkdesc(0x400 + R_QK, 128, 1024, 0), dK = mkdesc(0x400 + R_QK + 5120, 128, 1024, 0);
      float sc[16];
      zero_regs<16>(sc);
      fence_async_smem();
      bar_sync<NB_B, 256>();
      WG_FENCE();
#pragma unroll
      for (int k = 0; k < 4; k++) wg_ss32<1>(sc, dK + k * 16, dQ + k * 16);
      WG_COMMIT();
      const uint32_t top = rank == 0 ? to2 : to1, e = L4 + R_P + w * 256;
      WG_WAIT(0);
      reg_fence<16>(sc);
      if (w < 3) {
#pragma unroll
        for (int j = 0; j < 8; j++) {
          if ((j & 1) ? (j > 1 && (w == 0 || (w == 1 && j == 7))) : (j >= 4 || w != 1)) {
            const uint32_t t = pack2(sc[2 * j], sc[2 * j + 1]), o = (j >> 1) * 768 + (j & 1) * 128;
            st_async1(e + top + 3072 + o, t, bars + top + B_TS);
            sts32(e + o, t);
          }
        }
        __syncwarp();
        if (elect_one()) mbar_arrive(bars + B_TS);
      }
      constexpr uint64_t dP = mkdesc(0x400 + R_P, 128, 768, 0);
      const uint64_t dV = mkdesc(0x400 + R_VT, 128, 512, 0) + rank * 256, dM = mkdesc(0x400 + R_VM, 0, 128, 0) + rank * 64;
      float ao[16];
      zero_regs<16>(ao);
      mbar_wait(bars + B_VT, par);
      mbar_wait(bars + B_VM, par);
      asm volatile("barrier.cluster.arrive.relaxed.aligned;" ::: "memory");
      bar_sync<NB_P, 256>();
      WG_FENCE();
      wg_ss32<0>(ao, dV, dP); wg_ss32<0>(ao, dV + 16, dP + 16); wg_ss32<0>(ao, dM, dP + 32);
      WG_COMMIT();
      WG_WAIT(0);
      reg_fence<16>(ao);
#pragma unroll
      for (int j = 0; j < 8; j++) pk[j] = pack2(ao[2 * j], ao[2 * j + 1]);
      store_att(NSEG - 1);
      bar_sync<NB_C, 128>();
      if (w == 0 && elect_one()) { fence_gpu(); red_add_u32(&g_flags[FL_ATT + 8 * 15], 1); }
    } else {
      fence_async_smem();
      bar_arrive<NB_B, 256>();
      const int ln = opaque32(lane), kg = w - (ln >> 3);
      const uint32_t r16 = sb + R_P + w * 768 + (ln & 7) * 16;
      const uint32_t ta = r16 + (kg >= 0 ? kg * 128 : 640);
      const int dg = (ln >> 2) - 2 * (ln & 3);
      const uint32_t keep = dg > 0 ? 0xffffffffu : dg == 0 ? 0x0000ffffu : 0u;
      mbar_wait(bars + B_TS, par);
      asm volatile("barrier.cluster.arrive.relaxed.aligned;" ::: "memory");
      uint32_t x[6], y[4];
      ldsm4t(x, ta); ldsm4t(y, ta + 3072); ldsm2t(x + 4, r16 + 512 + ((ln >> 3) & 1) * 3072);
#pragma unroll
      for (int j = 0; j < 5; j++) x[j] = hadd2(x[j], j < 4 ? y[j] : x[5]);
      x[0] = (x[0] & keep) | (0xff80ff80u & ~keep);
      float sv[10];
      exp10(sv, x);
      float sum = (((sv[0] + sv[1]) + (sv[2] + sv[3])) + ((sv[4] + sv[5]) + (sv[6] + sv[7]))) + (sv[8] + sv[9]);
      sum += __shfl_xor_sync(0xffffffffu, sum, 1);
      sum += __shfl_xor_sync(0xffffffffu, sum, 2);
      const float inv = rcp(sum);
#pragma unroll
      for (int j = 0; j < 5; j++) x[j] = pack2(sv[2 * j] * inv, sv[2 * j + 1] * inv);
      stsm4(r16 + (kg & 3) * 128, x);
      sts32(sb + ln * 4 + w * 768 + R_P + 512, x[4]);
      fence_async_smem();
      bar_arrive<NB_P, 256>();
    }
    asm volatile("barrier.cluster.wait.aligned;" ::: "memory");
  }
#undef L16
#undef L8
#undef L4
#undef SLOT
#undef LV
}

__global__ void __cluster_dims__(3, 1, 1) __launch_bounds__(256, 1)
kernel_R(const __grid_constant__ CUtensorMap tmq, const __grid_constant__ CUtensorMap tmk, const __grid_constant__ CUtensorMap tmv,
         const __grid_constant__ CUtensorMap tmo, const __grid_constant__ CUtensorMap tmm, const __nv_bfloat16* __restrict__ x,
         const __nv_bfloat16* __restrict__ mem0, const __nv_bfloat16* __restrict__ cvec, const __grid_constant__ RDesc dsc) {
  extern __shared__ __align__(1024) uint8_t smem[];
  const uint32_t sb = smem_u32(smem);
  uint32_t rank; asm("mov.u32 %0, %%cluster_ctarank;" : "=r"(rank));
  rank = __shfl_sync(0xffffffffu, rank, 0);
  const int cta = blockIdx.x, head = __shfl_sync(0xffffffffu, cta / 3, 0);
  const int tid = threadIdx.x, lane = tid & 31;
  const int warp = __shfl_sync(0xffffffffu, tid >> 5, 0);
  const int wg = warp >> 2, w = warp & 3;
  const uint32_t bars = sb + R_BAR;
  const CUtensorMap* tmw = rank == 2 ? &tmv : (wg == 0 ? &tmq : &tmk);
  const int fcol = head * 128 + (rank == 2 ? wg * 64 : (int)rank * 64);

  asm volatile("griddepcontrol.launch_dependents;");
  uint32_t W[48][4];
  {
    if (sb != (rank << 24) + 0x400) __trap();
    if (tid == 0) {
      sts64(bars + 248, rank, head);
      mbar_init(bars + B_MB, 4); mbar_init(bars + B_MB + 8, 1); mbar_init(bars + B_MB + 16, 1); mbar_init(bars + B_MB + 24, SELF_STAS ? 1 : rank == 2 ? 5 : 4);
      for (int i = B_XS; i <= B_X; i += 8) mbar_init(bars + i, i == B_FA || i == B_FB || (i == B_TS && rank < 2) ? 4 : 1);
      asm volatile("fence.mbarrier_init.release.cluster;" ::: "memory");
      fence_async_smem();
    }
    __syncthreads();
    asm volatile("barrier.cluster.arrive.relaxed.aligned;" ::: "memory");
    TS(0);
    const int nwm = rank == 0 ? 6 : 5, wm0 = rank == 0 ? 0 : 5 * rank + 1, nrg = cta < 64 ? 3 : 2;
    if (elect_one()) {
      if (warp == 0) { mbar_expect(bars + B_WM, nwm * 8192); mbar_expect(bars + B_X, nrg * 16384); }
      if (warp < nwm) tma2d_once(sb + R_GA + warp * 8192, &tmm, head * 64, (wm0 + warp) * 64, bars + B_WM);
#pragma unroll 1
      for (int r = 0; r < nrg; r++) bulk_g2s(sb + R_TAIL + (r * 8 + warp) * 2064, x + (size_t)((cta + 96 * r) * 8 + warp) * D_, 2048, bars + B_X);
      if (w == 0) mbar_expect(bars + B_STG + wg * 16, 49152);
      if (w < 2) tma2d_once(sb + R_WO + wg * 49152 + w * 8192, tmw, fcol, rot_chunk(w, rank) * 64, bars + B_STG + wg * 16);
    }
    float* scr = reinterpret_cast<float*>(smem + R_VT);
#pragma unroll 1
    for (int i = tid; i < nwm * 64; i += 256) {
      const float c = __bfloat162float(cvec[wm0 * 64 + i]);
      scr[i] = __bfloat162float(__float2bfloat16(c / (1.f + __expf(-c))));
    }
    if (tid < 128) {
      uint32_t e[4] = {0u, 0u, 0u, 0u};
      if (cta >= 72 && (tid & 32)) {
        const uint16_t* mp = reinterpret_cast<const uint16_t*>(mem0) + 2 * (lane & 3) * D_ + (lane >> 2);
#pragma unroll
        for (int q = 0; q < 3; q++) {
          const int n = 3 * (tid >> 6) + q, col = wo_tile(3 * (cta & 7) + (n >> 1), (cta - 72) >> 3) * 16 + 8 * (n & 1);
          e[q] = mp[col] | (uint32_t)mp[col + D_] << 16;
        }
        e[3] = 0x42000000u;
      }
      reinterpret_cast<uint4*>(g_slot)[cta * 128 + tid] = make_uint4(e[0], e[1], e[2], e[3]);
    }
    __syncthreads();
    TS(1);
    mbar_wait_safe(bars + B_WM, 0);
    if (elect_one()) tma2d_once(sb + R_WO + wg * 49152 + (2 + w) * 8192, tmw, fcol, rot_chunk(2 + w, rank) * 64, bars + B_STG + wg * 16);
    {
      float a[8];
#pragma unroll
      for (int j = 0; j < 8; j++) a[j] = 0.f;
#pragma unroll 2
      for (int i = 0; i < 2 * nwm; i++) {
        uint32_t u[4];
        lds128(u, sb + R_GA + i * 4096 + tid * 16);
        const float sc = scr[i * 32 + (tid >> 3)];
#pragma unroll
        for (int j = 0; j < 4; j++) { a[2 * j] += sc * bf_lo(u[j]); a[2 * j + 1] += sc * bf_hi(u[j]); }
      }
#pragma unroll
      for (int j = 0; j < 8; j++) { a[j] += __shfl_xor_sync(0xffffffffu, a[j], 8); a[j] += __shfl_xor_sync(0xffffffffu, a[j], 16); }
      if (lane < 8) {
        sts128(sb + R_VT + 1536 + warp * 256 + lane * 32, __float_as_uint(a[0]), __float_as_uint(a[1]), __float_as_uint(a[2]), __float_as_uint(a[3]));
        sts128(sb + R_VT + 1552 + warp * 256 + lane * 32, __float_as_uint(a[4]), __float_as_uint(a[5]), __float_as_uint(a[6]), __float_as_uint(a[7]));
      }
    }
    __syncthreads();
    TS(2);
    if (warp == 7) {
      float t0 = 0.f, t1 = 0.f;
#pragma unroll
      for (int i = 0; i < 8; i++) { float t[2]; lds64f(t, sb + R_VT + 1536 + i * 256 + lane * 8); t0 += t[0]; t1 += t[1]; }
      reinterpret_cast<float2*>(g_modp + rank * 2048 + head * 64)[lane] = make_float2(t0, t1);
      fence_gpu();
      __syncwarp();
      if (lane == 0) red_add_u32(&g_flags[FL_S1], 1);
      __syncwarp();
    }
    mbar_wait_safe(bars + B_X, 0);
#pragma unroll 1
    for (int r = 0; r < nrg; r++) {
      float f[32];
#pragma unroll
      for (int i = 0; i < 4; i++) {
        uint32_t u[4];
        lds128(u, sb + R_TAIL + (r * 8 + warp) * 2064 + i * 512 + lane * 16);
#pragma unroll
        for (int j = 0; j < 4; j++) { f[8 * i + 2 * j] = bf_lo(u[j]); f[8 * i + 2 * j + 1] = bf_hi(u[j]); }
      }
      float t = 0.f;
#pragma unroll
      for (int i = 0; i < 32; i++) t += f[i];
#pragma unroll
      for (int o = 1; o < 32; o <<= 1) t += __shfl_xor_sync(0xffffffffu, t, o);
      const float mean = t * (1.f / D_);
      t = 0.f;
#pragma unroll
      for (int i = 0; i < 32; i++) t = fmaf(f[i] - mean, f[i] - mean, t);
#pragma unroll
      for (int o = 1; o < 32; o <<= 1) t += __shfl_xor_sync(0xffffffffu, t, o);
      const float rstd = rsqrtf(t * (1.f / D_) + 1e-5f);
      if (lane == 0) sts64(sb + R_VT + 3584 + (r * 8 + warp) * 8, __float_as_uint(rstd), __float_as_uint(-mean * rstd));
    }
    TS(3);
    if (w < PF1 && elect_one()) tma2d_prefetch(tmw, fcol, rot_chunk(6 + w, rank) * 64);
    if (tid == 0) wait_flag(&g_flags[FL_S1], 96);
    __syncthreads();
    TS(4);
    {
      float4 p[6];
#pragma unroll
      for (int i = 0; i < 6; i++) p[i] = __ldcg(reinterpret_cast<const float4*>(g_modp + (i >> 1) * 2048) + 2 * tid + (i & 1));
      if (w < PF2 && elect_one()) tma2d_prefetch(tmw, fcol, (9 + w) * 64);
      sts128(sb + R_VT + 5120 + tid * 16, pack2(p[0].x + p[2].x + p[4].x, p[0].y + p[2].y + p[4].y), pack2(p[0].z + p[2].z + p[4].z, p[0].w + p[2].w + p[4].w),
             pack2(p[1].x + p[3].x + p[5].x, p[1].y + p[3].y + p[5].y), pack2(p[1].z + p[3].z + p[5].z, p[1].w + p[3].w + p[5].w));
    }
    __syncthreads();
#pragma unroll 2
    for (int it = 0; it < 4 * nrg; it++) {
      const int r = it >> 2, rg = cta + 96 * r, c = 16 * warp + (lane >> 3) + 4 * (it & 3);
      uint32_t a[4], b[4], u[4], o[4];
      float t[2];
      lds128(u, sb + R_TAIL + (r * 8 + (lane & 7)) * 2064 + c * 16);
      lds128(a, sb + R_VT + 5120 + c * 16); lds128(b, sb + R_VT + 7168 + c * 16);
      lds64f(t, sb + R_VT + 3584 + (r * 8 + (lane & 7)) * 8);
#pragma unroll
      for (int j = 0; j < 4; j++)
        o[j] = pack2(fmaf(fmaf(bf_lo(u[j]), t[0], t[1]), 1.f + bf_lo(b[j]), bf_lo(a[j])), fmaf(fmaf(bf_hi(u[j]), t[0], t[1]), 1.f + bf_hi(b[j]), bf_hi(a[j])));
      *reinterpret_cast<uint4*>(g_h + (size_t)(rg >> 2) * 65536 + (lane & 7) * 16 + (c & 7) * 128 +
                                (c < 96 ? (c >> 3) * 4096 + (rg & 3) * 1024 : 49152 + (rg & 3) * 4096 + ((c >> 3) - 12) * 1024)) =
          make_uint4(o[0], o[1], o[2], o[3]);
    }
    TS(5);
    __syncthreads();
    TS(6);
    if (w < PF3 && elect_one()) tma2d_once(sb + R_TAIL + warp * 8192, tmw, fcol, 768 + w * 64, bars + B_TAIL);
    if (warp == 3 && lane == 0) { fence_gpu(); red_add_u32(&g_flags[FL_S2], 1); }
    __syncwarp();

    const uint32_t a0 = opaque32(sb + R_WO + wg * 49152 + ((lane >> 4) * 8 + (lane & 7)) * 128 + (((2 * w + ((lane >> 3) & 1)) ^ (lane & 7)) << 4));
    mbar_wait_safe(bars + B_STG + wg * 16, 0);
    TS(7);
#pragma unroll
    for (int i = 0; i < 24; i++) ldsm4t(W[i], a0 + i * 2048);
    if (tid == 0) wait_flag(&g_flags[FL_S2], 96);
    __syncthreads();
    asm volatile("fence.proxy.async.global;" ::: "memory");
    if (elect_one()) {
      if (wg == 0) load_chunk(sb + R_GA + w * 4096, 0, 12 + w, bars + B_FA);
      if (w == 0) mbar_expect(bars + B_STG + wg * 16 + 8, 49152);
#pragma unroll 1
      for (int c = w; c < 6; c += 4) tma2d_once(sb + R_WO + wg * 49152 + c * 8192, tmw, fcol, rot_chunk(6 + c, rank) * 64, bars + B_STG + wg * 16 + 8);
      if (warp == 0) mbar_expect(bars + B_TAIL, 65536);
      if (w >= PF3) tma2d_once(sb + R_TAIL + warp * 8192, tmw, fcol, 768 + w * 64, bars + B_TAIL);
      if (wg == 1) mbar_expect(bars + B_XS + 8 * w, w == 2 ? 0 : arm_size(w, rank == 2));
#pragma unroll 1
      for (int i = warp; i < PF4; i += 8) tma2d_prefetch(&tmo, 16 * wo_tile(i, rank), head * 128);
    }
    TS(8);
    mbar_wait_safe(bars + B_STG + wg * 16 + 8, 0);
    TS(9);
#pragma unroll
    for (int i = 0; i < 24; i++) ldsm4t(W[24 + i], a0 + i * 2048);
    __syncthreads();
    if (elect_one()) {
      const int n = rank == 2 ? 22 : 21;
      if (warp == 0) mbar_expect(bars + B_WO, n * 4096);
#pragma unroll 1
      for (int i = warp; i < n; i += 8) tma2d(sb + R_WO + i * 4096, &tmo, 16 * wo_tile(i, rank), head * 128, bars + B_WO);
    }
    sts32(sb + R_P + warp * 768 + 640 + lane * 4, wg == 0 ? 0u : 0xff80ff80u);
    mbar_wait_safe(bars + B_TAIL, 0);
    if (GO_EARLY && cta == GO_EARLY - 1 && tid == 0) red_add_u32(&g_flags[FL_GO], 1);
    asm volatile("barrier.cluster.wait.aligned;\nbarrier.cluster.arrive.relaxed.aligned;\nbarrier.cluster.wait.aligned;" ::: "memory");
  }
  uint32_t rh[2];
  lds64(rh, bars + 248);
  rh[0] = __shfl_sync(0xffffffffu, rh[0], 0); rh[1] = __shfl_sync(0xffffffffu, rh[1], 0);
  if (wg == 0) r_main<0>(W, dsc, rh[1], rh[0], lane, w);
  else r_main<1>(W, dsc, rh[1], rh[0], lane, w);
}

template <int TA, bool FIRST> __device__ __forceinline__ void wg_ss256(float* d, uint64_t a, uint64_t b) {
  if (FIRST)
    asm volatile("wgmma.mma_async.sync.aligned.m64n256k16.f32.bf16.bf16 {%0,%1,%2,%3,%4,%5,%6,%7,%8,%9,%10,%11,%12,%13,%14,%15,%16,%17,%18,%19,%20,%21,%22,%23,%24,%25,%26,%27,%28,%29,%30,%31,%32,%33,%34,%35,%36,%37,%38,%39,%40,%41,%42,%43,%44,%45,%46,%47,%48,%49,%50,%51,%52,%53,%54,%55,%56,%57,%58,%59,%60,%61,%62,%63,%64,%65,%66,%67,%68,%69,%70,%71,%72,%73,%74,%75,%76,%77,%78,%79,%80,%81,%82,%83,%84,%85,%86,%87,%88,%89,%90,%91,%92,%93,%94,%95,%96,%97,%98,%99,%100,%101,%102,%103,%104,%105,%106,%107,%108,%109,%110,%111,%112,%113,%114,%115,%116,%117,%118,%119,%120,%121,%122,%123,%124,%125,%126,%127}, %128, %129, 0, 1, 1, %130, 1;"
               : "=f"(d[0]), "=f"(d[1]), "=f"(d[2]), "=f"(d[3]), "=f"(d[4]), "=f"(d[5]), "=f"(d[6]), "=f"(d[7]),
                 "=f"(d[8]), "=f"(d[9]), "=f"(d[10]), "=f"(d[11]), "=f"(d[12]), "=f"(d[13]), "=f"(d[14]), "=f"(d[15]),
                 "=f"(d[16]), "=f"(d[17]), "=f"(d[18]), "=f"(d[19]), "=f"(d[20]), "=f"(d[21]), "=f"(d[22]), "=f"(d[23]),
                 "=f"(d[24]), "=f"(d[25]), "=f"(d[26]), "=f"(d[27]), "=f"(d[28]), "=f"(d[29]), "=f"(d[30]), "=f"(d[31]),
                 "=f"(d[32]), "=f"(d[33]), "=f"(d[34]), "=f"(d[35]), "=f"(d[36]), "=f"(d[37]), "=f"(d[38]), "=f"(d[39]),
                 "=f"(d[40]), "=f"(d[41]), "=f"(d[42]), "=f"(d[43]), "=f"(d[44]), "=f"(d[45]), "=f"(d[46]), "=f"(d[47]),
                 "=f"(d[48]), "=f"(d[49]), "=f"(d[50]), "=f"(d[51]), "=f"(d[52]), "=f"(d[53]), "=f"(d[54]), "=f"(d[55]),
                 "=f"(d[56]), "=f"(d[57]), "=f"(d[58]), "=f"(d[59]), "=f"(d[60]), "=f"(d[61]), "=f"(d[62]), "=f"(d[63]),
                 "=f"(d[64]), "=f"(d[65]), "=f"(d[66]), "=f"(d[67]), "=f"(d[68]), "=f"(d[69]), "=f"(d[70]), "=f"(d[71]),
                 "=f"(d[72]), "=f"(d[73]), "=f"(d[74]), "=f"(d[75]), "=f"(d[76]), "=f"(d[77]), "=f"(d[78]), "=f"(d[79]),
                 "=f"(d[80]), "=f"(d[81]), "=f"(d[82]), "=f"(d[83]), "=f"(d[84]), "=f"(d[85]), "=f"(d[86]), "=f"(d[87]),
                 "=f"(d[88]), "=f"(d[89]), "=f"(d[90]), "=f"(d[91]), "=f"(d[92]), "=f"(d[93]), "=f"(d[94]), "=f"(d[95]),
                 "=f"(d[96]), "=f"(d[97]), "=f"(d[98]), "=f"(d[99]), "=f"(d[100]), "=f"(d[101]), "=f"(d[102]), "=f"(d[103]),
                 "=f"(d[104]), "=f"(d[105]), "=f"(d[106]), "=f"(d[107]), "=f"(d[108]), "=f"(d[109]), "=f"(d[110]), "=f"(d[111]),
                 "=f"(d[112]), "=f"(d[113]), "=f"(d[114]), "=f"(d[115]), "=f"(d[116]), "=f"(d[117]), "=f"(d[118]), "=f"(d[119]),
                 "=f"(d[120]), "=f"(d[121]), "=f"(d[122]), "=f"(d[123]), "=f"(d[124]), "=f"(d[125]), "=f"(d[126]), "=f"(d[127])
               : "l"(a), "l"(b), "n"(TA));
  else
    asm volatile("wgmma.mma_async.sync.aligned.m64n256k16.f32.bf16.bf16 {%0,%1,%2,%3,%4,%5,%6,%7,%8,%9,%10,%11,%12,%13,%14,%15,%16,%17,%18,%19,%20,%21,%22,%23,%24,%25,%26,%27,%28,%29,%30,%31,%32,%33,%34,%35,%36,%37,%38,%39,%40,%41,%42,%43,%44,%45,%46,%47,%48,%49,%50,%51,%52,%53,%54,%55,%56,%57,%58,%59,%60,%61,%62,%63,%64,%65,%66,%67,%68,%69,%70,%71,%72,%73,%74,%75,%76,%77,%78,%79,%80,%81,%82,%83,%84,%85,%86,%87,%88,%89,%90,%91,%92,%93,%94,%95,%96,%97,%98,%99,%100,%101,%102,%103,%104,%105,%106,%107,%108,%109,%110,%111,%112,%113,%114,%115,%116,%117,%118,%119,%120,%121,%122,%123,%124,%125,%126,%127}, %128, %129, 1, 1, 1, %130, 1;"
               : "+f"(d[0]), "+f"(d[1]), "+f"(d[2]), "+f"(d[3]), "+f"(d[4]), "+f"(d[5]), "+f"(d[6]), "+f"(d[7]),
                 "+f"(d[8]), "+f"(d[9]), "+f"(d[10]), "+f"(d[11]), "+f"(d[12]), "+f"(d[13]), "+f"(d[14]), "+f"(d[15]),
                 "+f"(d[16]), "+f"(d[17]), "+f"(d[18]), "+f"(d[19]), "+f"(d[20]), "+f"(d[21]), "+f"(d[22]), "+f"(d[23]),
                 "+f"(d[24]), "+f"(d[25]), "+f"(d[26]), "+f"(d[27]), "+f"(d[28]), "+f"(d[29]), "+f"(d[30]), "+f"(d[31]),
                 "+f"(d[32]), "+f"(d[33]), "+f"(d[34]), "+f"(d[35]), "+f"(d[36]), "+f"(d[37]), "+f"(d[38]), "+f"(d[39]),
                 "+f"(d[40]), "+f"(d[41]), "+f"(d[42]), "+f"(d[43]), "+f"(d[44]), "+f"(d[45]), "+f"(d[46]), "+f"(d[47]),
                 "+f"(d[48]), "+f"(d[49]), "+f"(d[50]), "+f"(d[51]), "+f"(d[52]), "+f"(d[53]), "+f"(d[54]), "+f"(d[55]),
                 "+f"(d[56]), "+f"(d[57]), "+f"(d[58]), "+f"(d[59]), "+f"(d[60]), "+f"(d[61]), "+f"(d[62]), "+f"(d[63]),
                 "+f"(d[64]), "+f"(d[65]), "+f"(d[66]), "+f"(d[67]), "+f"(d[68]), "+f"(d[69]), "+f"(d[70]), "+f"(d[71]),
                 "+f"(d[72]), "+f"(d[73]), "+f"(d[74]), "+f"(d[75]), "+f"(d[76]), "+f"(d[77]), "+f"(d[78]), "+f"(d[79]),
                 "+f"(d[80]), "+f"(d[81]), "+f"(d[82]), "+f"(d[83]), "+f"(d[84]), "+f"(d[85]), "+f"(d[86]), "+f"(d[87]),
                 "+f"(d[88]), "+f"(d[89]), "+f"(d[90]), "+f"(d[91]), "+f"(d[92]), "+f"(d[93]), "+f"(d[94]), "+f"(d[95]),
                 "+f"(d[96]), "+f"(d[97]), "+f"(d[98]), "+f"(d[99]), "+f"(d[100]), "+f"(d[101]), "+f"(d[102]), "+f"(d[103]),
                 "+f"(d[104]), "+f"(d[105]), "+f"(d[106]), "+f"(d[107]), "+f"(d[108]), "+f"(d[109]), "+f"(d[110]), "+f"(d[111]),
                 "+f"(d[112]), "+f"(d[113]), "+f"(d[114]), "+f"(d[115]), "+f"(d[116]), "+f"(d[117]), "+f"(d[118]), "+f"(d[119]),
                 "+f"(d[120]), "+f"(d[121]), "+f"(d[122]), "+f"(d[123]), "+f"(d[124]), "+f"(d[125]), "+f"(d[126]), "+f"(d[127])
               : "l"(a), "l"(b), "n"(TA));
}
template <int TA, bool FIRST> __device__ __forceinline__ void wg_ss128(float* d, uint64_t a, uint64_t b) {
  if (FIRST)
    asm volatile("wgmma.mma_async.sync.aligned.m64n128k16.f32.bf16.bf16 {%0,%1,%2,%3,%4,%5,%6,%7,%8,%9,%10,%11,%12,%13,%14,%15,%16,%17,%18,%19,%20,%21,%22,%23,%24,%25,%26,%27,%28,%29,%30,%31,%32,%33,%34,%35,%36,%37,%38,%39,%40,%41,%42,%43,%44,%45,%46,%47,%48,%49,%50,%51,%52,%53,%54,%55,%56,%57,%58,%59,%60,%61,%62,%63}, %64, %65, 0, 1, 1, %66, 1;"
               : "=f"(d[0]), "=f"(d[1]), "=f"(d[2]), "=f"(d[3]), "=f"(d[4]), "=f"(d[5]), "=f"(d[6]), "=f"(d[7]),
                 "=f"(d[8]), "=f"(d[9]), "=f"(d[10]), "=f"(d[11]), "=f"(d[12]), "=f"(d[13]), "=f"(d[14]), "=f"(d[15]),
                 "=f"(d[16]), "=f"(d[17]), "=f"(d[18]), "=f"(d[19]), "=f"(d[20]), "=f"(d[21]), "=f"(d[22]), "=f"(d[23]),
                 "=f"(d[24]), "=f"(d[25]), "=f"(d[26]), "=f"(d[27]), "=f"(d[28]), "=f"(d[29]), "=f"(d[30]), "=f"(d[31]),
                 "=f"(d[32]), "=f"(d[33]), "=f"(d[34]), "=f"(d[35]), "=f"(d[36]), "=f"(d[37]), "=f"(d[38]), "=f"(d[39]),
                 "=f"(d[40]), "=f"(d[41]), "=f"(d[42]), "=f"(d[43]), "=f"(d[44]), "=f"(d[45]), "=f"(d[46]), "=f"(d[47]),
                 "=f"(d[48]), "=f"(d[49]), "=f"(d[50]), "=f"(d[51]), "=f"(d[52]), "=f"(d[53]), "=f"(d[54]), "=f"(d[55]),
                 "=f"(d[56]), "=f"(d[57]), "=f"(d[58]), "=f"(d[59]), "=f"(d[60]), "=f"(d[61]), "=f"(d[62]), "=f"(d[63])
               : "l"(a), "l"(b), "n"(TA));
  else
    asm volatile("wgmma.mma_async.sync.aligned.m64n128k16.f32.bf16.bf16 {%0,%1,%2,%3,%4,%5,%6,%7,%8,%9,%10,%11,%12,%13,%14,%15,%16,%17,%18,%19,%20,%21,%22,%23,%24,%25,%26,%27,%28,%29,%30,%31,%32,%33,%34,%35,%36,%37,%38,%39,%40,%41,%42,%43,%44,%45,%46,%47,%48,%49,%50,%51,%52,%53,%54,%55,%56,%57,%58,%59,%60,%61,%62,%63}, %64, %65, 1, 1, 1, %66, 1;"
               : "+f"(d[0]), "+f"(d[1]), "+f"(d[2]), "+f"(d[3]), "+f"(d[4]), "+f"(d[5]), "+f"(d[6]), "+f"(d[7]),
                 "+f"(d[8]), "+f"(d[9]), "+f"(d[10]), "+f"(d[11]), "+f"(d[12]), "+f"(d[13]), "+f"(d[14]), "+f"(d[15]),
                 "+f"(d[16]), "+f"(d[17]), "+f"(d[18]), "+f"(d[19]), "+f"(d[20]), "+f"(d[21]), "+f"(d[22]), "+f"(d[23]),
                 "+f"(d[24]), "+f"(d[25]), "+f"(d[26]), "+f"(d[27]), "+f"(d[28]), "+f"(d[29]), "+f"(d[30]), "+f"(d[31]),
                 "+f"(d[32]), "+f"(d[33]), "+f"(d[34]), "+f"(d[35]), "+f"(d[36]), "+f"(d[37]), "+f"(d[38]), "+f"(d[39]),
                 "+f"(d[40]), "+f"(d[41]), "+f"(d[42]), "+f"(d[43]), "+f"(d[44]), "+f"(d[45]), "+f"(d[46]), "+f"(d[47]),
                 "+f"(d[48]), "+f"(d[49]), "+f"(d[50]), "+f"(d[51]), "+f"(d[52]), "+f"(d[53]), "+f"(d[54]), "+f"(d[55]),
                 "+f"(d[56]), "+f"(d[57]), "+f"(d[58]), "+f"(d[59]), "+f"(d[60]), "+f"(d[61]), "+f"(d[62]), "+f"(d[63])
               : "l"(a), "l"(b), "n"(TA));
}
template <int TA, bool FIRST> __device__ __forceinline__ void wg_ss64(float* d, uint64_t a, uint64_t b) {
  if (FIRST)
    asm volatile("wgmma.mma_async.sync.aligned.m64n64k16.f32.bf16.bf16 {%0,%1,%2,%3,%4,%5,%6,%7,%8,%9,%10,%11,%12,%13,%14,%15,%16,%17,%18,%19,%20,%21,%22,%23,%24,%25,%26,%27,%28,%29,%30,%31}, %32, %33, 0, 1, 1, %34, 1;"
               : "=f"(d[0]), "=f"(d[1]), "=f"(d[2]), "=f"(d[3]), "=f"(d[4]), "=f"(d[5]), "=f"(d[6]), "=f"(d[7]),
                 "=f"(d[8]), "=f"(d[9]), "=f"(d[10]), "=f"(d[11]), "=f"(d[12]), "=f"(d[13]), "=f"(d[14]), "=f"(d[15]),
                 "=f"(d[16]), "=f"(d[17]), "=f"(d[18]), "=f"(d[19]), "=f"(d[20]), "=f"(d[21]), "=f"(d[22]), "=f"(d[23]),
                 "=f"(d[24]), "=f"(d[25]), "=f"(d[26]), "=f"(d[27]), "=f"(d[28]), "=f"(d[29]), "=f"(d[30]), "=f"(d[31])
               : "l"(a), "l"(b), "n"(TA));
  else
    asm volatile("wgmma.mma_async.sync.aligned.m64n64k16.f32.bf16.bf16 {%0,%1,%2,%3,%4,%5,%6,%7,%8,%9,%10,%11,%12,%13,%14,%15,%16,%17,%18,%19,%20,%21,%22,%23,%24,%25,%26,%27,%28,%29,%30,%31}, %32, %33, 1, 1, 1, %34, 1;"
               : "+f"(d[0]), "+f"(d[1]), "+f"(d[2]), "+f"(d[3]), "+f"(d[4]), "+f"(d[5]), "+f"(d[6]), "+f"(d[7]),
                 "+f"(d[8]), "+f"(d[9]), "+f"(d[10]), "+f"(d[11]), "+f"(d[12]), "+f"(d[13]), "+f"(d[14]), "+f"(d[15]),
                 "+f"(d[16]), "+f"(d[17]), "+f"(d[18]), "+f"(d[19]), "+f"(d[20]), "+f"(d[21]), "+f"(d[22]), "+f"(d[23]),
                 "+f"(d[24]), "+f"(d[25]), "+f"(d[26]), "+f"(d[27]), "+f"(d[28]), "+f"(d[29]), "+f"(d[30]), "+f"(d[31])
               : "l"(a), "l"(b), "n"(TA));
}

constexpr int H_STAGE = 49152, H_NST = 4;
constexpr int H_STG = H_NST * H_STAGE;
constexpr int H_VEC = H_STG + 16384;
constexpr int H_BAR = H_VEC + 6144;
constexpr int H_SMEM = H_BAR + 256;
constexpr int HB_FULL = 0, HB_EMPTY = 32, HB_IFULL = 64, HB_IEMPTY = 80, HB_ITEM = 96, HB_INC = 104;
enum { IT_END = 0, IT_MOD = 1, IT_XT = 2, IT_OUT = 3, IT_UV = 4, IT_F1 = 5, IT_F2 = 6 };
constexpr int MAX_ITEMS = 1400;
#define D_MOD 4
#define D_UV 2
#define UV_WAIT 0
#define PF_MAPS 1
#define R_LATE 1
#define CH_FENCE 1
#define CH_FENCE1 1
#define N_UV1 20
#define FINE 1
#define B_EARLY 1
#define XT_GO 0
__device__ __forceinline__ int item_sz(uint32_t it) { const int s = (it >> 13) & 3; return s == 3 ? 1 : s; }
struct HList { uint32_t n; uint32_t it[MAX_ITEMS]; };
#define HT(i)

__device__ __forceinline__ uint32_t tile_lane(int warp, int lane) { return warp * 1024 + (lane >> 2) * 64 + (((lane & 3) ^ (lane >> 3)) << 4); }
__device__ __forceinline__ constexpr uint32_t tile_off(int c, int h) { return (c >> 1) * 16384 + (c & 1) * 8192 + h * 512; }

template <int BN, int TA, bool PP = false, class PRE>
__device__ __forceinline__ void h_mainloop(float* acc, uint32_t sb, int nst, uint32_t& st, uint32_t& ph, int wg, bool leader, PRE pre, uint32_t odd = 0) {
  constexpr int KS = BN == 64 ? 8 : 4;
  constexpr uint32_t BOFF = BN == 64 ? 32768 : 16384;
  const int mh = PP ? 0 : wg;
  const uint64_t da0 = TA ? mkdesc(sb + mh * 1024, 2048, 128, 0) : mkdesc(sb + mh * 4096, 16, 512, 2);
  auto release = [&](uint32_t s) {
    if (leader) {
      if (PP) asm volatile("mbarrier.arrive.shared::cta.b64 _, [%0], 2;" :: "r"(sb + H_BAR + HB_EMPTY + s * 8) : "memory");
      else mbar_arrive(sb + H_BAR + HB_EMPTY + s * 8);
    }
  };
  const uint64_t db0 = mkdesc(sb + BOFF, 8192, 1024, 1);
  constexpr uint32_t kh = 512;
  uint32_t prev = 0;
  auto stage = [&](auto first, int i) {
    constexpr bool FIRST = decltype(first)::value;
    mbar_wait(sb + H_BAR + HB_FULL + st * 8, ph);
    if (FIRST) HT(1);
    if (PP && !FIRST && i == nst - 1) { if (odd) bar_arrive<5, 256>(); else bar_arrive<4, 256>(); }
    const uint64_t da = da0 + st * (H_STAGE >> 4), db = db0 + st * (H_STAGE >> 4);
    WG_FENCE();
#pragma unroll
    for (int k = 0; k < KS; k++) {
      const uint64_t a = da + (k >> 2) * 1024 + (TA ? (k & 3) * 256 : ((k >> 1) & 1) * kh + (k & 1) * 2), b = db + k * 128;
      if (FIRST && k == 0) { if (BN == 256) wg_ss256<TA, true>(acc, a, b); else if (BN == 128) wg_ss128<TA, true>(acc, a, b); else wg_ss64<TA, true>(acc, a, b); }
      else { if (BN == 256) wg_ss256<TA, false>(acc, a, b); else if (BN == 128) wg_ss128<TA, false>(acc, a, b); else wg_ss64<TA, false>(acc, a, b); }
      if (PP) { if (FIRST && k == 0) wg_ss128<TA, true>(acc + 64, a + (TA ? 64 : 256), b); else wg_ss128<TA, false>(acc + 64, a + (TA ? 64 : 256), b); }
    }
    WG_COMMIT();
  };
  stage(std::true_type(), 0);
  pre();
  prev = st;
  if (++st == H_NST) { st = 0; ph ^= 1; }
#pragma unroll 1
  for (int i = 1; i < nst; i++) {
    stage(std::false_type(), i);
    WG_WAIT(1);
    release(prev);
    prev = st;
    if (++st == H_NST) { st = 0; ph ^= 1; }
  }
  WG_WAIT(0);
  HT(2);
  reg_fence<PP ? BN : BN / 2>(acc);
  release(prev);
}

template <int BN, bool FINAL>
__device__ __forceinline__ bool h_residual(uint32_t sb, uint32_t va, int mt, int n0, uint32_t& st, uint32_t& ph, int warp, int lane, __nv_bfloat16* out,
                                           int part = 0, int lgp = 0) {
  const size_t toff = (size_t)(mt * 16 + (n0 >> 6)) * 16384 + tile_lane(warp, lane);
  uint4 r[BN / 16];
  auto load_r = [&]() {
#pragma unroll
    for (int i = 0; i < BN / 16; i++) r[i] = __ldcg(reinterpret_cast<const uint4*>(g_x1 + toff + tile_off(i >> 1, i & 1)));
  };
  if (!R_LATE) load_r();
  float acc[BN / 2];
  h_mainloop<BN, FINAL ? 0 : 1>(acc, sb, ((FINAL ? 56 : 64) / (BN == 64 ? 2 : 1)) >> lgp, st, ph, warp >> 2, (warp & 3) == 0 && lane == 0,
                                [&]() { if (R_LATE) load_r(); });
  if (BN == 64 && lgp > 0) {
    const int tile = ((FINAL ? 0 : mt >= 12 ? 4 : 8) + (mt & 3)) * 16 + (n0 >> 6);
    float4* ws = reinterpret_cast<float4*>(g_ws) + (size_t)tile * 8192 + warp * 32 + lane;
#pragma unroll
    for (int i = 0; i < 8; i++) ws[part * 2048 + i * 256] = make_float4(acc[4 * i], acc[4 * i + 1], acc[4 * i + 2], acc[4 * i + 3]);
    bar_sync<1, 256>();
    if (warp == 0 && lane == 0) { fence_gpu(); const uint32_t t = atomicAdd(&g_flags[FL_SPL + tile], 1); fence_gpu(); sts32(sb + H_BAR + HB_INC + 8, t); }
    bar_sync<1, 256>();
    if (lds32(sb + H_BAR + HB_INC + 8) != (1u << lgp) - 1) return false;
#pragma unroll 1
    for (int p = 1; p < (1 << lgp); p++) {
      float4 o[8];
#pragma unroll
      for (int i = 0; i < 8; i++) o[i] = __ldcg(ws + (part ^ p) * 2048 + i * 256);
#pragma unroll
      for (int i = 0; i < 8; i++) { acc[4 * i] += o[i].x; acc[4 * i + 1] += o[i].y; acc[4 * i + 2] += o[i].z; acc[4 * i + 3] += o[i].w; }
    }
  }
  float sm[4] = {0.f, 0.f, 0.f, 0.f};
  const uint32_t stg = sb + H_STG + warp * 2048;
#pragma unroll
  for (int c = 0; c < BN / 32; c++) {
    uint32_t y[2][4] = {{r[2 * c].x, r[2 * c].y, r[2 * c].z, r[2 * c].w}, {r[2 * c + 1].x, r[2 * c + 1].y, r[2 * c + 1].z, r[2 * c + 1].w}}, z[2][4];
#pragma unroll
    for (int j = 0; j < 4; j++) {
      const uint32_t gt = lds32(va + c * 64 + j * 16 + (lane & 3) * 4);
      const uint32_t cb = FINAL ? 0 : lds32(va + 512 + c * 64 + j * 16 + (lane & 3) * 4);
#pragma unroll
      for (int h = 0; h < 2; h++) {
        const float* a = acc + c * 16 + j * 4 + h * 2;
        y[h][j] = pack2(fmaf(bf_lo(gt), a[0], bf_lo(y[h][j])), fmaf(bf_hi(gt), a[1], bf_hi(y[h][j])));
        if (!FINAL) {
          const float p = bf_lo(y[h][j]), q = bf_hi(y[h][j]);
          sm[2 * h] += p + q;
          sm[2 * h + 1] = fmaf(p, p, fmaf(q, q, sm[2 * h + 1]));
          z[h][j] = pack2(fmaf(p, bf_lo(cb), p), fmaf(q, bf_hi(cb), q));
        }
      }
    }
    if (!FINAL) {
#pragma unroll
      for (int h = 0; h < 2; h++) {
        const size_t o = toff + tile_off(c, h);
        *reinterpret_cast<uint4*>(g_x1 + o) = make_uint4(y[h][0], y[h][1], y[h][2], y[h][3]);
        *reinterpret_cast<uint4*>(g_h2 + o) = make_uint4(z[h][0], z[h][1], z[h][2], z[h][3]);
      }
    } else {
#pragma unroll
      for (int h = 0; h < 2; h++) stsm4(stg + (h * 8 + (lane & 7)) * 128 + ((((c & 1) * 4 + (lane >> 3)) ^ (lane & 7)) << 4), y[h]);
      if (c & 1) {
        __syncwarp();
#pragma unroll
        for (int j = 0; j < 4; j++) {
          const int rr = 4 * j + (lane >> 3);
          uint32_t v[4];
          lds128(v, stg + rr * 128 + (((lane & 7) ^ (rr & 7)) << 4));
          *reinterpret_cast<uint4*>(out + (size_t)(mt * 128 + warp * 16 + rr) * D_ + n0 + (c >> 1) * 64 + (lane & 7) * 8) = make_uint4(v[0], v[1], v[2], v[3]);
        }
        __syncwarp();
      }
    }
    if (CH_FENCE && c + 1 < BN / 32) sched_fence(lane, 100);
  }
  if (!FINAL) {
#pragma unroll
    for (int j = 0; j < 4; j++) { sm[j] += __shfl_xor_sync(0xffffffffu, sm[j], 1); sm[j] += __shfl_xor_sync(0xffffffffu, sm[j], 2); }
    const int t = lane & 3;
    const float sv = t == 0 ? sm[0] : t == 1 ? sm[1] : t == 2 ? sm[2] : sm[3];
    asm volatile("red.relaxed.gpu.global.add.f32 [%0], %1;" :: "l"(g_stat + (mt * 128 + warp * 16 + (t >> 1) * 8 + (lane >> 2)) * 2 + (t & 1)), "f"(sv) : "memory");
  }
  return true;
}

__device__ __forceinline__ float silu_mul(float hg, float u) {
  float t; asm("tanh.approx.f32 %0, %1;" : "=f"(t) : "f"(hg));
  const float h = hg * u;
  return fmaf(h, t, h);
}

template <int BN>
__device__ __forceinline__ void h_swiglu(const float* acc, uint32_t va, int mt, int kb0, int warp, int lane) {
  uint8_t* ap = g_act + (size_t)(mt * 56 + kb0) * 16384 + tile_lane(warp, lane);
  float rs[2], nm[2], rh[2];
#pragma unroll
  for (int h = 0; h < 2; h++) {
    float t[2];
    lds64f(t, va + 2048 + (warp * 16 + h * 8 + (lane >> 2)) * 8);
    const float mean = t[0] * (1.f / D_);
    rs[h] = rsqrtf(fmaxf(t[1] * (1.f / D_) - mean * mean, 0.f) + 1e-5f);
    nm[h] = -mean * rs[h];
    rh[h] = 0.5f * rs[h];
  }
#pragma unroll
  for (int c = 0; c < BN / 64; c++) {
    uint32_t y[2][4];
#pragma unroll
    for (int j = 0; j < 4; j++) {
      const float* g = acc + 16 * c + 4 * j; const float* u = g + BN / 4;
      float p[4], q[4], o[4];
      lds128f(p, va + (4 * c + j) * 128 + (lane & 3) * 32); lds128f(q, va + (4 * c + j) * 128 + (lane & 3) * 32 + 16);
#pragma unroll
      for (int e = 0; e < 4; e++)
        o[e] = silu_mul(fmaf(rh[e >> 1], g[e], fmaf(nm[e >> 1], p[e & 1], p[2 + (e & 1)])), fmaf(rs[e >> 1], u[e], fmaf(nm[e >> 1], q[e & 1], q[2 + (e & 1)])));
      y[0][j] = pack2(o[0], o[1]); y[1][j] = pack2(o[2], o[3]);
    }
#pragma unroll
    for (int h = 0; h < 2; h++)
      *reinterpret_cast<uint4*>(ap + tile_off(c, h)) = make_uint4(y[h][0], y[h][1], y[h][2], y[h][3]);
    if (CH_FENCE1 && c + 1 < BN / 64) sched_fence(lane, 100);
  }
}

__global__ void __launch_bounds__(384, 1)
kernel_H(const __grid_constant__ CUtensorMap tmo, const __grid_constant__ CUtensorMap tm1, const __grid_constant__ CUtensorMap tm3,
         const __grid_constant__ CUtensorMap tm2, const __grid_constant__ CUtensorMap tmm, const __nv_bfloat16* __restrict__ x,
         const __nv_bfloat16* __restrict__ cvec, __nv_bfloat16* __restrict__ out, const __grid_constant__ HList list) {
  extern __shared__ __align__(1024) uint8_t smem[];
  constexpr uint32_t sb = 0x400, bars = sb + H_BAR;
  const int tid = threadIdx.x, lane = tid & 31;
  const int warp = __shfl_sync(0xffffffffu, tid >> 5, 0);
  if (tid == 0) {
    if (smem_u32(smem) != sb) __trap();
    for (int i = 0; i < H_NST; i++) { mbar_init(bars + HB_FULL + i * 8, 1); mbar_init(bars + HB_EMPTY + i * 8, 2); }
    for (int i = 0; i < 2; i++) { mbar_init(bars + HB_IFULL + i * 8, 1); mbar_init(bars + HB_IEMPTY + i * 8, 3); }
    fence_async_smem();
    if (PF_MAPS) {
      const CUtensorMap* maps[5] = {&tmm, &tm1, &tm3, &tmo, &tm2};
#pragma unroll
      for (int i = 0; i < 5; i++) asm volatile("prefetch.tensormap [%0];" :: "l"(maps[i]) : "memory");
    }
  }
  __syncthreads();
  if (warp >= 8) {
    asm volatile("setmaxnreg.dec.sync.aligned.u32 40;");
    if (warp == 8) {
      uint32_t st = 0, ph = 1;
#pragma unroll 1
      for (uint32_t n = 0;; n++) {
        uint32_t q = 0;
        if (lane == 0) q = atomicAdd(&g_flags[FL_HEAD], 1);
        q = __shfl_sync(0xffffffffu, q, 0);
        const uint32_t it = q < list.n ? list.it[q] : 0;
        const int type = it & 7, mt = (it >> 3) & 15, idx = (it >> 7) & 63, sz = item_sz(it), part = (it >> 15) & 3, lgp = (it >> 17) & 3;
        int f = FL_GO; uint32_t target = 1, first = 0;
        if (type == IT_OUT) { f = lane == 0 ? FL_ATT + 8 * mt : lane == 1 ? FL_XT + 8 * mt : lane == 9 ? FL_MODA : FL_MOD; target = lane == 0 ? 64 : lane == 1 ? 2 : lane == 9 ? 8 : 16; first = 3; }
        else if (type == IT_F1) { f = lane < 8 ? FL_OUT + 8 * mt + lane : FL_UV; target = lane < 8 ? 2 : 28; }
        else if (type == IT_F2) { f = lane < 8 ? FL_F1 + 8 * mt + lane : FL_MODB; target = 8; }
        else if (XT_GO && type == IT_XT) first = 1;
        const int gsh = type == IT_F1 ? 1 : type == IT_F2 ? 3 : 6;
        if (type >= IT_F1) first = FINE ? 1u << ((part * (56 >> lgp)) >> gsh) : type == IT_F1 ? 255u : 127u;
        uint32_t have = 0;
        auto need = [&](int g) {
          if (!((have >> g) & 1)) {
            if (lane == g) wait_flag2(&g_flags[f], target);
            __syncwarp();
            asm volatile("fence.proxy.async.global;" ::: "memory");
            have |= 1u << g;
          }
        };
        const bool has_a = type == IT_OUT || type >= IT_F1;
        auto publish = [&]() {
          mbar_wait(bars + HB_IEMPTY + (n & 1) * 8, ((n >> 1) & 1) ^ 1);
          if (elect_one()) {
            sts32(bars + HB_ITEM + (n & 1) * 4, it | (q << 19));
            mbar_arrive(bars + HB_IFULL + (n & 1) * 8);
          }
        };
        const bool early = B_EARLY && (has_a || type != IT_XT);
        if (early) publish();
        {
          uint32_t c = 0;
          while (first && ((have = __ballot_sync(0xffffffffu, ld_acquire(&g_flags[f]) >= target)) & first) != first) { if (++c > 20000000u) __trap(); __nanosleep(20); }
          asm volatile("fence.proxy.async.global;" ::: "memory");
        }
        if (!early) publish();
        if (type == IT_END) break;
        if (type != IT_XT) {
          const uint8_t* ap = type == IT_OUT ? g_att + (size_t)mt * 64 * 16384 : type == IT_F1 ? g_h2 + (size_t)mt * 16 * 16384 : g_act + (size_t)mt * 56 * 16384;
          const int nkb = (type == IT_OUT ? 64 : type == IT_F2 ? 56 : 16) >> lgp;
          const uint32_t abytes = has_a ? (sz == 2 ? 32768 : 16384) : 0, bytes = (sz == 0 ? 32768 : 16384) + abytes;
          const int dk = sz == 2 ? 1 : 0;
#pragma unroll 1
          for (int kb = part * nkb; kb < (part + 1) * nkb; kb += 1 + dk) {
            const uint32_t d = sb + st * H_STAGE, fb = bars + HB_FULL + st * 8;
            mbar_wait(bars + HB_EMPTY + st * 8, ph);
            if (has_a) need(kb >> gsh);
            if (has_a && kb + 1 + dk >= (part + 1) * nkb) {
              need(8);
              if (type == IT_OUT) need(9);
              if (elect_one()) {
                const bool f1 = type == IT_F1;
                const int c0 = f1 ? idx * (128 >> sz) : idx * (256 >> sz);
                const uint32_t v = sb + H_VEC + (n & 1) * 3072;
                const uint32_t n0 = (f1 ? 2048 : 512) >> sz, n1 = f1 ? 1024 : n0;
                asm volatile("mbarrier.expect_tx.relaxed.cta.shared::cta.b64 [%0], %1;" :: "r"(fb), "r"(n0 + n1) : "memory");
                bulk_g2s(v, f1 ? (const void*)(g_uv + c0 * 4) : (const void*)(g_mod + (type == IT_OUT ? 2 : 5) * D_ + c0), n0, fb);
                bulk_g2s(v + (f1 ? 2048 : 512), f1 ? (const void*)(g_stat + mt * 256) : (const void*)(g_mod + 4 * D_ + c0), n1, fb);
              }
            }
            if (elect_one()) {
              mbar_expect(fb, bytes);
              if (has_a) bulk_g2s(d, ap + (size_t)kb * 16384, abytes, fb);
            }
            if (++st == H_NST) { st = 0; ph ^= 1; }
          }
        }
      }
    } else if (warp >= 10) {
      const int hb = warp - 10;
      uint32_t st = 0, ph = 1;
#pragma unroll 1
      for (uint32_t n = 0;; n++) {
        mbar_wait(bars + HB_IFULL + (n & 1) * 8, (n >> 1) & 1);
        const uint32_t it = __shfl_sync(0xffffffffu, lds32(bars + HB_ITEM + (n & 1) * 4), 0);
        const int type = it & 7, idx = (it >> 7) & 63, sz = item_sz(it), part = (it >> 15) & 3, lgp = (it >> 17) & 3;
        if (type == IT_END) break;
        if (elect_one()) mbar_arrive(bars + HB_IEMPTY + (n & 1) * 8);
        if (type == IT_XT) continue;
        const bool ffn1 = type == IT_F1 || type == IT_UV;
        const int nkb = (type == IT_OUT ? 64 : type == IT_F2 ? 56 : 16) >> lgp;
        const CUtensorMap* tb = type == IT_OUT ? &tmo : ffn1 ? &tm1 : type == IT_F2 ? &tm2 : &tmm;
        const CUtensorMap* tc = ffn1 ? &tm3 : tb;
        const int c0 = ffn1 ? idx * (128 >> sz) : idx * (256 >> sz) + (type == IT_MOD ? 2048 : 0), c2 = ffn1 ? c0 : c0 + 128;
        const int dk = sz == 2 ? 1 : 0;
        const CUtensorMap* t0 = hb == 1 && sz == 1 ? tc : tb;
        const int ca = hb == 0 || sz == 2 || (sz == 1 && ffn1) ? c0 : c0 + 64;
        const uint32_t off = (sz == 2 ? 32768 : 16384) + hb * 8192;
        const uint32_t cold = type == IT_MOD ? D_MOD : type == IT_UV ? D_UV : H_NST;
        if (type == IT_MOD || type == IT_UV) {
          if (lane == 0) wait_flag2(&g_flags[UV_WAIT && type == IT_UV ? FL_MOD : FL_GO], UV_WAIT && type == IT_UV ? UV_WAIT : 1);
          __syncwarp();
        }
#pragma unroll 1
        for (int kb = part * nkb; kb < (part + 1) * nkb; kb += 1 + dk) {
          const uint32_t d = sb + st * H_STAGE + off, fb = bars + HB_FULL + st * 8;
          mbar_wait(bars + HB_EMPTY + st * 8, ph);
          if (cold < H_NST) mbar_wait(bars + HB_FULL + ((st - cold) & 3) * 8, st >= cold ? ph ^ 1 : ph);
          if (elect_one()) {
            tma5d(d, t0, ca, kb + hb * dk, fb);
            if (sz == 0) tma5d(d + 16384, tc, c2 + hb * 64, kb, fb);
          }
          if (++st == H_NST) { st = 0; ph ^= 1; }
        }
      }
    } else if (warp == 9) {
#pragma unroll 1
      for (uint32_t n = 0;; n++) {
        mbar_wait(bars + HB_IFULL + (n & 1) * 8, (n >> 1) & 1);
        const uint32_t itq = lds32(bars + HB_ITEM + (n & 1) * 4);
        const int type = itq & 7, mt = (itq >> 3) & 15;
        if (type == IT_END) break;
        if (n & 1) bar_sync<3, 288>(); else bar_sync<2, 288>();
        if (lane == 0) {
          const uint32_t inc = lds32(bars + HB_INC + (n & 1) * 4);
          mbar_arrive(bars + HB_IEMPTY + (n & 1) * 8);
          if (inc) {
            fence_gpu();
            const int idx = (itq >> 7) & 63, sz = item_sz(itq);
            const int mv = (idx >> sz) >> 2;
            uint32_t* fl = &g_flags[type == IT_MOD ? (mv == 0 ? FL_MODA : mv == 3 ? FL_MODB : FL_MOD) : type == IT_UV ? FL_UV : type == IT_XT ? FL_XT + 8 * mt
                                    : type == IT_OUT ? FL_OUT + 8 * mt + ((2 * idx) >> sz) : FL_F1 + 8 * mt + (idx >> (2 + sz))];
            red_add_u32(fl, inc);
            if (type == IT_OUT && sz == 0) red_add_u32(fl + 1, inc);
          }
        }
        __syncwarp();
      }
      asm volatile("griddepcontrol.wait;" ::: "memory");
      uint32_t k = 0;
      if (lane == 0) { fence_gpu(); k = atomicAdd(&g_flags[FL_EXIT], 1); }
      k = __shfl_sync(0xffffffffu, k, 0);
      if (k == gridDim.x - 1) {
        fence_gpu();
        for (int i = lane; i < 1024; i += 32) g_flags[i] = 0;
      }
    }
  } else {
    asm volatile("setmaxnreg.inc.sync.aligned.u32 232;");
    const int wg = warp >> 2;
    const bool leader = (tid & 127) == 0;
    uint32_t st = 0, ph = 0;
    int turn = 1;
#pragma unroll 1
    for (uint32_t n = 0;; n++) {
      mbar_wait(bars + HB_IFULL + (n & 1) * 8, (n >> 1) & 1);
      const uint32_t itq = __shfl_sync(0xffffffffu, lds32(bars + HB_ITEM + (n & 1) * 4), 0);
      const int type = itq & 7, mt = (itq >> 3) & 15, idx = (itq >> 7) & 63, sz = item_sz(itq), part = (itq >> 15) & 3, lgp = (itq >> 17) & 3;
      uint32_t inc = type == IT_OUT ? 2 : type == IT_F1 || type == IT_MOD ? 2 >> sz : type != IT_F2;
      if (type == IT_END) break;
      const bool pp = ((itq >> 13) & 3) == 3;
      if (pp) {
        turn ^= 1;
        if (turn != wg) {
          if (n & 1) { bar_arrive<3, 288>(); bar_sync<5, 256>(); } else { bar_arrive<2, 288>(); bar_sync<4, 256>(); }
          continue;
        }
      }
      HT(0);
      const uint32_t va = sb + H_VEC + (n & 1) * 3072;
      if (type == IT_OUT) {
        if (sz == 0) h_residual<256, false>(sb, va, mt, idx * 256, st, ph, warp, lane, out);
        else if (sz == 1) h_residual<128, false>(sb, va, mt, idx * 128, st, ph, warp, lane, out);
        else inc = h_residual<64, false>(sb, va, mt, idx * 64, st, ph, warp, lane, out, part, lgp);
      } else if (type == IT_F2) {
        if (sz == 0) h_residual<256, true>(sb, va, mt, idx * 256, st, ph, warp, lane, out);
        else if (sz == 1) h_residual<128, true>(sb, va, mt, idx * 128, st, ph, warp, lane, out);
        else h_residual<64, true>(sb, va, mt, idx * 64, st, ph, warp, lane, out, part, lgp);
      } else if (type == IT_XT) {
        const int rg = idx * 8 + warp;
        const uint32_t* xp = reinterpret_cast<const uint32_t*>(x + (size_t)(mt * 128 + rg * 8 + (lane >> 2)) * D_) + (lane & 3);
        uint8_t* tp = g_x1 + (size_t)mt * 262144 + rg * 512 + tile_lane(0, lane);
        if (lane < 16) g_stat[(mt * 128 + rg * 8) * 2 + lane] = 0.f;
#pragma unroll 1
        for (int b = 0; b < 2; b++) {
          uint32_t v[64];
#pragma unroll
          for (int i = 0; i < 64; i++) v[i] = __ldg(xp + 256 * b + 4 * i);
#pragma unroll
          for (int i = 0; i < 16; i++)
            *reinterpret_cast<uint4*>(tp + tile_off(16 * b + i, 0)) = make_uint4(v[4 * i], v[4 * i + 1], v[4 * i + 2], v[4 * i + 3]);
        }
      } else if (type == IT_F1) {
        if (pp) {
          float acc[128];
          h_mainloop<128, 0, true>(acc, sb, 16, st, ph, wg, leader, []() {}, n & 1);
          h_swiglu<128>(acc, va, mt, idx, warp & 3, lane);
          sched_fence(lane, 100);
          h_swiglu<128>(acc + 64, va, mt, idx, (warp & 3) + 4, lane);
        } else if (sz == 1) {
          float acc[64];
          h_mainloop<128, 0>(acc, sb, 16, st, ph, wg, leader, []() {});
          h_swiglu<128>(acc, va, mt, idx, warp, lane);
        } else {
          float acc[128];
          h_mainloop<256, 0>(acc, sb, 16, st, ph, wg, leader, []() {});
          h_swiglu<256>(acc, va, mt, idx * 2, warp, lane);
        }
      } else {
        if (type == IT_UV && tid == 0) wait_flag2(&g_flags[FL_MOD], 16);
        bar_sync<1, 256>();
        {
          const uint32_t* src = reinterpret_cast<const uint32_t*>(type == IT_UV ? g_mod + (wg == 0 ? 4 : 3) * D_ : cvec) + ((tid & 127) >> 2) * 16 + (tid & 3);
          uint32_t v[4];
#pragma unroll
          for (int j = 0; j < 4; j++) v[j] = __ldcg(src + 4 * j);
          const uint32_t p = sb + H_STG + ((tid & 127) >> 2) * 512 + (tid & 3) * 16;
          if (type == IT_MOD) {
#pragma unroll 1
            for (int j = 0; j < 4; j++) {
              const float c0 = bf_lo(v[0]), c1 = bf_hi(v[0]);
              v[0] = v[1]; v[1] = v[2]; v[2] = v[3];
              v[3] = pack2(c0 / (1.f + __expf(-c0)), c1 / (1.f + __expf(-c1)));
            }
          }
          if (type == IT_UV && wg == 0) sts128(p, 0x3f803f80u, 0x3f803f80u, 0x3f803f80u, 0x3f803f80u);
          if (type == IT_UV || wg == 0) sts128(type == IT_MOD ? p : wg == 0 ? p + 64 : (p ^ 16) + 128, v[0], v[1], v[2], v[3]);
        }
        fence_async_smem();
        bar_sync<1, 256>();
        float acc[8] = {0.f, 0.f, 0.f, 0.f, 0.f, 0.f, 0.f, 0.f};
        const uint64_t dw = mkdesc(sb + 16384 + wg * (16384 >> sz), 8192, 1024, 1), dv = mkdesc(sb + H_STG, 16, 0, 2);
#pragma unroll 1
        for (int i = 0; i < 16; i++) {
          mbar_wait(bars + HB_FULL + st * 8, ph);
          if (i == 0) HT(1);
          WG_FENCE();
#pragma unroll
          for (int k = 0; k < 4; k++) {
            const uint64_t a = dw + st * (H_STAGE >> 4) + k * 128, b = dv + i * 64 + (k >> 1) * 32 + (k & 1) * 2;
            wg_ss8(acc, a, b); wg_ss8(acc + 4, a + (sz ? 0 : 512), b);
          }
          WG_COMMIT();
          WG_WAIT(0);
          if (leader) mbar_arrive(bars + HB_EMPTY + st * 8);
          if (++st == H_NST) { st = 0; ph ^= 1; }
        }
        HT(2);
        reg_fence<8>(acc);
        const int t = lane & 3, c = (warp & 3) * 16 + (lane >> 2);
#pragma unroll
        for (int j = 0; j < 4; j++) {
          const int cj = c + (j >> 1) * 64 + (j & 1) * 8;
          if (type == IT_MOD) { if (t == 0 && (j < 2 || !sz)) g_mod[2048 + ((idx * 256 + wg * 128) >> sz) + cj] = __float2bfloat16(acc[2 * j]); }
          else if (t < 2) g_uv[idx * 512 + (cj >> 1) * 8 + wg * 4 + t * 2 + (cj & 1)] = (wg == 0 ? 0.5f : 1.f) * (t == 0 ? acc[2 * j] + acc[2 * j + 1] : acc[2 * j]);
        }
      }
      if (pp ? leader : tid == 0) sts32(bars + HB_INC + (n & 1) * 4, inc);
      if (n & 1) bar_arrive<3, 288>(); else bar_arrive<2, 288>();
    }
  }
}

const uint32_t h_items[] = {
  2, 130, 10, 138, 18, 146, 26, 154, 34, 162, 42, 170, 50, 178, 58, 186, 66, 194, 74, 202, 82, 210, 90, 218,
  98, 226, 106, 234, 114, 242, 122, 250, 1, 129, 257, 385, 513, 641, 769, 897, 1025, 1153, 1281, 1409, 4, 132, 260, 388,
  516, 644, 772, 900, 1028, 1156, 1284, 1412, 1540, 1668, 1796, 1924, 2052, 2180, 2308, 16387, 2436, 16515, 16643, 16771, 16899, 17027, 17155, 17283,
  17411, 17539, 17667, 17795, 17923, 18051, 18179, 18307, 2564, 2692, 2820, 2948, 3076, 3204, 3332, 1537, 3460, 1665, 1793, 1921, 16395, 16523, 16651, 16779,
  16907, 17035, 17163, 17291, 17419, 17547, 17675, 17803, 17931, 18059, 18187, 18315, 8211, 8339, 8467, 8595, 8723, 5, 133, 261, 389, 517, 645, 773,
  901, 1029, 1157, 1285, 1413, 1541, 1669, 1797, 1925, 2053, 2181, 2309, 2437, 8851, 8979, 9107, 2565, 2693, 2821, 2949, 3077, 3205, 3333, 3461,
  13, 141, 269, 781, 909, 1037, 1165, 1293, 1421, 1549, 1677, 1805, 1933, 2061, 2189, 2317, 2445, 397, 8219, 525, 8347, 653, 8475, 2573,
  2701, 2829, 8603, 2957, 3085, 8731, 3213, 3341, 17691, 3469, 8198, 8326, 8454, 8582, 17819, 2837, 8710, 8838, 17947, 8966, 18075, 9094, 3093, 18203,
  21, 3221, 18331, 16419, 3349, 16547, 16675, 3477, 16803, 1173, 16931, 1301, 17059, 1429, 2965, 1557, 17187, 1685, 17315, 2197, 17443, 1813, 17571, 2325,
  17699, 1941, 149, 2453, 277, 2069, 405, 2581, 533, 2709, 661, 29, 789, 157, 917, 285, 1045, 413, 17827, 541, 17955, 669, 18083, 797,
  18211, 925, 18339, 1053, 14, 1181, 142, 1309, 270, 1437, 398, 1565, 1693, 1821, 8235, 8363, 8491, 8619, 8747, 8875, 1949, 9003, 9131, 2077,
  2205, 2333, 3229, 2461, 3357, 2589, 3485, 2717, 8243, 2845, 8371, 2973, 8499, 3101, 8627, 8755, 8883, 9011, 9139, 37, 165, 293, 421, 549,
  677, 805, 933, 1061, 1189, 1317, 1445, 1573, 1701, 1829, 1957, 8251, 8379, 8507, 8635, 8763, 8891, 9019, 9147, 2085, 2213, 2341, 2469, 2597,
  2725, 2853, 2981, 3109, 3237, 3365, 3493, 45, 173, 301, 429, 557, 685, 813, 941, 1069, 1453, 1197, 1581, 1325, 9027, 1709, 1837, 1965,
  8259, 8387, 8515, 8643, 8771, 8899, 693, 9155, 2093, 2221, 2349, 2477, 2605, 2733, 2861, 2989, 3117, 3245, 9163, 2101, 2229, 3373, 3501, 53,
  181, 309, 437, 565, 821, 949, 1077, 1205, 1333, 1461, 1589, 1717, 1845, 1973, 8267, 8395, 8523, 8651, 8779, 8907, 9035, 2357, 2485, 2613,
  2741, 2869, 2997, 3125, 3253, 3381, 3509, 61, 189, 317, 445, 573, 701, 829, 957, 1085, 1213, 1341, 1469, 1597, 1725, 2493, 8275, 1853,
  8403, 1981, 8531, 2109, 8659, 2237, 8787, 2365, 8915, 9043, 9171, 2621, 2749, 2877, 3005, 3133, 3261, 3389, 3517, 1733, 69, 453, 197, 1861,
  325, 581, 709, 837, 1477, 965, 1605, 1093, 1989, 1221, 2117, 1349, 12869, 12997, 2245, 2501, 8283, 8411, 8539, 2629, 8667, 2757, 8795, 2885,
  8923, 9179, 3269, 3397, 1229, 3525, 973, 77, 205, 333, 461, 589, 1357, 717, 845, 1101, 3013, 9051, 3141, 1485, 1613, 1741, 1869, 1997,
  8675, 8291, 8803, 8419, 8931, 8547, 9059, 341, 3277, 85, 22, 469, 3405, 597, 3533, 725, 853, 981, 1109, 1237, 1365, 1493, 9187, 2125,
  2253, 2893, 2381, 2509, 3021, 213, 2637, 3149, 2765, 1621, 1749, 1877, 2005, 2133, 2261, 8427, 8299, 2389, 8555, 2517, 8683, 2645, 8811, 2773,
  8939, 2901, 9067, 3029, 9195, 150, 278, 406, 30, 158, 430, 286, 414, 38, 46, 166, 174, 294, 302, 422, 54, 182, 310, 438,
  8307, 8435, 8563, 8691, 8819, 8947, 9075, 9203, 278651, 311419, 344187, 376955, 278779, 311547, 344315, 377083, 180987, 312315, 148347, 345083, 181115, 148731, 181499, 148859,
  3157, 62, 148987, 149243, 278907, 3285, 190, 318, 149115, 311675, 148219, 344443, 279547, 181627, 1757, 377211, 181755, 181883, 1885, 147963, 2013, 180731, 2141, 2269,
  2397, 101, 2525, 182011, 148091, 180859, 3165, 149371, 182139, 280571, 313339, 346107, 279675, 377851, 378875, 312443, 345211, 377979, 446, 2653, 2781, 2909, 3037, 3293,
  3421, 3549, 3413, 733, 229, 989, 741, 1117, 1245, 869, 997, 1373, 1125, 1501, 1253, 1509, 3541, 93, 1629, 221, 349, 477, 1381, 605,
  357, 485, 861, 613, 1637, 1893, 2021, 2149, 2277, 2405, 2533, 2661, 2789, 12269, 2917, 3045, 12397, 3173, 12525, 3301, 12653, 3429, 12781, 12909,
  3557, 13037, 8301, 8429, 13165, 13293, 1765, 8557, 8685, 13421, 13549, 8813, 13677, 9069, 13805, 9197, 13933, 8941, 14061, 9325, 9453, 14189, 14317, 9581,
  9709, 14445, 14573, 9837, 10861, 10989, 11117, 11245, 11373, 11501, 11629, 9965, 14701, 14829, 10093, 10221, 14957, 15213, 15341, 10605, 10733, 15085, 11757, 10349,
  8573, 11885, 10477, 8701, 12013, 2549, 12141, 2677, 8317, 2805, 2933, 8262, 8390, 8518, 8646, 8774, 9030, 9158, 8902, 9038, 9166, 8270, 8398, 8526,
  8654, 8782, 3061, 8910, 3189, 3317, 117, 245, 373, 501, 629, 757, 3445, 3573, 1269, 1397, 1525, 8445, 8829, 8957, 9085, 9213, 9341, 9469,
  9597, 9725, 9853, 10621, 9981, 10109, 10749, 11645, 10237, 11773, 12029, 10365, 11901, 12157, 12285, 10493, 885, 12413, 1653, 1781, 1013, 1909, 1141, 12541,
  2037, 12669, 2165, 12797, 2293, 12925, 2421, 13053, 13181, 13309, 13565, 13437, 13693, 13821, 10877, 11005, 11133, 11517, 13949, 14077, 14205, 14333, 14461, 14589,
  14717, 14845, 14973, 8278, 8406, 8534, 15101, 8662, 15229, 8790, 15357, 9174, 8918, 11261, 8286, 9046, 8542, 11389, 8414, 8670, 8798, 8926, 9054, 9182,
  147558, 180326, 147686, 180454, 147814, 180582, 16870, 16998, 17126, 17254, 17382, 17510, 17638, 17766, 17894, 18022, 18150, 18278, 18406, 16494, 16622, 16750, 16878, 17006,
  17134, 17390, 17518, 17646, 17774, 17902, 18030, 18158, 17262, 18414, 18286, 16894, 17022, 17150, 17278, 17534, 17662, 17790, 18046, 18174, 278774, 16510, 16638, 311542,
  16766, 18302, 344310, 18430, 147574, 17918, 377078, 17406, 180342, 147830, 180598, 148470, 181238, 182006, 149366, 182134, 148598, 181366, 148726, 148854, 181494, 181622, 147958, 180726,
  148086, 180854, 148214, 180982, 148342, 181110, 148982, 181750, 149110, 181878, 149238, 149494, 182262,
};
void build_list(HList& l) {
  l.n = sizeof(h_items) / sizeof(h_items[0]);
  for (uint32_t i = 0; i < l.n; i++) l.it[i] = h_items[i];
}

typedef CUresult (*EncodeFn)(CUtensorMap*, CUtensorMapDataType, cuuint32_t, void*, const cuuint64_t*, const cuuint64_t*,
                             const cuuint32_t*, const cuuint32_t*, CUtensorMapInterleave, CUtensorMapSwizzle,
                             CUtensorMapL2promotion, CUtensorMapFloatOOBfill);

#define PROMO_W CU_TENSOR_MAP_L2_PROMOTION_L2_128B
#define PROMO_O CU_TENSOR_MAP_L2_PROMOTION_L2_128B
#define PROMO_M CU_TENSOR_MAP_L2_PROMOTION_L2_128B
#define PROMO_H CU_TENSOR_MAP_L2_PROMOTION_L2_128B
void make_map(EncodeFn fn, CUtensorMap* m, const void* p, uint64_t cols, uint64_t rows, uint32_t bc, uint32_t br, CUtensorMapSwizzle sw,
              CUtensorMapL2promotion promo) {
  cuuint64_t dims[2] = {cols, rows};
  cuuint64_t strides[1] = {cols * 2};
  cuuint32_t box[2] = {bc, br};
  cuuint32_t es[2] = {1, 1};
  fn(m, CU_TENSOR_MAP_DATA_TYPE_BFLOAT16, 2, const_cast<void*>(p), dims, strides, box, es, CU_TENSOR_MAP_INTERLEAVE_NONE, sw,
     promo, CU_TENSOR_MAP_FLOAT_OOB_FILL_NONE);
}

void make_map_perm(EncodeFn fn, CUtensorMap* m, const void* p, uint64_t cols, uint64_t rows, bool perm) {
  cuuint64_t dims[5] = {cols, 2, 4, 4, rows / 32};
  cuuint64_t strides[4] = {cols * 2, cols * 2 * (perm ? 8 : 2), cols * 2 * (perm ? 2 : 8), cols * 2 * 32};
  cuuint32_t box[5] = {64, 2, 4, 4, 2};
  cuuint32_t es[5] = {1, 1, 1, 1, 1};
  fn(m, CU_TENSOR_MAP_DATA_TYPE_BFLOAT16, 5, const_cast<void*>(p), dims, strides, box, es, CU_TENSOR_MAP_INTERLEAVE_NONE,
     CU_TENSOR_MAP_SWIZZLE_128B, PROMO_H, CU_TENSOR_MAP_FLOAT_OOB_FILL_NONE);
}

}

extern "C" void kernel_launch(void* const* d_in, const int* in_sizes, int n_in, void* d_out, int out_size) {
  const __nv_bfloat16* x = (const __nv_bfloat16*)d_in[0];
  const __nv_bfloat16* mem0 = (const __nv_bfloat16*)d_in[1];
  const __nv_bfloat16* cvec = (const __nv_bfloat16*)d_in[11];
  static EncodeFn enc = nullptr;
  if (!enc) {
    cudaDriverEntryPointQueryResult qr;
    void* fp = nullptr;
    cudaGetDriverEntryPoint("cuTensorMapEncodeTiled", &fp, cudaEnableDefault, &qr);
    enc = (EncodeFn)fp;
    cudaFuncSetAttribute(kernel_R, cudaFuncAttributeMaxDynamicSharedMemorySize, R_SMEM);
    cudaFuncSetAttribute(kernel_H, cudaFuncAttributeMaxDynamicSharedMemorySize, H_SMEM);
  }
  CUtensorMap tmq, tmk, tmv, tmo, tmm;
  make_map(enc, &tmm, d_in[12], 6144, 1024, 64, 64, CU_TENSOR_MAP_SWIZZLE_NONE, PROMO_M);
  make_map(enc, &tmq, d_in[2], 4096, 1024, 64, 64, CU_TENSOR_MAP_SWIZZLE_128B, PROMO_W);
  make_map(enc, &tmk, d_in[3], 4096, 1024, 64, 64, CU_TENSOR_MAP_SWIZZLE_128B, PROMO_W);
  make_map(enc, &tmv, d_in[4], 4096, 1024, 64, 64, CU_TENSOR_MAP_SWIZZLE_128B, PROMO_W);
  make_map(enc, &tmo, d_in[5], 1024, 4096, 16, 128, CU_TENSOR_MAP_SWIZZLE_32B, PROMO_O);
  RDesc dsc;
  for (int k = 0; k < 32; k++) {
    dsc.tok[k] = mkdesc(0x400 + (k < 16 ? R_GA : R_GB) + ((k & 15) >> 2) * 4096 + (k & 3) * 256, 128, 1024, 0);
    dsc.tail_a[k] = mkdesc(0x400 + R_TAIL + k * 2048, 1024, 1024, 1);
    if (k < 16) dsc.tail_b[k] = mkdesc(0x400 + R_GA + k * 256, 128, 4096, 0);
  }
  kernel_R<<<96, 256, R_SMEM, cudaStreamPerThread>>>(tmq, tmk, tmv, tmo, tmm, x, mem0, cvec, dsc);

  CUtensorMap ho, h1, h3, h2, hm;
  make_map_perm(enc, &ho, d_in[5], 1024, 4096, false);
  make_map_perm(enc, &h1, d_in[8], F_, 1024, true);
  make_map_perm(enc, &h3, d_in[9], F_, 1024, true);
  make_map_perm(enc, &h2, d_in[10], 1024, F_, true);
  make_map_perm(enc, &hm, d_in[12], 6144, 1024, true);
  HList list;
  build_list(list);
  cudaLaunchConfig_t cfg = {};
#define H_GRID 132
  cfg.gridDim = dim3(H_GRID); cfg.blockDim = dim3(384); cfg.dynamicSmemBytes = H_SMEM; cfg.stream = cudaStreamPerThread;
  cudaLaunchAttribute at[1];
  at[0].id = cudaLaunchAttributeProgrammaticStreamSerialization;
  at[0].val.programmaticStreamSerializationAllowed = 1;
  cfg.attrs = at;
  cfg.numAttrs = 1;
  cudaLaunchKernelEx(&cfg, kernel_H, ho, h1, h3, h2, hm, x, cvec, (__nv_bfloat16*)d_out, list);
}
```

```cpp
#include <cuda_runtime.h>
#include <cuda_bf16.h>
#include <cuda.h>
#include <stdint.h>
#include <type_traits>

namespace {

constexpr int S_ = 2048, D_ = 1024, NSEG = 64, F_ = 3584;

__device__ __align__(1024) uint8_t g_h[S_ * D_ * 2];
__device__ __align__(1024) uint8_t g_att[S_ * 4096 * 2];
__device__ __align__(1024) uint8_t g_x1[S_ * D_ * 2];
__device__ __align__(1024) uint8_t g_h2[S_ * D_ * 2];
__device__ __align__(1024) uint8_t g_act[S_ * F_ * 2];
__device__ __align__(1024) float g_ws[12 * 16 * 4 * 8192];
__device__ __align__(1024) float g_stat[S_ * 2];
__device__ __align__(1024) float g_uv[F_ * 4];
__device__ __align__(1024) float g_slot[4 * 3 * 8 * 4 * 32 * 4];
__device__ __align__(128) __nv_bfloat16 g_mod[6 * D_];
__device__ __align__(128) float g_modp[3 * 2 * D_];
__device__ __align__(128) uint32_t g_flags[1024];
constexpr int FL_S1 = 0, FL_S2 = 32, FL_MOD = 64, FL_HEAD = 96, FL_EXIT = 128, FL_UV = 160, FL_GO = 192, FL_MODB = 224, FL_MODA = 240, FL_ATT = 256, FL_XT = 384, FL_OUT = 512, FL_F1 = 640, FL_SPL = 768;

#define EVF 1
__device__ __forceinline__ uint32_t smem_u32(const void* p) { return (uint32_t)__cvta_generic_to_shared(p); }
__device__ __forceinline__ uint32_t mapa(uint32_t a, uint32_t r) { uint32_t o; asm("mapa.shared::cluster.u32 %0, %1, %2;" : "=r"(o) : "r"(a), "r"(r)); return o; }
__device__ __forceinline__ uint32_t pack2(float a, float b) { uint32_t r; asm("cvt.rn.bf16x2.f32 %0, %1, %2;" : "=r"(r) : "f"(b), "f"(a)); return r; }
__device__ __forceinline__ float bf_lo(uint32_t w) { return __uint_as_float(w << 16); }
__device__ __forceinline__ float bf_hi(uint32_t w) { return __uint_as_float(w & 0xffff0000u); }
__device__ __forceinline__ float ex2(float x) { float y; asm("ex2.approx.ftz.f32 %0, %1;" : "=f"(y) : "f"(x)); return y; }
__device__ __forceinline__ float rcp(float x) { float y; asm("rcp.approx.ftz.f32 %0, %1;" : "=f"(y) : "f"(x)); return y; }
__device__ __forceinline__ uint32_t clk32() { uint64_t c; asm volatile("mov.u64 %0, %%clock64;" : "=l"(c) :: "memory"); return (uint32_t)c; }

__device__ __forceinline__ void mbar_init(uint32_t b, uint32_t n) { asm volatile("mbarrier.init.shared::cta.b64 [%0], %1;" :: "r"(b), "r"(n) : "memory"); }
__device__ __forceinline__ void mbar_arrive(uint32_t b) { asm volatile("mbarrier.arrive.shared::cta.b64 _, [%0];" :: "r"(b) : "memory"); }
__device__ __forceinline__ void mbar_expect(uint32_t b, uint32_t n) { asm volatile("mbarrier.arrive.expect_tx.shared::cta.b64 _, [%0], %1;" :: "r"(b), "r"(n) : "memory"); }
__device__ __forceinline__ uint32_t mbar_try(uint32_t b, uint32_t par) {
  uint32_t ok;
  asm volatile("{\n.reg .pred p;\nmbarrier.try_wait.parity.shared::cta.b64 p, [%1], %2;\nselp.u32 %0, 1, 0, p;\n}" : "=r"(ok) : "r"(b), "r"(par) : "memory");
  return ok;
}
__device__ __forceinline__ bool mbar_test(uint32_t b, uint32_t par) {
  uint32_t ok;
  asm volatile("{\n.reg .pred p;\nmbarrier.test_wait.parity.shared::cta.b64 p, [%1], %2;\nselp.u32 %0, 1, 0, p;\n}" : "=r"(ok) : "r"(b), "r"(par) : "memory");
  return ok;
}
__device__ __forceinline__ void mbar_wait(uint32_t b, uint32_t par) {
  asm volatile("{\n.reg .pred p;\n"
               "LOOP:\n"
               "mbarrier.try_wait.parity.shared::cta.b64 p, [%0], %1;\n"
               "@!p bra.uni LOOP;\n}" :: "r"(b), "r"(par) : "memory");
}
__device__ __forceinline__ void mbar_wait_safe(uint32_t b, uint32_t par) {
  uint32_t c = 0;
  while (!mbar_try(b, par)) { if (++c > 4000000u) __trap(); }
}
__device__ __forceinline__ bool elect_one() {
  uint32_t p;
  asm volatile("{\n.reg .pred p;\nelect.sync _|p, 0xffffffff;\nselp.u32 %0, 1, 0, p;\n}" : "=r"(p));
  return p;
}
__device__ __forceinline__ void sched_fence(uint32_t x, uint32_t y) { asm volatile("{\n.reg .pred p;\nsetp.eq.u32 p, %0, %1;\n@p trap;\n}" :: "r"(x), "r"(y) : "memory"); }
template <class T> __device__ __forceinline__ T opaque32(T x) { asm volatile("" : "+r"(x)); return x; }
template <class T> __device__ __forceinline__ T opaque64(T x) { asm volatile("" : "+l"(x)); return x; }
template <int ID, int N> __device__ __forceinline__ void bar_sync() { asm volatile("bar.sync %0, %1;" :: "n"(ID), "n"(N) : "memory"); }
template <int ID, int N> __device__ __forceinline__ void bar_arrive() { asm volatile("bar.arrive %0, %1;" :: "n"(ID), "n"(N) : "memory"); }
__device__ __forceinline__ void fence_async_smem() { asm volatile("fence.proxy.async.shared::cta;" ::: "memory"); }
__device__ __forceinline__ void fence_async_all() { asm volatile("fence.proxy.async;" ::: "memory"); }
__device__ __forceinline__ void fence_gpu() { asm volatile("fence.acq_rel.gpu;" ::: "memory"); }
__device__ __forceinline__ void red_add_u32(uint32_t* p, uint32_t v) { asm volatile("red.relaxed.gpu.global.add.u32 [%0], %1;" :: "l"(p), "r"(v) : "memory"); }
__device__ __forceinline__ uint32_t ld_acquire(const uint32_t* p) { uint32_t v; asm volatile("ld.acquire.gpu.global.u32 %0, [%1];" : "=r"(v) : "l"(p) : "memory"); return v; }
__device__ __forceinline__ void wait_flag(const uint32_t* p, uint32_t target) {
  uint32_t c = 0;
  while (ld_acquire(p) < target) { if (++c > 20000000u) __trap(); __nanosleep(20); }
}

__device__ __forceinline__ void wait_flag2(const uint32_t* p, uint32_t target) {
  asm volatile("{\n.reg .pred p;\n.reg .u32 v, c;\nmov.u32 c, 0;\nWL:\nld.acquire.gpu.global.u32 v, [%0];\nsetp.ge.u32 p, v, %1;\n@p bra WD;\n"
               "add.u32 c, c, 1;\nsetp.gt.u32 p, c, 20000000;\n@p trap;\nnanosleep.u32 20;\nbra WL;\nWD:\n}" :: "l"(p), "r"(target) : "memory");
}
__device__ __forceinline__ void tma2d(uint32_t dst, const CUtensorMap* m, int c0, int c1, uint32_t bar) {
  asm volatile("cp.async.bulk.tensor.2d.shared::cluster.global.mbarrier::complete_tx::bytes [%0], [%1, {%3, %4}], [%2];"
               :: "r"(dst), "l"(m), "r"(bar), "r"(c0), "r"(c1) : "memory");
}
__device__ __forceinline__ void tma2d_once(uint32_t dst, const CUtensorMap* m, int c0, int c1, uint32_t bar) {
  asm volatile("{\n.reg .b64 pol;\ncreatepolicy.fractional.L2::evict_first.b64 pol, 1.0;\n"
               "cp.async.bulk.tensor.2d.shared::cluster.global.mbarrier::complete_tx::bytes.L2::cache_hint [%0], [%1, {%3, %4}], [%2], pol;\n}"
               :: "r"(dst), "l"(m), "r"(bar), "r"(c0), "r"(c1) : "memory");
}
__device__ __forceinline__ void tma5d(uint32_t dst, const CUtensorMap* m, int n0, int kb, uint32_t bar) {
  asm volatile("cp.async.bulk.tensor.5d.shared::cluster.global.mbarrier::complete_tx::bytes [%0], [%1, {%3, %5, %5, %5, %4}], [%2];"
               :: "r"(dst), "l"(m), "r"(bar), "r"(n0), "r"(2 * kb), "r"(0) : "memory");
}
__device__ __forceinline__ void tma2d_prefetch(const CUtensorMap* m, int c0, int c1) {
  asm volatile("cp.async.bulk.prefetch.tensor.2d.L2.global [%0, {%1, %2}];" :: "l"(m), "r"(c0), "r"(c1) : "memory");
}
__device__ __forceinline__ void bulk_g2s(uint32_t dst, const void* src, uint32_t bytes, uint32_t bar) {
  asm volatile("cp.async.bulk.shared::cluster.global.mbarrier::complete_tx::bytes [%0], [%1], %2, [%3];"
               :: "r"(dst), "l"(src), "r"(bytes), "r"(bar) : "memory");
}
__device__ __forceinline__ void bulk_s2s(uint32_t dst, uint32_t src, uint32_t bytes, uint32_t bar) {
  asm volatile("cp.async.bulk.shared::cluster.shared::cta.mbarrier::complete_tx::bytes [%0], [%1], %2, [%3];"
               :: "r"(dst), "r"(src), "r"(bytes), "r"(bar) : "memory");
}
__device__ __forceinline__ void st_async1(uint32_t dst, uint32_t a, uint32_t bar) {
  asm volatile("st.async.shared::cluster.mbarrier::complete_tx::bytes.b32 [%0], %1, [%2];" :: "r"(dst), "r"(a), "r"(bar) : "memory");
}
__device__ __forceinline__ void st_async2(uint32_t dst, uint32_t a, uint32_t b, uint32_t bar) {
  asm volatile("st.async.shared::cluster.mbarrier::complete_tx::bytes.v2.b32 [%0], {%1, %2}, [%3];" :: "r"(dst), "r"(a), "r"(b), "r"(bar) : "memory");
}
__device__ __forceinline__ void st_async4(uint32_t dst, const uint32_t* r, uint32_t bar) {
  asm volatile("st.async.shared::cluster.mbarrier::complete_tx::bytes.v4.b32 [%0], {%1, %2, %3, %4}, [%5];"
               :: "r"(dst), "r"(r[0]), "r"(r[1]), "r"(r[2]), "r"(r[3]), "r"(bar) : "memory");
}
__device__ __forceinline__ void sts32(uint32_t a, uint32_t v) { asm volatile("st.shared.b32 [%0], %1;" :: "r"(a), "r"(v) : "memory"); }
__device__ __forceinline__ void sts64(uint32_t a, uint32_t x, uint32_t y) { asm volatile("st.shared.v2.b32 [%0], {%1, %2};" :: "r"(a), "r"(x), "r"(y) : "memory"); }
__device__ __forceinline__ void sts128(uint32_t a, uint32_t x, uint32_t y, uint32_t z, uint32_t w) {
  asm volatile("st.shared.v4.b32 [%0], {%1, %2, %3, %4};" :: "r"(a), "r"(x), "r"(y), "r"(z), "r"(w) : "memory");
}
__device__ __forceinline__ void lds128(uint32_t* r, uint32_t a) {
  asm volatile("ld.shared.v4.b32 {%0, %1, %2, %3}, [%4];" : "=r"(r[0]), "=r"(r[1]), "=r"(r[2]), "=r"(r[3]) : "r"(a) : "memory");
}
__device__ __forceinline__ uint32_t lds32(uint32_t a) { uint32_t r; asm volatile("ld.shared.b32 %0, [%1];" : "=r"(r) : "r"(a) : "memory"); return r; }
__device__ __forceinline__ void lds64(uint32_t* r, uint32_t a) {
  asm volatile("ld.shared.v2.b32 {%0, %1}, [%2];" : "=r"(r[0]), "=r"(r[1]) : "r"(a) : "memory");
}
__device__ __forceinline__ void lds128f(float* r, uint32_t a) {
  asm volatile("ld.shared.v4.f32 {%0, %1, %2, %3}, [%4];" : "=f"(r[0]), "=f"(r[1]), "=f"(r[2]), "=f"(r[3]) : "r"(a) : "memory");
}
__device__ __forceinline__ void lds64f(float* r, uint32_t a) {
  asm volatile("ld.shared.v2.f32 {%0, %1}, [%2];" : "=f"(r[0]), "=f"(r[1]) : "r"(a) : "memory");
}
__device__ __forceinline__ void ldsm4(uint32_t* r, uint32_t a) {
  asm volatile("ldmatrix.sync.aligned.m8n8.x4.shared.b16 {%0, %1, %2, %3}, [%4];" : "=r"(r[0]), "=r"(r[1]), "=r"(r[2]), "=r"(r[3]) : "r"(a) : "memory");
}
__device__ __forceinline__ void ldsm4t(uint32_t* r, uint32_t a) {
  asm volatile("ldmatrix.sync.aligned.m8n8.x4.trans.shared.b16 {%0, %1, %2, %3}, [%4];" : "=r"(r[0]), "=r"(r[1]), "=r"(r[2]), "=r"(r[3]) : "r"(a) : "memory");
}
__device__ __forceinline__ void ldsm2(uint32_t* r, uint32_t a) {
  asm volatile("ldmatrix.sync.aligned.m8n8.x2.shared.b16 {%0, %1}, [%2];" : "=r"(r[0]), "=r"(r[1]) : "r"(a) : "memory");
}
__device__ __forceinline__ void stsm4(uint32_t a, const uint32_t* r) {
  asm volatile("stmatrix.sync.aligned.m8n8.x4.shared.b16 [%0], {%1, %2, %3, %4};" :: "r"(a), "r"(r[0]), "r"(r[1]), "r"(r[2]), "r"(r[3]) : "memory");
}
__device__ __forceinline__ uint32_t hadd2(uint32_t a, uint32_t b) { uint32_t t; asm("add.rn.bf16x2 %0, %1, %2;" : "=r"(t) : "r"(a), "r"(b)); return t; }
__device__ __forceinline__ uint32_t hmax2(uint32_t a, uint32_t b) { uint32_t t; asm("max.bf16x2 %0, %1, %2;" : "=r"(t) : "r"(a), "r"(b)); return t; }
__device__ __forceinline__ void ldsm2t(uint32_t* r, uint32_t a) {
  asm volatile("ldmatrix.sync.aligned.m8n8.x2.trans.shared.b16 {%0, %1}, [%2];" : "=r"(r[0]), "=r"(r[1]) : "r"(a) : "memory");
}
__device__ __forceinline__ uint32_t movm(uint32_t x) { uint32_t y; asm volatile("movmatrix.sync.aligned.m8n8.trans.b16 %0, %1;" : "=r"(y) : "r"(x)); return y; }
__device__ __forceinline__ void hmma(float* d, uint32_t a0, uint32_t a1, uint32_t a2, uint32_t a3, uint32_t b0, uint32_t b1) {
  asm volatile("mma.sync.aligned.m16n8k16.row.col.f32.bf16.bf16.f32 {%0,%1,%2,%3}, {%4,%5,%6,%7}, {%8,%9}, {%0,%1,%2,%3};"
               : "+f"(d[0]), "+f"(d[1]), "+f"(d[2]), "+f"(d[3]) : "r"(a0), "r"(a1), "r"(a2), "r"(a3), "r"(b0), "r"(b1));
}
__device__ __forceinline__ void hmma0(float* d, uint32_t a0, uint32_t a1, uint32_t a2, uint32_t a3, uint32_t b0, uint32_t b1) {
  asm volatile("mma.sync.aligned.m16n8k16.row.col.f32.bf16.bf16.f32 {%0,%1,%2,%3}, {%4,%5,%6,%7}, {%8,%9}, {%10,%10,%10,%10};"
               : "=f"(d[0]), "=f"(d[1]), "=f"(d[2]), "=f"(d[3]) : "r"(a0), "r"(a1), "r"(a2), "r"(a3), "r"(b0), "r"(b1), "f"(0.f));
}
__device__ __forceinline__ void hmma_k8(float* d, uint32_t a0, uint32_t a1, uint32_t b0) {
  asm volatile("mma.sync.aligned.m16n8k8.row.col.f32.bf16.bf16.f32 {%0,%1,%2,%3}, {%4,%5}, {%6}, {%0,%1,%2,%3};"
               : "+f"(d[0]), "+f"(d[1]), "+f"(d[2]), "+f"(d[3]) : "r"(a0), "r"(a1), "r"(b0));
}
__host__ __device__ constexpr uint64_t mkdesc(uint32_t addr, uint32_t lbo, uint32_t sbo, uint32_t sw) {
  return (uint64_t)((addr & 0x3FFFF) >> 4) | ((uint64_t)(lbo >> 4) << 16) | ((uint64_t)(sbo >> 4) << 32) | ((uint64_t)sw << 62);
}
#define WG_FENCE() asm volatile("wgmma.fence.sync.aligned;" ::: "memory")
#define WG_COMMIT() asm volatile("wgmma.commit_group.sync.aligned;" ::: "memory")
#define WG_WAIT(n) asm volatile("wgmma.wait_group.sync.aligned " #n ";" ::: "memory")
template <int N> __device__ __forceinline__ void reg_fence(float* d) {
#pragma unroll
  for (int i = 0; i < N; i++) asm volatile("" : "+f"(d[i]) :: "memory");
}
template <int N> __device__ __forceinline__ void zero_regs(float* d) {
#pragma unroll
  for (int i = 0; i < N; i++) asm volatile("mov.b32 %0, 0;" : "=f"(d[i]));
}
template <int SD>
__device__ __forceinline__ void wg_rs32(float* d, uint32_t a0, uint32_t a1, uint32_t a2, uint32_t a3, uint64_t b) {
  asm volatile("wgmma.mma_async.sync.aligned.m64n32k16.f32.bf16.bf16 {%0,%1,%2,%3,%4,%5,%6,%7,%8,%9,%10,%11,%12,%13,%14,%15}, {%16,%17,%18,%19}, %20, %21, 1, 1, 0;"
               : "+f"(d[0]), "+f"(d[1]), "+f"(d[2]), "+f"(d[3]), "+f"(d[4]), "+f"(d[5]), "+f"(d[6]), "+f"(d[7]),
                 "+f"(d[8]), "+f"(d[9]), "+f"(d[10]), "+f"(d[11]), "+f"(d[12]), "+f"(d[13]), "+f"(d[14]), "+f"(d[15])
               : "r"(a0), "r"(a1), "r"(a2), "r"(a3), "l"(b), "n"(SD));
}
template <int TB>
__device__ __forceinline__ void wg_ss40(float* d, uint64_t a, uint64_t b) {
  asm volatile("wgmma.mma_async.sync.aligned.m64n40k16.f32.bf16.bf16 {%0,%1,%2,%3,%4,%5,%6,%7,%8,%9,%10,%11,%12,%13,%14,%15,%16,%17,%18,%19}, %20, %21, 1, 1, 1, 1, %22;"
               : "+f"(d[0]), "+f"(d[1]), "+f"(d[2]), "+f"(d[3]), "+f"(d[4]), "+f"(d[5]), "+f"(d[6]), "+f"(d[7]),
                 "+f"(d[8]), "+f"(d[9]), "+f"(d[10]), "+f"(d[11]), "+f"(d[12]), "+f"(d[13]), "+f"(d[14]), "+f"(d[15]),
                 "+f"(d[16]), "+f"(d[17]), "+f"(d[18]), "+f"(d[19])
               : "l"(a), "l"(b), "n"(TB));
}
__device__ __forceinline__ void wg_ss8(float* d, uint64_t a, uint64_t b) {
  asm volatile("wgmma.mma_async.sync.aligned.m64n8k16.f32.bf16.bf16 {%0,%1,%2,%3}, %4, %5, 1, 1, 1, 1, 0;"
               : "+f"(d[0]), "+f"(d[1]), "+f"(d[2]), "+f"(d[3]) : "l"(a), "l"(b));
}
template <int T>
__device__ __forceinline__ void wg_ss32(float* d, uint64_t a, uint64_t b) {
  asm volatile("wgmma.mma_async.sync.aligned.m64n32k16.f32.bf16.bf16 {%0,%1,%2,%3,%4,%5,%6,%7,%8,%9,%10,%11,%12,%13,%14,%15}, %16, %17, 1, 1, 1, %18, %18;"
               : "+f"(d[0]), "+f"(d[1]), "+f"(d[2]), "+f"(d[3]), "+f"(d[4]), "+f"(d[5]), "+f"(d[6]), "+f"(d[7]),
                 "+f"(d[8]), "+f"(d[9]), "+f"(d[10]), "+f"(d[11]), "+f"(d[12]), "+f"(d[13]), "+f"(d[14]), "+f"(d[15])
               : "l"(a), "l"(b), "n"(T));
}

constexpr int R_TAIL = 0;
constexpr int R_WO = 65536;
constexpr int R_QK = R_WO + 86016;
constexpr int R_P = R_QK + 10240;
constexpr int R_GA = R_P + 6400;
constexpr int R_M2 = R_GA + 16384;
constexpr int R_M1 = R_M2 + 7168;
constexpr int R_GB = R_M1 + 9216;
constexpr int R_VT = R_GB + 16384;
constexpr int R_VM = R_VT + 8192;
constexpr int R_XS = R_VM + 2048;
constexpr int R_OX = R_XS + 1280;
constexpr int R_BAR = R_OX + 2048;
constexpr int R_TRC = R_BAR + 256;
constexpr int R_SMEM = R_TRC + 1024;
constexpr int B_MB = 0, B_XS = 32, B_VM = 40, B_VT = 48, B_TS = 56, B_FA = 64, B_FB = 72, B_TAIL = 80, B_WO = 88, B_STG = 96, B_WM = 128, B_X = 136;
constexpr int NB_A = 1, NB_B = 2, NB_X = 3, NB_C = 4, NB_D = 5, NB_E = 6, NB_F = 7, NB_G = 8, NB_H = 9, NB_S = 10, NB_E2 = 11, NB_P = 12, NB_W0 = 13;

#define FIN 1
#define POLL_DELAY 750
#define POLL_DELAY1 700
#define POLL_STAG 150
#define POLL_K0 20
#define PF1 2
#define PF2 2
#define PF3 2
#define PF4 0
#define CLR_D 2
#define PADN 0
#define PFD 0
#define GO_EARLY 0
#define RF_FIRST 1
#define BX_I 5
#define NCH 4
#define TOP2 0
#define CX_I 13
#define ATT_LATE 0
#define V_FENCE 1
#define SELF_STAS 1
#define Q_FENCE 1
#define ND_K 3
#define TRACE(i)
#define TS(i)

__device__ __forceinline__ int rot_chunk(int c, int rank) {
  int G = c;
  if (c < 9) { G = c + 3 * rank; if (G >= 9) G -= 9; }
  return G;
}
__device__ __forceinline__ int wo_tile(int i, int rank) {
  if (i < 12) return 12 * rank + i;
  const int r = i - 12 + 9 * rank;
  return r < 16 ? 48 + r : 20 + r;
}
__device__ __forceinline__ void load_chunk(uint32_t dst, int seg, int G, uint32_t bar) {
  mbar_expect(bar, 4096);
  bulk_g2s(dst, g_h + (size_t)(seg * 16 + G) * 4096, 4096, bar);
}
__device__ __forceinline__ void load_red(uint32_t* v, const float* p) {
#pragma unroll
  for (int j = 0; j < 2; j++)
    asm volatile("ld.relaxed.gpu.global.v4.u32 {%0, %1, %2, %3}, [%4];"
                 : "=r"(v[4 * j]), "=r"(v[4 * j + 1]), "=r"(v[4 * j + 2]), "=r"(v[4 * j + 3]) : "l"(p + j * 256) : "memory");
}
__device__ __forceinline__ bool red_done(const uint32_t* v) { return __all_sync(0xffffffffu, (v[3] & v[7]) == 0x42000000u); }
__device__ __forceinline__ uint32_t finish_red(uint32_t* v, const float* p) {
  uint32_t tries = 0;
  if (__builtin_expect(!red_done(v), 0)) {
    do { if (++tries > 20000000u) __trap(); load_red(v, p); } while (!red_done(v));
  }
  return tries;
}
__device__ __forceinline__ void exp10(float* sv, const uint32_t* x) {
  constexpr float SC = 0.08838834764831845f * 1.4426950408889634f;
  uint32_t m2 = hmax2(hmax2(hmax2(x[0], x[1]), hmax2(x[2], x[3])), x[4]);
  m2 = hmax2(m2, __shfl_xor_sync(0xffffffffu, m2, 1));
  m2 = hmax2(m2, __shfl_xor_sync(0xffffffffu, m2, 2));
  const float nm = -fmaxf(bf_lo(m2), bf_hi(m2)) * SC;
#pragma unroll
  for (int j = 0; j < 5; j++) { sv[2 * j] = ex2(fmaf(bf_lo(x[j]), SC, nm)); sv[2 * j + 1] = ex2(fmaf(bf_hi(x[j]), SC, nm)); }
}

__device__ __forceinline__ uint32_t arm_size(int w, bool isC) {
  return w == 0 ? (isC ? 1280 : 640) : w == 1 ? (isC ? 0 : 2048) : w == 2 ? (isC ? 0 : 8192) : (isC ? 0 : 1792);
}
struct RDesc { uint64_t tok[32], tail_b[16], tail_a[32]; };

template <int WG>
__device__ __forceinline__ void r_main(const uint32_t (&W)[48][4], const RDesc& dsc, int head, uint32_t rank, int lane_, int w) {
  const uint32_t sb = (rank << 24) + 0x400, bars = sb + R_BAR;
  const uint32_t to1 = rank == 0 ? 2u << 24 : 0u - (1u << 24), to2 = rank == 2 ? 0u - (2u << 24) : 1u << 24;
  const bool isC = rank == 2;
  const int lane = opaque32(lane_), warp = WG * 4 + w;
  const int gl = rot_chunk(4 * (lane & 3) + w, rank);
  const int g0 = __shfl_sync(0xffffffffu, gl, 0), g1 = __shfl_sync(0xffffffffu, gl, 1), g2 = __shfl_sync(0xffffffffu, gl, 2);
  const uint32_t arm_bytes = arm_size(w, isC);

#define L16 opaque32(sb + opaque32(lane) * 16)
#define L8 opaque32(sb + opaque32(lane) * 8)
#define L4 opaque32(sb + opaque32(lane) * 4)
#define LV opaque32(sb + R_VT + ((opaque32(lane) >> 3) & 1) * 512 + (opaque32(lane) >> 4) * 128 + (opaque32(lane) & 7) * 16)
#define SLOT(st) opaque64(slot0 + ((st) & 3) * 12288 + ((st) & 4) * 32)
  float* const slot0 = opaque64(g_slot + (rank * 1024 + warp * 128 + lane) * 4);
  const uint32_t woa = opaque32(sb + R_WO + warp * 12288 + ((lane >> 4) * 8 + (lane & 7)) * 32 + ((((lane >> 3) ^ (lane >> 2)) & 1) << 4));
  const bool has_wo = WG == 0 || isC || w < 3;
  float acc[20];
  uint32_t pk[8] = {0u, 0u, 0u, 0u, 0u, 0u, 0u, 0u};

  auto forward = [&](auto rd, const uint32_t* v, int st, uint32_t tries) {
    constexpr int RD = decltype(rd)::value;
    uint32_t u[6];
#pragma unroll
    for (int j = 0; j < 6; j++) u[j] = movm(v[4 * (j / 3) + j % 3]);
    const bool all3 = RD == 0 || w < 3;
    if (RD == 0) {
      const uint32_t a = L16 + R_M1 + w * 768, a2 = L8 + R_M1 + 512 + w * 768;
      st_async4(a + to1 + 3072, u, bars + to1 + B_MB + 8); st_async2(a2 + to1 + 3072, u[4], u[5], bars + to1 + B_MB + 8);
      sts128(a, u[0], u[1], u[2], u[3]); sts64(a2, u[4], u[5]);
      __syncwarp();
      if (elect_one()) mbar_arrive(bars + B_MB);
      st_async4(a + to2 + 6144, u, bars + to2 + B_MB + 16); st_async2(a2 + to2 + 6144, u[4], u[5], bars + to2 + B_MB + 16);
    } else {
      const uint32_t a = L4 + R_M2 + rank * 2304 + w * 768;
#pragma unroll
      for (int j = 0; j < 6; j++) if (j < 2 || all3) st_async1(a + to1 + j * 128, u[j], bars + to1 + B_MB + 24);
#pragma unroll
      for (int j = 0; j < 6; j++) if (j < 2 || all3) st_async1(a + to2 + j * 128, u[j], bars + to2 + B_MB + 24);
      if (SELF_STAS) {
#pragma unroll
        for (int j = 0; j < 6; j++) if (j < 2 || all3) st_async1(a + j * 128, u[j], bars + B_MB + 24);
      } else {
#pragma unroll
        for (int j = 0; j < 6; j++) if (j < 2 || all3) sts32(a + j * 128, u[j]);
        __syncwarp();
        if (elect_one()) mbar_arrive(bars + B_MB + 24);
      }
    }
  };

  auto send_vt = [&]() {
    if (elect_one()) {
      const uint32_t src = sb + R_VT + warp * 1024;
      bulk_s2s(src + to1, src, 1024, bars + to1 + B_VT);
      bulk_s2s(src + to2, src, 1024, bars + to2 + B_VT);
    }
  };
  auto store_att = [&](int sg) {
    uint32_t* op = reinterpret_cast<uint32_t*>(g_att + (size_t)((sg >> 2) * 64 + head * 2 + rank) * 16384 + (2 * w * 16 + (sg & 3) * 4) * 128) + opaque32(lane);
#pragma unroll
    for (int j = 0; j < 8; j++) op[(j & 1) * 512 + (j >> 1) * 32] = pk[j];
  };

  if (WG == 0) bar_arrive<NB_G, 256>();
#pragma unroll 1
  for (int s = -1; s < NSEG - FIN; s++) {
    const uint32_t par = (s + 1) & 1;
    const uint32_t last = !FIN && s == NSEG - 1;
    TRACE(0);
    {
      float c[NCH][4];
      uint32_t b[3][6];
      const uint32_t ma = L16, m8 = L8;
#pragma unroll
      for (int i = 0; i < 18; i++) {
        if (i < 16) {
          if (i % 4 == 0 && !(i == 4 && TOP2)) mbar_wait(bars + B_MB + (i / 4) * 8, par ^ 1);
          if (i == 0 && TOP2) mbar_wait(bars + B_MB + 8, par ^ 1);
          if (i % 4 == 0) TRACE(1 + i / 4);
          if (i < 12) { lds128(b[i % 3], ma + R_M1 + i * 768); lds64(b[i % 3] + 4, m8 + R_M1 + 512 + i * 768); }
          else { ldsm4(b[i % 3], ma + R_M2 + 4096 + (i - 12) * 768); ldsm2(b[i % 3] + 4, ma + R_M2 + 4096 + 512 + (i - 12) * 768); }
          if (WG == 1 && i == BX_I) {
            bar_sync<NB_G, 256>();
            if (!last && elect_one()) load_chunk(sb + R_GB + w * 4096, s + 1, g0, bars + B_FB);
          }
          if (i == CX_I) {
            if (isC && s >= 0) send_vt();
            if (WG == 1 && ATT_LATE && !isC && s > 0) store_att(s - 1);
          }
          __syncwarp();
        }
        if (i >= 2) {
          const int j = i - 2;
#pragma unroll
          for (int q = 0; q < 3; q++) {
            const uint32_t* f = W[3 * j + q];
            if (3 * j + q < NCH) hmma0(c[3 * j + q], f[0], f[1], f[2], f[3], b[j % 3][2 * q], b[j % 3][2 * q + 1]);
            else hmma(c[(3 * j + q) % NCH], f[0], f[1], f[2], f[3], b[j % 3][2 * q], b[j % 3][2 * q + 1]);
          }
        }
        if (i == 14) zero_regs<16>(acc);
        if (i == 16) mbar_wait(bars + B_FA, last);
      }
#pragma unroll
      for (int j = 0; j < 4; j++) acc[16 + j] = NCH == 3 ? (c[0][j] + c[1][j]) + c[2][j] : (c[0][j] + c[1][j]) + (c[2][j] + c[NCH - 1][j]);
    }
    TRACE(5);
    bar_sync<NB_H, 256>();
    WG_FENCE();
#pragma unroll
    for (int k = 0; k < 16; k++) wg_ss40<0>(acc, dsc.tail_a[WG * 16 + k], dsc.tail_b[k]);
    WG_COMMIT();
    uint32_t vt[4][4];
    {
      const uint32_t a = opaque32(L4 + w * 256 + (isC ? WG * 1024 + R_VM : R_QK + 4096 + WG * 5120));
      const uint32_t qa = L16 + R_QK, xa = opaque32(LV + w * 2048 + (WG == 0 ? 0 : (opaque32(lane) & 8) * 64 + R_QK + 5120 - R_VT));
      const uint32_t d = opaque32(L4 + R_XS + rank * 640 + w * 256);
      if (s == 0) {
        mbar_wait_safe(bars + B_WO, 0);
        if (!GO_EARLY && WG == 1 && head == 0 && rank == 0 && w == 0 && elect_one()) red_add_u32(&g_flags[FL_GO], 1);
      }
      mbar_wait(bars + B_FB, last);
      if (WG == 0) mbar_wait(bars + B_VT, par);
      WG_WAIT(0);
      reg_fence<20>(acc);
      TRACE(6);
      const uint32_t p0 = pack2(acc[16], acc[17]), p1 = pack2(acc[18], acc[19]);
      sts32(a, p0); sts32(a + 128, p1);
      if (isC) {
        st_async1(a + to1, p0, bars + B_VM + to1); st_async1(a + to1 + 128, p1, bars + B_VM + to1);
        st_async1(a + to2, p0, bars + B_VM + to2); st_async1(a + to2 + 128, p1, bars + B_VM + to2);
      }
      if (WG == 0) {
        bar_arrive<NB_A, 256>();
        if (Q_FENCE && !isC) fence_async_smem();
#pragma unroll
        for (int i = 0; i < 4; i++) ldsm4(vt[i], xa + (i >> 1) * 1024 + (i & 1) * 256);
        bar_sync<NB_S, 256>();
      } else {
        bar_sync<NB_A, 256>();
        if (!isC) {
          if (w < 3) {
            uint32_t q[8], k[4][4];
            ldsm4t(q, qa + 4096); ldsm4t(k[0], xa); ldsm4t(k[1], xa + 256);
            ldsm4t(q + 4, qa + 4096 + 512); ldsm4t(k[2], xa + 512); ldsm4t(k[3], xa + 768);
            float x[4], y[4];
            hmma0(x, k[0][0], k[0][1], k[0][2], k[0][3], q[0], q[1]); hmma0(y, k[1][0], k[1][1], k[1][2], k[1][3], q[2], q[3]);
            hmma(x, k[2][0], k[2][1], k[2][2], k[2][3], q[4], q[5]); hmma(y, k[3][0], k[3][1], k[3][2], k[3][3], q[6], q[7]);
            const uint32_t s0 = pack2(x[0] + y[0], x[1] + y[1]), s1 = pack2(x[2] + y[2], x[3] + y[3]);
            st_async1(d + to1, s0, bars + B_XS + to1);
            st_async1(d + to2, s0, bars + B_XS + to2);
            if (w < 2) { st_async1(d + to1 + 128, s1, bars + B_XS + to1); st_async1(d + to2 + 128, s1, bars + B_XS + to2); sts32(d + 128, s1); }
            sts32(d, s0);
          }
        }
        bar_arrive<NB_S, 256>();
      }
    }
    if (WG == 1) {
      if (!last && elect_one()) load_chunk(sb + R_GA + w * 4096, s + 1, g1, bars + B_FA);
      {
        if (w > 0 && elect_one()) mbar_expect(bars + B_MB + 8 * w, w < 3 ? 3072 : SELF_STAS ? 28 * 256 : isC ? 18 * 256 : 19 * 256);
      }
      fence_async_smem();
      bar_sync<NB_B, 256>();
    }
    TRACE(7);
    WG_FENCE();
#pragma unroll
    for (int k = 0; k < 16; k++) wg_rs32<1>(acc, W[k][0], W[k][1], W[k][2], W[k][3], dsc.tok[16 + k]);
    WG_COMMIT();
    uint32_t wa[3][4];
    const uint32_t oxa = L16 + R_OX;
    if (WG == 0) {
      const uint32_t vma = oxa - (R_OX - R_VM) + w * 512, oa = opaque32(L4 + w * 512 + R_OX);
      TRACE(8);
      mbar_wait(bars + B_XS, par);
      TRACE(9);
      float sv[10];
      {
        uint32_t x[10];
        ldsm4t(x, oxa - (R_OX - R_XS)); ldsm4t(x + 4, oxa - (R_OX - R_XS) + 512); ldsm2t(x + 8, oxa - (R_OX - R_XS) + 1024);
        bar_arrive<NB_B, 256>();
#pragma unroll
        for (int j = 0; j < 5; j++) x[j] = hadd2(x[j], x[j + 5]);
        exp10(sv, x);
      }
      WG_WAIT(0);
      bar_arrive<NB_X, 256>();
      mbar_wait(bars + B_VM, par);
      uint32_t vm[4];
      ldsm4(vm, vma);
      uint32_t pb[5];
#pragma unroll
      for (int j = 0; j < 5; j++) pb[j] = pack2(sv[2 * j], sv[2 * j + 1]);
      TRACE(10);
      float o0[4], o1[4], sm[4];
      const uint32_t ONE = 0x3f803f80u;
      hmma0(o0, vt[0][0], vt[0][1], vt[0][2], vt[0][3], pb[0], pb[1]);
      hmma0(o1, vt[2][0], vt[2][1], vt[2][2], vt[2][3], pb[0], pb[1]);
      hmma0(sm, ONE, ONE, ONE, ONE, pb[0], pb[1]);
      hmma(sm, ONE, ONE, ONE, ONE, pb[2], pb[3]);
      hmma(o0, vt[1][0], vt[1][1], vt[1][2], vt[1][3], pb[2], pb[3]);
      hmma(o1, vt[3][0], vt[3][1], vt[3][2], vt[3][3], pb[2], pb[3]);
      hmma_k8(sm, ONE, ONE, pb[4]);
      hmma_k8(o0, vm[0], vm[1], pb[4]);
      hmma_k8(o1, vm[2], vm[3], pb[4]);
#pragma unroll
      for (int i = 0; i < 3; i++) ldsm4t(wa[i], woa + i * 4096);
      __syncwarp();
      const float i0 = rcp(sm[0]), i1 = rcp(sm[1]);
      sts32(oa, pack2(o0[0] * i0, o0[1] * i1)); sts32(oa + 128, pack2(o0[2] * i0, o0[3] * i1));
      sts32(oa + 256, pack2(o1[0] * i0, o1[1] * i1)); sts32(oa + 384, pack2(o1[2] * i0, o1[3] * i1));
      TRACE(11);
      bar_sync<NB_C, 128>();
    } else {
      if (!isC) {
        constexpr uint64_t dQ = mkdesc(0x400 + R_QK, 128, 1024, 0), dK = mkdesc(0x400 + R_QK + 5120, 128, 1024, 0);
        float sc[16];
        zero_regs<16>(sc);
        WG_FENCE();
#pragma unroll
        for (int k = 0; k < 4; k++) wg_ss32<1>(sc, dK + k * 16, dQ + k * 16);
        WG_COMMIT();
        const uint32_t top = rank == 0 ? to2 : to1, e = L4 + R_P + w * 256;
        WG_WAIT(0);
        bar_sync<NB_X, 256>();
        if (!last && elect_one()) load_chunk(sb + R_GB + w * 4096, s + 1, g2, bars + B_FB);
        reg_fence<16>(sc);
        if (w < 3) {
#pragma unroll
          for (int j = 0; j < 8; j++) {
            if ((j & 1) ? (j > 1 && (w == 0 || (w == 1 && j == 7))) : (j >= 4 || w != 1)) {
              const uint32_t t = pack2(sc[2 * j], sc[2 * j + 1]), o = (j >> 1) * 768 + (j & 1) * 128;
              st_async1(e + top + 3072 + o, t, bars + top + B_TS);
              sts32(e + o, t);
            }
          }
          __syncwarp();
          if (elect_one()) mbar_arrive(bars + B_TS);
        }
      } else {
        WG_WAIT(0);
        bar_sync<NB_X, 256>();
        if (!last && elect_one()) load_chunk(sb + R_GB + w * 4096, s + 1, g2, bars + B_FB);
      }
      TRACE(8);
      mbar_wait(bars + B_FA, 1);
      TRACE(11);
    }
    if (has_wo) {
      float* rslot = SLOT(s);
      uint32_t ob[4][4];
      float c[3][4];
      if (WG == 1) {
#pragma unroll
        for (int i = 0; i < 3; i++) ldsm4t(wa[i], woa + i * 4096);
        bar_sync<NB_D, 256>();
      }
      ldsm4t(ob[0], oxa);
      __syncwarp();
#pragma unroll
      for (int k = 0; k < 8; k++) {
        uint32_t nx[3][4];
        if ((k & 1) == 0 && k < 6) { ldsm4t(ob[(k >> 1) + 1], oxa + ((k >> 1) + 1) * 512); __syncwarp(); }
#pragma unroll
        for (int i = 0; i < 3; i++) {
          const uint32_t* o = ob[k >> 1] + (k & 1) * 2;
          if (k < 7) { ldsm4t(nx[i], woa + i * 4096 + (k + 1) * 512); if (i == 2) __syncwarp(); }
          if (k == 0) hmma0(c[i], wa[i][0], wa[i][1], wa[i][2], wa[i][3], o[0], o[1]);
          else hmma(c[i], wa[i][0], wa[i][1], wa[i][2], wa[i][3], o[0], o[1]);
#pragma unroll
          for (int q = 0; q < 4; q++) if (k < 7) wa[i][q] = nx[i][q];
        }
        if (k == ND_K && WG == 0) bar_arrive<NB_D, 256>();
      }
      const float* cv = &c[0][0];
      uint32_t r[6];
#pragma unroll
      for (int j = 0; j < 6; j++) r[j] = pack2(cv[2 * j], cv[2 * j + 1]);
      asm volatile("{\n.reg .pred p;\nsetp.lt.s32 p, %8, 0;\n@p bra.uni SKIP;\n"
                   "red.relaxed.gpu.global.add.noftz.v4.bf16x2 [%0], {%1, %2, %3, %7};\n"
                   "red.relaxed.gpu.global.add.noftz.v4.bf16x2 [%0+1024], {%4, %5, %6, %7};\nSKIP:\n}"
                   :: "l"(rslot), "r"(r[0]), "r"(r[1]), "r"(r[2]), "r"(r[3]), "r"(r[4]), "r"(r[5]), "r"(0x3f800000), "r"(s) : "memory");
    } else {
      bar_arrive<NB_D, 256>();
      if ((s & 3) == 0) {
        fence_gpu();
        if (s > 0 && elect_one()) red_add_u32(&g_flags[FL_ATT + 2 * (s - 4)], 1);
      }
      if (PFD && head < 8 && (PFD > 90 || s + PFD < NSEG) && elect_one())
        asm volatile("cp.async.bulk.prefetch.L2.global [%0], 4096;" :: "l"(g_h + (size_t)((PFD > 90 ? 0 : s + PFD) * 16 + head * 2 + rank) * 4096) : "memory");
      if (rank == 0 || head < 16)
        reinterpret_cast<uint4*>(g_slot)[((s + CLR_D) & 3) * 3072 + ((s + CLR_D) & 4) * 8 + rank * 2048 + head * 64 + opaque32(lane)] = make_uint4(0, 0, 0, 0);
    }
    const uint32_t t_red = clk32();
    uint32_t v[8];
    const float* slot = SLOT(s);
    TRACE(13);
    if (WG == 0) {
      if (!isC) {
        const int ln = opaque32(lane), kg = w - (ln >> 3);
        const uint32_t r16 = sb + R_P + w * 768 + (ln & 7) * 16;
        const uint32_t ta = r16 + (kg >= 0 ? kg * 128 : 640);
        const int dg = (ln >> 2) - 2 * (ln & 3);
        const uint32_t keep = dg > 0 ? 0xffffffffu : dg == 0 ? 0x0000ffffu : 0u;
        mbar_wait(bars + B_TS, par);
        uint32_t x[6], y[4];
        ldsm4t(x, ta); ldsm4t(y, ta + 3072); ldsm2t(x + 4, r16 + 512 + ((ln >> 3) & 1) * 3072);
#pragma unroll
        for (int j = 0; j < 5; j++) x[j] = hadd2(x[j], j < 4 ? y[j] : x[5]);
        x[0] = (x[0] & keep) | (0xff80ff80u & ~keep);
        float sv[10];
        exp10(sv, x);
        float sum = (((sv[0] + sv[1]) + (sv[2] + sv[3])) + ((sv[4] + sv[5]) + (sv[6] + sv[7]))) + (sv[8] + sv[9]);
        sum += __shfl_xor_sync(0xffffffffu, sum, 1);
        sum += __shfl_xor_sync(0xffffffffu, sum, 2);
        const float inv = rcp(sum);
#pragma unroll
        for (int j = 0; j < 5; j++) x[j] = pack2(sv[2 * j] * inv, sv[2 * j + 1] * inv);
        stsm4(r16 + (kg & 3) * 128, x);
        sts32(sb + ln * 4 + w * 768 + R_P + 512, x[4]);
        fence_async_smem();
        bar_arrive<NB_P, 256>();
      }
      while (clk32() - t_red < POLL_DELAY) {}
      load_red(v, slot);
      bar_sync<NB_E, 256>();
    } else {
      mbar_wait(bars + B_FB, 1);
    }
    TRACE(14);
    float ao[16];
    if (WG == 1) zero_regs<16>(ao);
    WG_FENCE();
#pragma unroll
    for (int k = 0; k < 32; k++) {
      if (WG == 0 && k == 16) WG_COMMIT();
      wg_rs32<1>(acc, W[16 + k][0], W[16 + k][1], W[16 + k][2], W[16 + k][3], dsc.tok[k]);
    }
    WG_COMMIT();
    TRACE(12);
    if (WG == 1) {
      if (!isC) {
        constexpr uint64_t dP = mkdesc(0x400 + R_P, 128, 768, 0);
        const uint64_t dV = mkdesc(0x400 + R_VT, 128, 512, 0) + rank * 256, dM = mkdesc(0x400 + R_VM, 0, 128, 0) + rank * 64;
        bar_sync<NB_P, 256>();
        WG_FENCE();
        wg_ss32<0>(ao, dV, dP); wg_ss32<0>(ao, dV + 16, dP + 16); wg_ss32<0>(ao, dM, dP + 32);
        WG_COMMIT();
      }
      bar_arrive<NB_E, 256>();
      if (elect_one()) mbar_expect(bars + B_XS + 8 * w, arm_bytes);
      while (clk32() - t_red < POLL_DELAY1) {}
      load_red(v, slot);
      bar_arrive<NB_W0, 128>();
    } else {
      WG_WAIT(1);
      bar_arrive<NB_F, 256>();
      sched_fence(head, 100);
      v[3] = opaque32(v[3]);
      const uint32_t tries = finish_red(v, slot);
      forward(std::integral_constant<int, 0>(), v, s, tries);
      TRACE(16);
    }
    WG_WAIT(0);
    reg_fence<16>(acc);
    if (WG == 0) bar_arrive<NB_G, 256>();
    TRACE(15);
    {
      uint32_t pq[8];
#pragma unroll
      for (int j = 0; j < 8; j++) pq[j] = pack2(acc[2 * j], acc[2 * j + 1]);
      if (WG == 1) {
        reg_fence<16>(ao);
#pragma unroll
        for (int j = 0; j < 8; j++) pk[j] = pack2(ao[2 * j], ao[2 * j + 1]);
      }
      if (!isC) {
        const uint32_t q = L4 + w * 256 + R_QK + WG * 5120;
#pragma unroll
        for (int j = 0; j < 8; j++) sts32(q + (j >> 1) * 1024 + (j & 1) * 128, pq[j]);
        if (WG == 1 && !ATT_LATE && s >= 0) store_att(s);
      } else {
        const uint32_t a = LV + warp * 1024;
        stsm4(a, pq); stsm4(a + 256, pq + 4);
      }
    }
    TRACE(17);
    if (WG == 1) {
      auto refill = [&]() {
        bar_sync<NB_F, 256>();
        if (s < NSEG - 2 && elect_one()) load_chunk(sb + R_GA + w * 4096, s + 2, 12 + w, bars + B_FA);
      };
      if (RF_FIRST) refill();
      if (has_wo) { v[3] = opaque32(v[3]); const uint32_t tries = finish_red(v, slot); forward(std::integral_constant<int, 1>(), v, s, tries); }
      if (!RF_FIRST) refill();
      TRACE(16);
    }
    if (isC && V_FENCE) { fence_async_smem(); __syncwarp(); }
    TRACE(18);
  }
  {
    constexpr uint32_t par = NSEG & 1;
    if (WG == 1 || isC) {
      float c[NCH][4], m[4];
      uint32_t b[3][6];
      const uint32_t ma = L16, m8 = L8;
#pragma unroll
      for (int i = 0; i < 18; i++) {
        if (i < 16) {
          if (i % 4 == 0) mbar_wait(bars + B_MB + (i / 4) * 8, par ^ 1);
          if (i < 12) { lds128(b[i % 3], ma + R_M1 + i * 768); lds64(b[i % 3] + 4, m8 + R_M1 + 512 + i * 768); }
          else { ldsm4(b[i % 3], ma + R_M2 + 4096 + (i - 12) * 768); ldsm2(b[i % 3] + 4, ma + R_M2 + 4096 + 512 + (i - 12) * 768); }
          if (i == CX_I && isC) send_vt();
          __syncwarp();
        }
        if (i >= 2) {
          const int j = i - 2;
#pragma unroll
          for (int q = 0; q < 3; q++) {
            const uint32_t* f = W[3 * j + q];
            if (3 * j + q < NCH) hmma0(c[3 * j + q], f[0], f[1], f[2], f[3], b[j % 3][2 * q], b[j % 3][2 * q + 1]);
            else hmma(c[(3 * j + q) % NCH], f[0], f[1], f[2], f[3], b[j % 3][2 * q], b[j % 3][2 * q + 1]);
          }
        }
      }
#pragma unroll
      for (int j = 0; j < 4; j++) m[j] = NCH == 3 ? (c[0][j] + c[1][j]) + c[2][j] : (c[0][j] + c[1][j]) + (c[2][j] + c[NCH - 1][j]);
      if (isC) bar_sync<NB_H, 256>();
      WG_FENCE();
#pragma unroll
      for (int k = 0; k < 16; k++) wg_ss8(m, dsc.tail_a[WG * 16 + k], dsc.tail_b[k] + 1024);
      WG_COMMIT();
      const uint32_t a = opaque32(L4 + w * 256 + (isC ? WG * 1024 + R_VM : R_QK + 4096 + WG * 5120));
      WG_WAIT(0);
      reg_fence<4>(m);
      const uint32_t p0 = pack2(m[0], m[1]), p1 = pack2(m[2], m[3]);
      if (isC) {
        st_async1(a + to1, p0, bars + B_VM + to1); st_async1(a + to1 + 128, p1, bars + B_VM + to1);
        st_async1(a + to2, p0, bars + B_VM + to2); st_async1(a + to2 + 128, p1, bars + B_VM + to2);
      } else {
        sts32(a, p0); sts32(a + 128, p1);
      }
    }
    if (WG == 1) bar_sync<NB_G, 256>();
    if (isC) {
      asm volatile("barrier.cluster.arrive.relaxed.aligned;" ::: "memory");
    } else if (WG == 1) {
      constexpr uint64_t dQ = mkdesc(0x400 + R_QK, 128, 1024, 0), dK = mkdesc(0x400 + R_QK + 5120, 128, 1024, 0);
      float sc[16];
      zero_regs<16>(sc);
      fence_async_smem();
      bar_sync<NB_B, 256>();
      WG_FENCE();
#pragma unroll
      for (int k = 0; k < 4; k++) wg_ss32<1>(sc, dK + k * 16, dQ + k * 16);
      WG_COMMIT();
      const uint32_t top = rank == 0 ? to2 : to1, e = L4 + R_P + w * 256;
      WG_WAIT(0);
      reg_fence<16>(sc);
      if (w < 3) {
#pragma unroll
        for (int j = 0; j < 8; j++) {
          if ((j & 1) ? (j > 1 && (w == 0 || (w == 1 && j == 7))) : (j >= 4 || w != 1)) {
            const uint32_t t = pack2(sc[2 * j], sc[2 * j + 1]), o = (j >> 1) * 768 + (j & 1) * 128;
            st_async1(e + top + 3072 + o, t, bars + top + B_TS);
            sts32(e + o, t);
          }
        }
        __syncwarp();
        if (elect_one()) mbar_arrive(bars + B_TS);
      }
      constexpr uint64_t dP = mkdesc(0x400 + R_P, 128, 768, 0);
      const uint64_t dV = mkdesc(0x400 + R_VT, 128, 512, 0) + rank * 256, dM = mkdesc(0x400 + R_VM, 0, 128, 0) + rank * 64;
      float ao[16];
      zero_regs<16>(ao);
      mbar_wait(bars + B_VT, par);
      mbar_wait(bars + B_VM, par);
      asm volatile("barrier.cluster.arrive.relaxed.aligned;" ::: "memory");
      bar_sync<NB_P, 256>();
      WG_FENCE();
      wg_ss32<0>(ao, dV, dP); wg_ss32<0>(ao, dV + 16, dP + 16); wg_ss32<0>(ao, dM, dP + 32);
      WG_COMMIT();
      WG_WAIT(0);
      reg_fence<16>(ao);
#pragma unroll
      for (int j = 0; j < 8; j++) pk[j] = pack2(ao[2 * j], ao[2 * j + 1]);
      store_att(NSEG - 1);
      bar_sync<NB_C, 128>();
      if (w == 0 && elect_one()) { fence_gpu(); red_add_u32(&g_flags[FL_ATT + 8 * 15], 1); }
    } else {
      fence_async_smem();
      bar_arrive<NB_B, 256>();
      const int ln = opaque32(lane), kg = w - (ln >> 3);
      const uint32_t r16 = sb + R_P + w * 768 + (ln & 7) * 16;
      const uint32_t ta = r16 + (kg >= 0 ? kg * 128 : 640);
      const int dg = (ln >> 2) - 2 * (ln & 3);
      const uint32_t keep = dg > 0 ? 0xffffffffu : dg == 0 ? 0x0000ffffu : 0u;
      mbar_wait(bars + B_TS, par);
      asm volatile("barrier.cluster.arrive.relaxed.aligned;" ::: "memory");
      uint32_t x[6], y[4];
      ldsm4t(x, ta); ldsm4t(y, ta + 3072); ldsm2t(x + 4, r16 + 512 + ((ln >> 3) & 1) * 3072);
#pragma unroll
      for (int j = 0; j < 5; j++) x[j] = hadd2(x[j], j < 4 ? y[j] : x[5]);
      x[0] = (x[0] & keep) | (0xff80ff80u & ~keep);
      float sv[10];
      exp10(sv, x);
      float sum = (((sv[0] + sv[1]) + (sv[2] + sv[3])) + ((sv[4] + sv[5]) + (sv[6] + sv[7]))) + (sv[8] + sv[9]);
      sum += __shfl_xor_sync(0xffffffffu, sum, 1);
      sum += __shfl_xor_sync(0xffffffffu, sum, 2);
      const float inv = rcp(sum);
#pragma unroll
      for (int j = 0; j < 5; j++) x[j] = pack2(sv[2 * j] * inv, sv[2 * j + 1] * inv);
      stsm4(r16 + (kg & 3) * 128, x);
      sts32(sb + ln * 4 + w * 768 + R_P + 512, x[4]);
      fence_async_smem();
      bar_arrive<NB_P, 256>();
    }
    asm volatile("barrier.cluster.wait.aligned;" ::: "memory");
  }
#undef L16
#undef L8
#undef L4
#undef SLOT
#undef LV
}

__global__ void __cluster_dims__(3, 1, 1) __launch_bounds__(256, 1)
kernel_R(const __grid_constant__ CUtensorMap tmq, const __grid_constant__ CUtensorMap tmk, const __grid_constant__ CUtensorMap tmv,
         const __grid_constant__ CUtensorMap tmo, const __grid_constant__ CUtensorMap tmm, const __nv_bfloat16* __restrict__ x,
         const __nv_bfloat16* __restrict__ mem0, const __nv_bfloat16* __restrict__ cvec, const __grid_constant__ RDesc dsc) {
  extern __shared__ __align__(1024) uint8_t smem[];
  const uint32_t sb = smem_u32(smem);
  uint32_t rank; asm("mov.u32 %0, %%cluster_ctarank;" : "=r"(rank));
  rank = __shfl_sync(0xffffffffu, rank, 0);
  const int cta = blockIdx.x, head = __shfl_sync(0xffffffffu, cta / 3, 0);
  const int tid = threadIdx.x, lane = tid & 31;
  const int warp = __shfl_sync(0xffffffffu, tid >> 5, 0);
  const int wg = warp >> 2, w = warp & 3;
  const uint32_t bars = sb + R_BAR;
  const CUtensorMap* tmw = rank == 2 ? &tmv : (wg == 0 ? &tmq : &tmk);
  const int fcol = head * 128 + (rank == 2 ? wg * 64 : (int)rank * 64);

  asm volatile("griddepcontrol.launch_dependents;");
  uint32_t W[48][4];
  {
    if (sb != (rank << 24) + 0x400) __trap();
    if (tid == 0) {
      sts64(bars + 248, rank, head);
      mbar_init(bars + B_MB, 4); mbar_init(bars + B_MB + 8, 1); mbar_init(bars + B_MB + 16, 1); mbar_init(bars + B_MB + 24, SELF_STAS ? 1 : rank == 2 ? 5 : 4);
      for (int i = B_XS; i <= B_X; i += 8) mbar_init(bars + i, i == B_FA || i == B_FB || (i == B_TS && rank < 2) ? 4 : 1);
      asm volatile("fence.mbarrier_init.release.cluster;" ::: "memory");
      fence_async_smem();
    }
    __syncthreads();
    asm volatile("barrier.cluster.arrive.relaxed.aligned;" ::: "memory");
    TS(0);
    const int nwm = rank == 0 ? 6 : 5, wm0 = rank == 0 ? 0 : 5 * rank + 1, nrg = cta < 64 ? 3 : 2;
    if (elect_one()) {
      if (warp == 0) { mbar_expect(bars + B_WM, nwm * 8192); mbar_expect(bars + B_X, nrg * 16384); }
      if (warp < nwm) tma2d_once(sb + R_GA + warp * 8192, &tmm, head * 64, (wm0 + warp) * 64, bars + B_WM);
#pragma unroll 1
      for (int r = 0; r < nrg; r++) bulk_g2s(sb + R_TAIL + (r * 8 + warp) * 2064, x + (size_t)((cta + 96 * r) * 8 + warp) * D_, 2048, bars + B_X);
      if (w == 0) mbar_expect(bars + B_STG + wg * 16, 49152);
      if (w < 2) tma2d_once(sb + R_WO + wg * 49152 + w * 8192, tmw, fcol, rot_chunk(w, rank) * 64, bars + B_STG + wg * 16);
    }
    float* scr = reinterpret_cast<float*>(smem + R_VT);
#pragma unroll 1
    for (int i = tid; i < nwm * 64; i += 256) {
      const float c = __bfloat162float(cvec[wm0 * 64 + i]);
      scr[i] = __bfloat162float(__float2bfloat16(c / (1.f + __expf(-c))));
    }
    if (tid < 128) {
      uint32_t e[4] = {0u, 0u, 0u, 0u};
      if (cta >= 72 && (tid & 32)) {
        const uint16_t* mp = reinterpret_cast<const uint16_t*>(mem0) + 2 * (lane & 3) * D_ + (lane >> 2);
#pragma unroll
        for (int q = 0; q < 3; q++) {
          const int n = 3 * (tid >> 6) + q, col = wo_tile(3 * (cta & 7) + (n >> 1), (cta - 72) >> 3) * 16 + 8 * (n & 1);
          e[q] = mp[col] | (uint32_t)mp[col + D_] << 16;
        }
        e[3] = 0x42000000u;
      }
      reinterpret_cast<uint4*>(g_slot)[cta * 128 + tid] = make_uint4(e[0], e[1], e[2], e[3]);
    }
    __syncthreads();
    TS(1);
    mbar_wait_safe(bars + B_WM, 0);
    if (elect_one()) tma2d_once(sb + R_WO + wg * 49152 + (2 + w) * 8192, tmw, fcol, rot_chunk(2 + w, rank) * 64, bars + B_STG + wg * 16);
    {
      float a[8];
#pragma unroll
      for (int j = 0; j < 8; j++) a[j] = 0.f;
#pragma unroll 2
      for (int i = 0; i < 2 * nwm; i++) {
        uint32_t u[4];
        lds128(u, sb + R_GA + i * 4096 + tid * 16);
        const float sc = scr[i * 32 + (tid >> 3)];
#pragma unroll
        for (int j = 0; j < 4; j++) { a[2 * j] += sc * bf_lo(u[j]); a[2 * j + 1] += sc * bf_hi(u[j]); }
      }
#pragma unroll
      for (int j = 0; j < 8; j++) { a[j] += __shfl_xor_sync(0xffffffffu, a[j], 8); a[j] += __shfl_xor_sync(0xffffffffu, a[j], 16); }
      if (lane < 8) {
        sts128(sb + R_VT + 1536 + warp * 256 + lane * 32, __float_as_uint(a[0]), __float_as_uint(a[1]), __float_as_uint(a[2]), __float_as_uint(a[3]));
        sts128(sb + R_VT + 1552 + warp * 256 + lane * 32, __float_as_uint(a[4]), __float_as_uint(a[5]), __float_as_uint(a[6]), __float_as_uint(a[7]));
      }
    }
    __syncthreads();
    TS(2);
    if (warp == 7) {
      float t0 = 0.f, t1 = 0.f;
#pragma unroll
      for (int i = 0; i < 8; i++) { float t[2]; lds64f(t, sb + R_VT + 1536 + i * 256 + lane * 8); t0 += t[0]; t1 += t[1]; }
      reinterpret_cast<float2*>(g_modp + rank * 2048 + head * 64)[lane] = make_float2(t0, t1);
      fence_gpu();
      __syncwarp();
      if (lane == 0) red_add_u32(&g_flags[FL_S1], 1);
      __syncwarp();
    }
    mbar_wait_safe(bars + B_X, 0);
#pragma unroll 1
    for (int r = 0; r < nrg; r++) {
      float f[32];
#pragma unroll
      for (int i = 0; i < 4; i++) {
        uint32_t u[4];
        lds128(u, sb + R_TAIL + (r * 8 + warp) * 2064 + i * 512 + lane * 16);
#pragma unroll
        for (int j = 0; j < 4; j++) { f[8 * i + 2 * j] = bf_lo(u[j]); f[8 * i + 2 * j + 1] = bf_hi(u[j]); }
      }
      float t = 0.f;
#pragma unroll
      for (int i = 0; i < 32; i++) t += f[i];
#pragma unroll
      for (int o = 1; o < 32; o <<= 1) t += __shfl_xor_sync(0xffffffffu, t, o);
      const float mean = t * (1.f / D_);
      t = 0.f;
#pragma unroll
      for (int i = 0; i < 32; i++) t = fmaf(f[i] - mean, f[i] - mean, t);
#pragma unroll
      for (int o = 1; o < 32; o <<= 1) t += __shfl_xor_sync(0xffffffffu, t, o);
      const float rstd = rsqrtf(t * (1.f / D_) + 1e-5f);
      if (lane == 0) sts64(sb + R_VT + 3584 + (r * 8 + warp) * 8, __float_as_uint(rstd), __float_as_uint(-mean * rstd));
    }
    TS(3);
    if (w < PF1 && elect_one()) tma2d_prefetch(tmw, fcol, rot_chunk(6 + w, rank) * 64);
    if (tid == 0) wait_flag(&g_flags[FL_S1], 96);
    __syncthreads();
    TS(4);
    {
      float4 p[6];
#pragma unroll
      for (int i = 0; i < 6; i++) p[i] = __ldcg(reinterpret_cast<const float4*>(g_modp + (i >> 1) * 2048) + 2 * tid + (i & 1));
      if (w < PF2 && elect_one()) tma2d_prefetch(tmw, fcol, (9 + w) * 64);
      sts128(sb + R_VT + 5120 + tid * 16, pack2(p[0].x + p[2].x + p[4].x, p[0].y + p[2].y + p[4].y), pack2(p[0].z + p[2].z + p[4].z, p[0].w + p[2].w + p[4].w),
             pack2(p[1].x + p[3].x + p[5].x, p[1].y + p[3].y + p[5].y), pack2(p[1].z + p[3].z + p[5].z, p[1].w + p[3].w + p[5].w));
    }
    __syncthreads();
#pragma unroll 2
    for (int it = 0; it < 4 * nrg; it++) {
      const int r = it >> 2, rg = cta + 96 * r, c = 16 * warp + (lane >> 3) + 4 * (it & 3);
      uint32_t a[4], b[4], u[4], o[4];
      float t[2];
      lds128(u, sb + R_TAIL + (r * 8 + (lane & 7)) * 2064 + c * 16);
      lds128(a, sb + R_VT + 5120 + c * 16); lds128(b, sb + R_VT + 7168 + c * 16);
      lds64f(t, sb + R_VT + 3584 + (r * 8 + (lane & 7)) * 8);
#pragma unroll
      for (int j = 0; j < 4; j++)
        o[j] = pack2(fmaf(fmaf(bf_lo(u[j]), t[0], t[1]), 1.f + bf_lo(b[j]), bf_lo(a[j])), fmaf(fmaf(bf_hi(u[j]), t[0], t[1]), 1.f + bf_hi(b[j]), bf_hi(a[j])));
      *reinterpret_cast<uint4*>(g_h + (size_t)(rg >> 2) * 65536 + (lane & 7) * 16 + (c & 7) * 128 +
                                (c < 96 ? (c >> 3) * 4096 + (rg & 3) * 1024 : 49152 + (rg & 3) * 4096 + ((c >> 3) - 12) * 1024)) =
          make_uint4(o[0], o[1], o[2], o[3]);
    }
    TS(5);
    __syncthreads();
    TS(6);
    if (w < PF3 && elect_one()) tma2d_once(sb + R_TAIL + warp * 8192, tmw, fcol, 768 + w * 64, bars + B_TAIL);
    if (warp == 3 && lane == 0) { fence_gpu(); red_add_u32(&g_flags[FL_S2], 1); }
    __syncwarp();

    const uint32_t a0 = opaque32(sb + R_WO + wg * 49152 + ((lane >> 4) * 8 + (lane & 7)) * 128 + (((2 * w + ((lane >> 3) & 1)) ^ (lane & 7)) << 4));
    mbar_wait_safe(bars + B_STG + wg * 16, 0);
    TS(7);
#pragma unroll
    for (int i = 0; i < 24; i++) ldsm4t(W[i], a0 + i * 2048);
    if (tid == 0) wait_flag(&g_flags[FL_S2], 96);
    __syncthreads();
    asm volatile("fence.proxy.async.global;" ::: "memory");
    if (elect_one()) {
      if (wg == 0) load_chunk(sb + R_GA + w * 4096, 0, 12 + w, bars + B_FA);
      if (w == 0) mbar_expect(bars + B_STG + wg * 16 + 8, 49152);
#pragma unroll 1
      for (int c = w; c < 6; c += 4) tma2d_once(sb + R_WO + wg * 49152 + c * 8192, tmw, fcol, rot_chunk(6 + c, rank) * 64, bars + B_STG + wg * 16 + 8);
      if (warp == 0) mbar_expect(bars + B_TAIL, 65536);
      if (w >= PF3) tma2d_once(sb + R_TAIL + warp * 8192, tmw, fcol, 768 + w * 64, bars + B_TAIL);
      if (wg == 1) mbar_expect(bars + B_XS + 8 * w, w == 2 ? 0 : arm_size(w, rank == 2));
#pragma unroll 1
      for (int i = warp; i < PF4; i += 8) tma2d_prefetch(&tmo, 16 * wo_tile(i, rank), head * 128);
    }
    TS(8);
    mbar_wait_safe(bars + B_STG + wg * 16 + 8, 0);
    TS(9);
#pragma unroll
    for (int i = 0; i < 24; i++) ldsm4t(W[24 + i], a0 + i * 2048);
    __syncthreads();
    if (elect_one()) {
      const int n = rank == 2 ? 22 : 21;
      if (warp == 0) mbar_expect(bars + B_WO, n * 4096);
#pragma unroll 1
      for (int i = warp; i < n; i += 8) tma2d(sb + R_WO + i * 4096, &tmo, 16 * wo_tile(i, rank), head * 128, bars + B_WO);
    }
    sts32(sb + R_P + warp * 768 + 640 + lane * 4, wg == 0 ? 0u : 0xff80ff80u);
    mbar_wait_safe(bars + B_TAIL, 0);
    if (GO_EARLY && cta == GO_EARLY - 1 && tid == 0) red_add_u32(&g_flags[FL_GO], 1);
    asm volatile("barrier.cluster.wait.aligned;\nbarrier.cluster.arrive.relaxed.aligned;\nbarrier.cluster.wait.aligned;" ::: "memory");
  }
  uint32_t rh[2];
  lds64(rh, bars + 248);
  rh[0] = __shfl_sync(0xffffffffu, rh[0], 0); rh[1] = __shfl_sync(0xffffffffu, rh[1], 0);
  if (wg == 0) r_main<0>(W, dsc, rh[1], rh[0], lane, w);
  else r_main<1>(W, dsc, rh[1], rh[0], lane, w);
}

template <int TA, bool FIRST> __device__ __forceinline__ void wg_ss256(float* d, uint64_t a, uint64_t b) {
  if (FIRST)
    asm volatile("wgmma.mma_async.sync.aligned.m64n256k16.f32.bf16.bf16 {%0,%1,%2,%3,%4,%5,%6,%7,%8,%9,%10,%11,%12,%13,%14,%15,%16,%17,%18,%19,%20,%21,%22,%23,%24,%25,%26,%27,%28,%29,%30,%31,%32,%33,%34,%35,%36,%37,%38,%39,%40,%41,%42,%43,%44,%45,%46,%47,%48,%49,%50,%51,%52,%53,%54,%55,%56,%57,%58,%59,%60,%61,%62,%63,%64,%65,%66,%67,%68,%69,%70,%71,%72,%73,%74,%75,%76,%77,%78,%79,%80,%81,%82,%83,%84,%85,%86,%87,%88,%89,%90,%91,%92,%93,%94,%95,%96,%97,%98,%99,%100,%101,%102,%103,%104,%105,%106,%107,%108,%109,%110,%111,%112,%113,%114,%115,%116,%117,%118,%119,%120,%121,%122,%123,%124,%125,%126,%127}, %128, %129, 0, 1, 1, %130, 1;"
               : "=f"(d[0]), "=f"(d[1]), "=f"(d[2]), "=f"(d[3]), "=f"(d[4]), "=f"(d[5]), "=f"(d[6]), "=f"(d[7]),
                 "=f"(d[8]), "=f"(d[9]), "=f"(d[10]), "=f"(d[11]), "=f"(d[12]), "=f"(d[13]), "=f"(d[14]), "=f"(d[15]),
                 "=f"(d[16]), "=f"(d[17]), "=f"(d[18]), "=f"(d[19]), "=f"(d[20]), "=f"(d[21]), "=f"(d[22]), "=f"(d[23]),
                 "=f"(d[24]), "=f"(d[25]), "=f"(d[26]), "=f"(d[27]), "=f"(d[28]), "=f"(d[29]), "=f"(d[30]), "=f"(d[31]),
                 "=f"(d[32]), "=f"(d[33]), "=f"(d[34]), "=f"(d[35]), "=f"(d[36]), "=f"(d[37]), "=f"(d[38]), "=f"(d[39]),
                 "=f"(d[40]), "=f"(d[41]), "=f"(d[42]), "=f"(d[43]), "=f"(d[44]), "=f"(d[45]), "=f"(d[46]), "=f"(d[47]),
                 "=f"(d[48]), "=f"(d[49]), "=f"(d[50]), "=f"(d[51]), "=f"(d[52]), "=f"(d[53]), "=f"(d[54]), "=f"(d[55]),
                 "=f"(d[56]), "=f"(d[57]), "=f"(d[58]), "=f"(d[59]), "=f"(d[60]), "=f"(d[61]), "=f"(d[62]), "=f"(d[63]),
                 "=f"(d[64]), "=f"(d[65]), "=f"(d[66]), "=f"(d[67]), "=f"(d[68]), "=f"(d[69]), "=f"(d[70]), "=f"(d[71]),
                 "=f"(d[72]), "=f"(d[73]), "=f"(d[74]), "=f"(d[75]), "=f"(d[76]), "=f"(d[77]), "=f"(d[78]), "=f"(d[79]),
                 "=f"(d[80]), "=f"(d[81]), "=f"(d[82]), "=f"(d[83]), "=f"(d[84]), "=f"(d[85]), "=f"(d[86]), "=f"(d[87]),
                 "=f"(d[88]), "=f"(d[89]), "=f"(d[90]), "=f"(d[91]), "=f"(d[92]), "=f"(d[93]), "=f"(d[94]), "=f"(d[95]),
                 "=f"(d[96]), "=f"(d[97]), "=f"(d[98]), "=f"(d[99]), "=f"(d[100]), "=f"(d[101]), "=f"(d[102]), "=f"(d[103]),
                 "=f"(d[104]), "=f"(d[105]), "=f"(d[106]), "=f"(d[107]), "=f"(d[108]), "=f"(d[109]), "=f"(d[110]), "=f"(d[111]),
                 "=f"(d[112]), "=f"(d[113]), "=f"(d[114]), "=f"(d[115]), "=f"(d[116]), "=f"(d[117]), "=f"(d[118]), "=f"(d[119]),
                 "=f"(d[120]), "=f"(d[121]), "=f"(d[122]), "=f"(d[123]), "=f"(d[124]), "=f"(d[125]), "=f"(d[126]), "=f"(d[127])
               : "l"(a), "l"(b), "n"(TA));
  else
    asm volatile("wgmma.mma_async.sync.aligned.m64n256k16.f32.bf16.bf16 {%0,%1,%2,%3,%4,%5,%6,%7,%8,%9,%10,%11,%12,%13,%14,%15,%16,%17,%18,%19,%20,%21,%22,%23,%24,%25,%26,%27,%28,%29,%30,%31,%32,%33,%34,%35,%36,%37,%38,%39,%40,%41,%42,%43,%44,%45,%46,%47,%48,%49,%50,%51,%52,%53,%54,%55,%56,%57,%58,%59,%60,%61,%62,%63,%64,%65,%66,%67,%68,%69,%70,%71,%72,%73,%74,%75,%76,%77,%78,%79,%80,%81,%82,%83,%84,%85,%86,%87,%88,%89,%90,%91,%92,%93,%94,%95,%96,%97,%98,%99,%100,%101,%102,%103,%104,%105,%106,%107,%108,%109,%110,%111,%112,%113,%114,%115,%116,%117,%118,%119,%120,%121,%122,%123,%124,%125,%126,%127}, %128, %129, 1, 1, 1, %130, 1;"
               : "+f"(d[0]), "+f"(d[1]), "+f"(d[2]), "+f"(d[3]), "+f"(d[4]), "+f"(d[5]), "+f"(d[6]), "+f"(d[7]),
                 "+f"(d[8]), "+f"(d[9]), "+f"(d[10]), "+f"(d[11]), "+f"(d[12]), "+f"(d[13]), "+f"(d[14]), "+f"(d[15]),
                 "+f"(d[16]), "+f"(d[17]), "+f"(d[18]), "+f"(d[19]), "+f"(d[20]), "+f"(d[21]), "+f"(d[22]), "+f"(d[23]),
                 "+f"(d[24]), "+f"(d[25]), "+f"(d[26]), "+f"(d[27]), "+f"(d[28]), "+f"(d[29]), "+f"(d[30]), "+f"(d[31]),
                 "+f"(d[32]), "+f"(d[33]), "+f"(d[34]), "+f"(d[35]), "+f"(d[36]), "+f"(d[37]), "+f"(d[38]), "+f"(d[39]),
                 "+f"(d[40]), "+f"(d[41]), "+f"(d[42]), "+f"(d[43]), "+f"(d[44]), "+f"(d[45]), "+f"(d[46]), "+f"(d[47]),
                 "+f"(d[48]), "+f"(d[49]), "+f"(d[50]), "+f"(d[51]), "+f"(d[52]), "+f"(d[53]), "+f"(d[54]), "+f"(d[55]),
                 "+f"(d[56]), "+f"(d[57]), "+f"(d[58]), "+f"(d[59]), "+f"(d[60]), "+f"(d[61]), "+f"(d[62]), "+f"(d[63]),
                 "+f"(d[64]), "+f"(d[65]), "+f"(d[66]), "+f"(d[67]), "+f"(d[68]), "+f"(d[69]), "+f"(d[70]), "+f"(d[71]),
                 "+f"(d[72]), "+f"(d[73]), "+f"(d[74]), "+f"(d[75]), "+f"(d[76]), "+f"(d[77]), "+f"(d[78]), "+f"(d[79]),
                 "+f"(d[80]), "+f"(d[81]), "+f"(d[82]), "+f"(d[83]), "+f"(d[84]), "+f"(d[85]), "+f"(d[86]), "+f"(d[87]),
                 "+f"(d[88]), "+f"(d[89]), "+f"(d[90]), "+f"(d[91]), "+f"(d[92]), "+f"(d[93]), "+f"(d[94]), "+f"(d[95]),
                 "+f"(d[96]), "+f"(d[97]), "+f"(d[98]), "+f"(d[99]), "+f"(d[100]), "+f"(d[101]), "+f"(d[102]), "+f"(d[103]),
                 "+f"(d[104]), "+f"(d[105]), "+f"(d[106]), "+f"(d[107]), "+f"(d[108]), "+f"(d[109]), "+f"(d[110]), "+f"(d[111]),
                 "+f"(d[112]), "+f"(d[113]), "+f"(d[114]), "+f"(d[115]), "+f"(d[116]), "+f"(d[117]), "+f"(d[118]), "+f"(d[119]),
                 "+f"(d[120]), "+f"(d[121]), "+f"(d[122]), "+f"(d[123]), "+f"(d[124]), "+f"(d[125]), "+f"(d[126]), "+f"(d[127])
               : "l"(a), "l"(b), "n"(TA));
}
template <int TA, bool FIRST> __device__ __forceinline__ void wg_ss128(float* d, uint64_t a, uint64_t b) {
  if (FIRST)
    asm volatile("wgmma.mma_async.sync.aligned.m64n128k16.f32.bf16.bf16 {%0,%1,%2,%3,%4,%5,%6,%7,%8,%9,%10,%11,%12,%13,%14,%15,%16,%17,%18,%19,%20,%21,%22,%23,%24,%25,%26,%27,%28,%29,%30,%31,%32,%33,%34,%35,%36,%37,%38,%39,%40,%41,%42,%43,%44,%45,%46,%47,%48,%49,%50,%51,%52,%53,%54,%55,%56,%57,%58,%59,%60,%61,%62,%63}, %64, %65, 0, 1, 1, %66, 1;"
               : "=f"(d[0]), "=f"(d[1]), "=f"(d[2]), "=f"(d[3]), "=f"(d[4]), "=f"(d[5]), "=f"(d[6]), "=f"(d[7]),
                 "=f"(d[8]), "=f"(d[9]), "=f"(d[10]), "=f"(d[11]), "=f"(d[12]), "=f"(d[13]), "=f"(d[14]), "=f"(d[15]),
                 "=f"(d[16]), "=f"(d[17]), "=f"(d[18]), "=f"(d[19]), "=f"(d[20]), "=f"(d[21]), "=f"(d[22]), "=f"(d[23]),
                 "=f"(d[24]), "=f"(d[25]), "=f"(d[26]), "=f"(d[27]), "=f"(d[28]), "=f"(d[29]), "=f"(d[30]), "=f"(d[31]),
                 "=f"(d[32]), "=f"(d[33]), "=f"(d[34]), "=f"(d[35]), "=f"(d[36]), "=f"(d[37]), "=f"(d[38]), "=f"(d[39]),
                 "=f"(d[40]), "=f"(d[41]), "=f"(d[42]), "=f"(d[43]), "=f"(d[44]), "=f"(d[45]), "=f"(d[46]), "=f"(d[47]),
                 "=f"(d[48]), "=f"(d[49]), "=f"(d[50]), "=f"(d[51]), "=f"(d[52]), "=f"(d[53]), "=f"(d[54]), "=f"(d[55]),
                 "=f"(d[56]), "=f"(d[57]), "=f"(d[58]), "=f"(d[59]), "=f"(d[60]), "=f"(d[61]), "=f"(d[62]), "=f"(d[63])
               : "l"(a), "l"(b), "n"(TA));
  else
    asm volatile("wgmma.mma_async.sync.aligned.m64n128k16.f32.bf16.bf16 {%0,%1,%2,%3,%4,%5,%6,%7,%8,%9,%10,%11,%12,%13,%14,%15,%16,%17,%18,%19,%20,%21,%22,%23,%24,%25,%26,%27,%28,%29,%30,%31,%32,%33,%34,%35,%36,%37,%38,%39,%40,%41,%42,%43,%44,%45,%46,%47,%48,%49,%50,%51,%52,%53,%54,%55,%56,%57,%58,%59,%60,%61,%62,%63}, %64, %65, 1, 1, 1, %66, 1;"
               : "+f"(d[0]), "+f"(d[1]), "+f"(d[2]), "+f"(d[3]), "+f"(d[4]), "+f"(d[5]), "+f"(d[6]), "+f"(d[7]),
                 "+f"(d[8]), "+f"(d[9]), "+f"(d[10]), "+f"(d[11]), "+f"(d[12]), "+f"(d[13]), "+f"(d[14]), "+f"(d[15]),
                 "+f"(d[16]), "+f"(d[17]), "+f"(d[18]), "+f"(d[19]), "+f"(d[20]), "+f"(d[21]), "+f"(d[22]), "+f"(d[23]),
                 "+f"(d[24]), "+f"(d[25]), "+f"(d[26]), "+f"(d[27]), "+f"(d[28]), "+f"(d[29]), "+f"(d[30]), "+f"(d[31]),
                 "+f"(d[32]), "+f"(d[33]), "+f"(d[34]), "+f"(d[35]), "+f"(d[36]), "+f"(d[37]), "+f"(d[38]), "+f"(d[39]),
                 "+f"(d[40]), "+f"(d[41]), "+f"(d[42]), "+f"(d[43]), "+f"(d[44]), "+f"(d[45]), "+f"(d[46]), "+f"(d[47]),
                 "+f"(d[48]), "+f"(d[49]), "+f"(d[50]), "+f"(d[51]), "+f"(d[52]), "+f"(d[53]), "+f"(d[54]), "+f"(d[55]),
                 "+f"(d[56]), "+f"(d[57]), "+f"(d[58]), "+f"(d[59]), "+f"(d[60]), "+f"(d[61]), "+f"(d[62]), "+f"(d[63])
               : "l"(a), "l"(b), "n"(TA));
}
template <int TA, bool FIRST> __device__ __forceinline__ void wg_ss64(float* d, uint64_t a, uint64_t b) {
  if (FIRST)
    asm volatile("wgmma.mma_async.sync.aligned.m64n64k16.f32.bf16.bf16 {%0,%1,%2,%3,%4,%5,%6,%7,%8,%9,%10,%11,%12,%13,%14,%15,%16,%17,%18,%19,%20,%21,%22,%23,%24,%25,%26,%27,%28,%29,%30,%31}, %32, %33, 0, 1, 1, %34, 1;"
               : "=f"(d[0]), "=f"(d[1]), "=f"(d[2]), "=f"(d[3]), "=f"(d[4]), "=f"(d[5]), "=f"(d[6]), "=f"(d[7]),
                 "=f"(d[8]), "=f"(d[9]), "=f"(d[10]), "=f"(d[11]), "=f"(d[12]), "=f"(d[13]), "=f"(d[14]), "=f"(d[15]),
                 "=f"(d[16]), "=f"(d[17]), "=f"(d[18]), "=f"(d[19]), "=f"(d[20]), "=f"(d[21]), "=f"(d[22]), "=f"(d[23]),
                 "=f"(d[24]), "=f"(d[25]), "=f"(d[26]), "=f"(d[27]), "=f"(d[28]), "=f"(d[29]), "=f"(d[30]), "=f"(d[31])
               : "l"(a), "l"(b), "n"(TA));
  else
    asm volatile("wgmma.mma_async.sync.aligned.m64n64k16.f32.bf16.bf16 {%0,%1,%2,%3,%4,%5,%6,%7,%8,%9,%10,%11,%12,%13,%14,%15,%16,%17,%18,%19,%20,%21,%22,%23,%24,%25,%26,%27,%28,%29,%30,%31}, %32, %33, 1, 1, 1, %34, 1;"
               : "+f"(d[0]), "+f"(d[1]), "+f"(d[2]), "+f"(d[3]), "+f"(d[4]), "+f"(d[5]), "+f"(d[6]), "+f"(d[7]),
                 "+f"(d[8]), "+f"(d[9]), "+f"(d[10]), "+f"(d[11]), "+f"(d[12]), "+f"(d[13]), "+f"(d[14]), "+f"(d[15]),
                 "+f"(d[16]), "+f"(d[17]), "+f"(d[18]), "+f"(d[19]), "+f"(d[20]), "+f"(d[21]), "+f"(d[22]), "+f"(d[23]),
                 "+f"(d[24]), "+f"(d[25]), "+f"(d[26]), "+f"(d[27]), "+f"(d[28]), "+f"(d[29]), "+f"(d[30]), "+f"(d[31])
               : "l"(a), "l"(b), "n"(TA));
}

constexpr int H_STAGE = 49152, H_NST = 4;
constexpr int H_STG = H_NST * H_STAGE;
constexpr int H_VEC = H_STG + 16384;
constexpr int H_BAR = H_VEC + 6144;
constexpr int H_SMEM = H_BAR + 256;
constexpr int HB_FULL = 0, HB_EMPTY = 32, HB_IFULL = 64, HB_IEMPTY = 80, HB_ITEM = 96, HB_INC = 104, HB_HAVE = 116, HB_NEXT = 160;
enum { IT_END = 0, IT_MOD = 1, IT_XT = 2, IT_OUT = 3, IT_UV = 4, IT_F1 = 5, IT_F2 = 6 };
constexpr int MAX_ITEMS = 1400;
#define D_MOD 4
#define D_UV 2
#define UV_WAIT 0
#define PF_MAPS 1
#define R_LATE 1
#define CH_FENCE 1
#define CH_FENCE1 1
#define N_UV1 20
#define FINE 1
#define B_EARLY 1
#define VEC_EARLY 1
#define HOLD 1
#define PEEK 4
#define ECL0 2
#define ECL1 6
constexpr uint32_t IT_GATHER = 0x80000000u;
__host__ __device__ __forceinline__ int split_tile(int type, int mt, int idx) { return ((type == IT_F2 ? 0 : mt >= 12 ? 4 : 8) + (mt & 3)) * 16 + idx; }
__device__ __forceinline__ int item_sz(uint32_t it) { return (it >> 13) & 3; }
struct HList { uint32_t n; uint32_t it[MAX_ITEMS]; };
__device__ __forceinline__ void item_deps(int type, int mt, int lane, int& f, uint32_t& target) {
  f = FL_GO; target = 1;
  if (type == IT_OUT) { f = lane == 0 ? FL_ATT + 8 * mt : lane == 1 ? FL_XT + 8 * mt : lane == 9 ? FL_MODA : FL_MOD; target = lane == 0 ? 64 : lane == 1 ? 2 : lane == 9 ? 8 : 16; }
  else if (type == IT_F1) { f = lane < 8 ? FL_OUT + 8 * mt + lane : FL_UV; target = lane < 8 ? 2 : 28; }
  else if (type == IT_F2) { f = lane < 8 ? FL_F1 + 8 * mt + lane : FL_MODB; target = 8; }
}
#define HT(i)

__device__ __forceinline__ uint32_t tile_lane(int warp, int lane) { return warp * 1024 + (lane >> 2) * 64 + (((lane & 3) ^ (lane >> 3)) << 4); }
__device__ __forceinline__ constexpr uint32_t tile_off(int c, int h) { return (c >> 1) * 16384 + (c & 1) * 8192 + h * 512; }

template <int BN, int TA, class PRE, class POST>
__device__ __forceinline__ void h_mainloop(float* acc, uint32_t sb, int nst, uint32_t& st, uint32_t& ph, int wg, bool leader, PRE pre, POST post) {
  constexpr int KS = BN == 64 ? 8 : 4;
  constexpr uint32_t BOFF = BN == 64 ? 32768 : 16384;
  const uint64_t da0 = TA ? mkdesc(sb + wg * 1024, 2048, 128, 0) : mkdesc(sb + wg * 4096, 16, 512, 2);
  auto release = [&](uint32_t s) { if (leader) mbar_arrive(sb + H_BAR + HB_EMPTY + s * 8); };
  const uint64_t db0 = mkdesc(sb + BOFF, 8192, 1024, 1);
  constexpr uint32_t kh = 512;
  uint32_t prev = 0;
  auto stage = [&](auto first) {
    constexpr bool FIRST = decltype(first)::value;
    mbar_wait(sb + H_BAR + HB_FULL + st * 8, ph);
    if (FIRST) HT(1);
    const uint64_t da = da0 + st * (H_STAGE >> 4), db = db0 + st * (H_STAGE >> 4);
    WG_FENCE();
#pragma unroll
    for (int k = 0; k < KS; k++) {
      const uint64_t a = da + (k >> 2) * 1024 + (TA ? (k & 3) * 256 : ((k >> 1) & 1) * kh + (k & 1) * 2), b = db + k * 128;
      if (FIRST && k == 0) { if (BN == 256) wg_ss256<TA, true>(acc, a, b); else if (BN == 128) wg_ss128<TA, true>(acc, a, b); else wg_ss64<TA, true>(acc, a, b); }
      else { if (BN == 256) wg_ss256<TA, false>(acc, a, b); else if (BN == 128) wg_ss128<TA, false>(acc, a, b); else wg_ss64<TA, false>(acc, a, b); }
    }
    WG_COMMIT();
  };
  stage(std::true_type());
  pre();
  prev = st;
  if (++st == H_NST) { st = 0; ph ^= 1; }
#pragma unroll 1
  for (int i = 1; i < nst; i++) {
    stage(std::false_type());
    WG_WAIT(1);
    release(prev);
    prev = st;
    if (++st == H_NST) { st = 0; ph ^= 1; }
  }
  post();
  WG_WAIT(0);
  HT(2);
  reg_fence<BN / 2>(acc);
  release(prev);
}

template <int BN, bool FINAL, class POST>
__device__ __forceinline__ void h_residual(uint32_t sb, uint32_t va, int mt, int n0, uint32_t& st, uint32_t& ph, int warp, int lane, __nv_bfloat16* out,
                                           POST post, int part = 0, int lgp = 0, bool gather = false) {
  const size_t toff = (size_t)(mt * 16 + (n0 >> 6)) * 16384 + tile_lane(warp, lane);
  uint4 r[BN / 16];
  auto load_r = [&]() {
#pragma unroll
    for (int i = 0; i < BN / 16; i++) r[i] = __ldcg(reinterpret_cast<const uint4*>(g_x1 + toff + tile_off(i >> 1, i & 1)));
  };
  const bool partial = BN == 64 && lgp > 0 && !gather;
  if (!R_LATE && !partial) load_r();
  float acc[BN / 2];
  h_mainloop<BN, FINAL ? 0 : 1>(acc, sb, ((FINAL ? 56 : 64) / (BN == 64 ? 2 : 1)) >> lgp, st, ph, warp >> 2, (warp & 3) == 0 && lane == 0,
                                [&]() { if (R_LATE && !partial) load_r(); }, post);
  if (BN == 64 && lgp > 0) {
    if (partial) {
      float4* ws = reinterpret_cast<float4*>(g_ws) + (size_t)split_tile(FINAL ? IT_F2 : IT_OUT, mt, n0 >> 6) * 8192 + part * 2048 + warp * 32 + lane;
#pragma unroll
      for (int i = 0; i < 8; i++) ws[i * 256] = make_float4(acc[4 * i], acc[4 * i + 1], acc[4 * i + 2], acc[4 * i + 3]);
      return;
    }
#pragma unroll 1
    for (int p = 1; p < (1 << lgp); p++) {
      mbar_wait(sb + H_BAR + HB_FULL + st * 8, ph);
#pragma unroll
      for (int i = 0; i < 8; i++) {
        float o[4];
        lds128f(o, sb + st * H_STAGE + i * 4096 + warp * 512 + lane * 16);
        acc[4 * i] += o[0]; acc[4 * i + 1] += o[1]; acc[4 * i + 2] += o[2]; acc[4 * i + 3] += o[3];
      }
      reg_fence<32>(acc);
      bar_sync<1, 256>();
      if ((warp & 3) == 0 && lane == 0) mbar_arrive(sb + H_BAR + HB_EMPTY + st * 8);
      if (++st == H_NST) { st = 0; ph ^= 1; }
    }
  }
  float sm[4] = {0.f, 0.f, 0.f, 0.f};
  const uint32_t stg = sb + H_STG + warp * 2048;
#pragma unroll
  for (int c = 0; c < BN / 32; c++) {
    uint32_t y[2][4] = {{r[2 * c].x, r[2 * c].y, r[2 * c].z, r[2 * c].w}, {r[2 * c + 1].x, r[2 * c + 1].y, r[2 * c + 1].z, r[2 * c + 1].w}}, z[2][4];
#pragma unroll
    for (int j = 0; j < 4; j++) {
      const uint32_t gt = lds32(va + c * 64 + j * 16 + (lane & 3) * 4);
      const uint32_t cb = FINAL ? 0 : lds32(va + 512 + c * 64 + j * 16 + (lane & 3) * 4);
#pragma unroll
      for (int h = 0; h < 2; h++) {
        const float* a = acc + c * 16 + j * 4 + h * 2;
        y[h][j] = pack2(fmaf(bf_lo(gt), a[0], bf_lo(y[h][j])), fmaf(bf_hi(gt), a[1], bf_hi(y[h][j])));
        if (!FINAL) {
          const float p = bf_lo(y[h][j]), q = bf_hi(y[h][j]);
          sm[2 * h] += p + q;
          sm[2 * h + 1] = fmaf(p, p, fmaf(q, q, sm[2 * h + 1]));
          z[h][j] = pack2(fmaf(p, bf_lo(cb), p), fmaf(q, bf_hi(cb), q));
        }
      }
    }
    if (!FINAL) {
#pragma unroll
      for (int h = 0; h < 2; h++) {
        const size_t o = toff + tile_off(c, h);
        *reinterpret_cast<uint4*>(g_x1 + o) = make_uint4(y[h][0], y[h][1], y[h][2], y[h][3]);
        *reinterpret_cast<uint4*>(g_h2 + o) = make_uint4(z[h][0], z[h][1], z[h][2], z[h][3]);
      }
    } else {
#pragma unroll
      for (int h = 0; h < 2; h++) stsm4(stg + (h * 8 + (lane & 7)) * 128 + ((((c & 1) * 4 + (lane >> 3)) ^ (lane & 7)) << 4), y[h]);
      if (c & 1) {
        __syncwarp();
#pragma unroll
        for (int j = 0; j < 4; j++) {
          const int rr = 4 * j + (lane >> 3);
          uint32_t v[4];
          lds128(v, stg + rr * 128 + (((lane & 7) ^ (rr & 7)) << 4));
          *reinterpret_cast<uint4*>(out + (size_t)(mt * 128 + warp * 16 + rr) * D_ + n0 + (c >> 1) * 64 + (lane & 7) * 8) = make_uint4(v[0], v[1], v[2], v[3]);
        }
        __syncwarp();
      }
    }
    if (CH_FENCE && c + 1 < BN / 32) sched_fence(lane, 100);
  }
  if (!FINAL) {
#pragma unroll
    for (int j = 0; j < 4; j++) { sm[j] += __shfl_xor_sync(0xffffffffu, sm[j], 1); sm[j] += __shfl_xor_sync(0xffffffffu, sm[j], 2); }
    const int t = lane & 3;
    const float sv = t == 0 ? sm[0] : t == 1 ? sm[1] : t == 2 ? sm[2] : sm[3];
    asm volatile("red.relaxed.gpu.global.add.f32 [%0], %1;" :: "l"(g_stat + (mt * 128 + warp * 16 + (t >> 1) * 8 + (lane >> 2)) * 2 + (t & 1)), "f"(sv) : "memory");
  }
}

__device__ __forceinline__ float silu_mul(float hg, float u) {
  float t; asm("tanh.approx.f32 %0, %1;" : "=f"(t) : "f"(hg));
  const float h = hg * u;
  return fmaf(h, t, h);
}

template <int BN>
__device__ __forceinline__ void h_swiglu(const float* acc, uint32_t va, int mt, int kb0, int warp, int lane) {
  uint8_t* ap = g_act + (size_t)(mt * 56 + kb0) * 16384 + tile_lane(warp, lane);
  float rs[2], nm[2], rh[2];
#pragma unroll
  for (int h = 0; h < 2; h++) {
    float t[2];
    lds64f(t, va + 2048 + (warp * 16 + h * 8 + (lane >> 2)) * 8);
    const float mean = t[0] * (1.f / D_);
    rs[h] = rsqrtf(fmaxf(t[1] * (1.f / D_) - mean * mean, 0.f) + 1e-5f);
    nm[h] = -mean * rs[h];
    rh[h] = 0.5f * rs[h];
  }
#pragma unroll
  for (int c = 0; c < BN / 64; c++) {
    uint32_t y[2][4];
#pragma unroll
    for (int j = 0; j < 4; j++) {
      const float* g = acc + 16 * c + 4 * j; const float* u = g + BN / 4;
      float p[4], q[4], o[4];
      lds128f(p, va + (4 * c + j) * 128 + (lane & 3) * 32); lds128f(q, va + (4 * c + j) * 128 + (lane & 3) * 32 + 16);
#pragma unroll
      for (int e = 0; e < 4; e++)
        o[e] = silu_mul(fmaf(rh[e >> 1], g[e], fmaf(nm[e >> 1], p[e & 1], p[2 + (e & 1)])), fmaf(rs[e >> 1], u[e], fmaf(nm[e >> 1], q[e & 1], q[2 + (e & 1)])));
      y[0][j] = pack2(o[0], o[1]); y[1][j] = pack2(o[2], o[3]);
    }
#pragma unroll
    for (int h = 0; h < 2; h++)
      *reinterpret_cast<uint4*>(ap + tile_off(c, h)) = make_uint4(y[h][0], y[h][1], y[h][2], y[h][3]);
    if (CH_FENCE1 && c + 1 < BN / 64) sched_fence(lane, 100);
  }
}

__global__ void __launch_bounds__(384, 1)
kernel_H(const __grid_constant__ CUtensorMap tmo, const __grid_constant__ CUtensorMap tm1, const __grid_constant__ CUtensorMap tm3,
         const __grid_constant__ CUtensorMap tm2, const __grid_constant__ CUtensorMap tmm, const __nv_bfloat16* __restrict__ x,
         const __nv_bfloat16* __restrict__ cvec, __nv_bfloat16* __restrict__ out, const __grid_constant__ HList list) {
  extern __shared__ __align__(1024) uint8_t smem[];
  constexpr uint32_t sb = 0x400, bars = sb + H_BAR;
  const int tid = threadIdx.x, lane = tid & 31;
  const int warp = __shfl_sync(0xffffffffu, tid >> 5, 0);
  if (tid == 0) {
    if (smem_u32(smem) != sb) __trap();
    for (int i = 0; i < H_NST; i++) { mbar_init(bars + HB_FULL + i * 8, 1); mbar_init(bars + HB_EMPTY + i * 8, 2); }
    for (int i = 0; i < 2; i++) { mbar_init(bars + HB_IFULL + i * 8, 1); mbar_init(bars + HB_IEMPTY + i * 8, 3); }
    mbar_init(bars + HB_NEXT, 1);
    fence_async_smem();
    if (PF_MAPS) {
      const CUtensorMap* maps[5] = {&tmm, &tm1, &tm3, &tmo, &tm2};
#pragma unroll
      for (int i = 0; i < 5; i++) asm volatile("prefetch.tensormap [%0];" :: "l"(maps[i]) : "memory");
    }
  }
  __syncthreads();
  if (warp >= 8) {
    asm volatile("setmaxnreg.dec.sync.aligned.u32 40;");
    if (warp == 8) {
      uint32_t st = 0, ph = 1;
#pragma unroll 1
      for (uint32_t n = 0;; n++) {
        mbar_wait(bars + HB_IFULL + (n & 1) * 8, (n >> 1) & 1);
        const uint32_t it = __shfl_sync(0xffffffffu, lds32(bars + HB_ITEM + (n & 1) * 4), 0);
        uint32_t have = __shfl_sync(0xffffffffu, lds32(bars + HB_HAVE + (n & 1) * 4), 0);
        if (elect_one()) mbar_arrive(bars + HB_IEMPTY + (n & 1) * 8);
        const int type = it & 7, mt = (it >> 3) & 15, idx = (it >> 7) & 63, sz = item_sz(it), part = (it >> 15) & 3, lgp = (it >> 17) & 3;
        if (type == IT_END) break;
        int f; uint32_t target, first = 0;
        item_deps(type, mt, opaque32(lane), f, target);
        if (type == IT_OUT) first = 3;
        const int gsh = type == IT_F1 ? 1 : type == IT_F2 ? 3 : 6;
        if (type >= IT_F1) first = FINE ? 1u << ((part * (56 >> lgp)) >> gsh) : type == IT_F1 ? 255u : 127u;
        auto need = [&](int g) {
          if (!((have >> g) & 1)) {
            if (lane == g) wait_flag2(&g_flags[f], target);
            __syncwarp();
            asm volatile("fence.proxy.async.global;" ::: "memory");
            have |= 1u << g;
          }
        };
        const bool has_a = type == IT_OUT || type >= IT_F1;
        if ((have & first) != first) {
          uint32_t c = 0;
          while (((have = __ballot_sync(0xffffffffu, ld_acquire(&g_flags[f]) >= target)) & first) != first) { if (++c > 20000000u) __trap(); __nanosleep(20); }
          asm volatile("fence.proxy.async.global;" ::: "memory");
        }
        if (type == IT_XT && elect_one()) mbar_arrive(bars + HB_NEXT);
        if (type != IT_XT) {
          const uint8_t* ap = type == IT_OUT ? g_att + (size_t)mt * 64 * 16384 : type == IT_F1 ? g_h2 + (size_t)mt * 16 * 16384 : g_act + (size_t)mt * 56 * 16384;
          const int nkb = (type == IT_OUT ? 64 : type == IT_F2 ? 56 : 16) >> lgp;
          const uint32_t abytes = has_a ? (sz == 2 ? 32768 : 16384) : 0, bytes = (sz == 0 ? 32768 : 16384) + abytes;
          const int dk = sz == 2 ? 1 : 0;
          const uint32_t late = type == IT_OUT ? 0x300 : type == IT_F1 ? 0x1ff : 0x100;
          const int kvec = !has_a || (lgp && !(it & IT_GATHER)) ? -1 : VEC_EARLY && (have & late) == late ? part * nkb + 1 + dk : (part + 1) * nkb - 1 - dk;
          const int knext = max(part * nkb, (part + 1) * nkb - ((sz == 0 ? ECL0 : ECL1) << dk));
#pragma unroll 1
          for (int kb = part * nkb; kb < (part + 1) * nkb; kb += 1 + dk) {
            const uint32_t d = sb + st * H_STAGE, fb = bars + HB_FULL + st * 8;
            mbar_wait(bars + HB_EMPTY + st * 8, ph);
            if (has_a) need(kb >> gsh);
            if (kb == kvec) {
              need(8);
              if (type == IT_OUT) need(9);
              if (elect_one()) {
                const bool f1 = type == IT_F1;
                const int c0 = f1 ? idx * (128 >> sz) : idx * (256 >> sz);
                const uint32_t v = sb + H_VEC + (n & 1) * 3072;
                const uint32_t n0 = (f1 ? 2048 : 512) >> sz, n1 = f1 ? 1024 : n0;
                asm volatile("mbarrier.expect_tx.relaxed.cta.shared::cta.b64 [%0], %1;" :: "r"(fb), "r"(n0 + n1) : "memory");
                bulk_g2s(v, f1 ? (const void*)(g_uv + c0 * 4) : (const void*)(g_mod + (type == IT_OUT ? 2 : 5) * D_ + c0), n0, fb);
                bulk_g2s(v + (f1 ? 2048 : 512), f1 ? (const void*)(g_stat + mt * 256) : (const void*)(g_mod + 4 * D_ + c0), n1, fb);
              }
            }
            if (elect_one()) {
              mbar_expect(fb, bytes);
              if (has_a) bulk_g2s(d, ap + (size_t)kb * 16384, abytes, fb);
              if (kb == knext) mbar_arrive(bars + HB_NEXT);
            }
            if (++st == H_NST) { st = 0; ph ^= 1; }
          }
          if (it & IT_GATHER) {
            const uint32_t i2 = opaque32(it), np = 1u << ((i2 >> 17) & 3);
            const int tile = split_tile(i2 & 7, (i2 >> 3) & 15, (i2 >> 7) & 63);
            if (lane == 0) wait_flag2(&g_flags[FL_SPL + tile], np - 1);
            __syncwarp();
            asm volatile("fence.proxy.async.global;" ::: "memory");
#pragma unroll 1
            for (uint32_t p = 1; p < np; p++) {
              const uint32_t fb = bars + HB_FULL + st * 8;
              mbar_wait(bars + HB_EMPTY + st * 8, ph);
              if (elect_one()) {
                mbar_expect(fb, 32768);
                bulk_g2s(sb + st * H_STAGE, g_ws + (size_t)tile * 32768 + (((i2 >> 15) & 3) ^ p) * 8192, 32768, fb);
              }
              if (++st == H_NST) { st = 0; ph ^= 1; }
            }
          }
        }
      }
    } else if (warp >= 10) {
      const int hb = warp - 10;
      uint32_t st = 0, ph = 1;
#pragma unroll 1
      for (uint32_t n = 0;; n++) {
        mbar_wait(bars + HB_IFULL + (n & 1) * 8, (n >> 1) & 1);
        const uint32_t it = __shfl_sync(0xffffffffu, lds32(bars + HB_ITEM + (n & 1) * 4), 0);
        const int type = it & 7, idx = (it >> 7) & 63, sz = item_sz(it), part = (it >> 15) & 3, lgp = (it >> 17) & 3;
        if (type == IT_END) break;
        if (elect_one()) mbar_arrive(bars + HB_IEMPTY + (n & 1) * 8);
        if (type == IT_XT) continue;
        const bool ffn1 = type == IT_F1 || type == IT_UV;
        const int nkb = (type == IT_OUT ? 64 : type == IT_F2 ? 56 : 16) >> lgp;
        const CUtensorMap* tb = type == IT_OUT ? &tmo : ffn1 ? &tm1 : type == IT_F2 ? &tm2 : &tmm;
        const CUtensorMap* tc = ffn1 ? &tm3 : tb;
        const int c0 = ffn1 ? idx * (128 >> sz) : idx * (256 >> sz) + (type == IT_MOD ? 2048 : 0), c2 = ffn1 ? c0 : c0 + 128;
        const int dk = sz == 2 ? 1 : 0;
        const CUtensorMap* t0 = hb == 1 && sz == 1 ? tc : tb;
        const int ca = hb == 0 || sz == 2 || (sz == 1 && ffn1) ? c0 : c0 + 64;
        const uint32_t off = (sz == 2 ? 32768 : 16384) + hb * 8192;
        const uint32_t cold = type == IT_MOD ? D_MOD : type == IT_UV ? D_UV : H_NST;
        if (type == IT_MOD || type == IT_UV) {
          if (lane == 0) wait_flag2(&g_flags[UV_WAIT && type == IT_UV ? FL_MOD : FL_GO], UV_WAIT && type == IT_UV ? UV_WAIT : 1);
          __syncwarp();
        }
#pragma unroll 1
        for (int kb = part * nkb; kb < (part + 1) * nkb; kb += 1 + dk) {
          const uint32_t d = sb + st * H_STAGE + off, fb = bars + HB_FULL + st * 8;
          mbar_wait(bars + HB_EMPTY + st * 8, ph);
          if (cold < H_NST) mbar_wait(bars + HB_FULL + ((st - cold) & 3) * 8, st >= cold ? ph ^ 1 : ph);
          if (elect_one()) {
            tma5d(d, t0, ca, kb + hb * dk, fb);
            if (sz == 0) tma5d(d + 16384, tc, c2 + hb * 64, kb, fb);
          }
          if (++st == H_NST) { st = 0; ph ^= 1; }
        }
        if (it & IT_GATHER) {
#pragma unroll 1
          for (int p = 1; p < (1 << lgp); p++) {
            mbar_wait(bars + HB_EMPTY + st * 8, ph);
            if (++st == H_NST) { st = 0; ph ^= 1; }
          }
        }
      }
    } else if (warp == 9) {
      uint32_t have;
      auto claim = [&]() {
        uint32_t q = 0;
        if (lane == 0) q = atomicAdd(&g_flags[FL_HEAD], 1);
        q = __shfl_sync(0xffffffffu, q, 0);
        const uint32_t it = q < list.n ? list.it[q] : 0;
        int f; uint32_t target;
        item_deps(it & 7, (it >> 3) & 15, lane, f, target);
        have = __ballot_sync(0xffffffffu, ld_acquire(&g_flags[f]) >= target);
        asm volatile("fence.proxy.async.global;" ::: "memory");
        return it | (q << 19);
      };
      auto hand_out = [&](uint32_t n, uint32_t it) {
        mbar_wait(bars + HB_IEMPTY + (n & 1) * 8, ((n >> 1) & 1) ^ 1);
        if (elect_one()) {
          sts32(bars + HB_ITEM + (n & 1) * 4, it);
          sts32(bars + HB_HAVE + (n & 1) * 4, have);
          mbar_arrive(bars + HB_IFULL + (n & 1) * 8);
        }
      };
      uint32_t next = claim();
      hand_out(0, next);
#pragma unroll 1
      for (uint32_t n = 0;; n++) {
        const uint32_t itq = next;
        const int type = itq & 7, mt = (itq >> 3) & 15;
        if (type == IT_END) break;
        mbar_wait(bars + HB_NEXT, n & 1);
        next = claim();
        const bool split = (itq >> 17) & 3, gath = itq & IT_GATHER;
        const bool hold = split && (gath ? (type == IT_OUT ? HOLD & 2 : false) : type == IT_OUT ? HOLD & 1 : HOLD & 4);
        if (!hold) hand_out(n + 1, next);
        if (n & 1) bar_sync<3, 288>(); else bar_sync<2, 288>();
        if (lane == 0) {
          const uint32_t inc = lds32(bars + HB_INC + (n & 1) * 4);
          if (inc) {
            fence_gpu();
            const int idx = (itq >> 7) & 63, sz = item_sz(itq);
            const int mv = (idx >> sz) >> 2;
            uint32_t* fl = &g_flags[type == IT_MOD ? (mv == 0 ? FL_MODA : mv == 3 ? FL_MODB : FL_MOD) : type == IT_UV ? FL_UV : type == IT_XT ? FL_XT + 8 * mt
                                    : type == IT_OUT ? FL_OUT + 8 * mt + ((2 * idx) >> sz) : FL_F1 + 8 * mt + (idx >> (2 + sz))];
            if (((itq >> 17) & 3) && !(itq & IT_GATHER)) fl = &g_flags[FL_SPL + split_tile(type, mt, idx)];
            red_add_u32(fl, inc);
            if (type == IT_OUT && sz == 0) red_add_u32(fl + 1, inc);
          }
        }
        __syncwarp();
        if (hold) hand_out(n + 1, next);
      }
      asm volatile("griddepcontrol.wait;" ::: "memory");
      uint32_t k = 0;
      if (lane == 0) { fence_gpu(); k = atomicAdd(&g_flags[FL_EXIT], 1); }
      k = __shfl_sync(0xffffffffu, k, 0);
      if (k == gridDim.x - 1) {
        fence_gpu();
        for (int i = lane; i < 1024; i += 32) g_flags[i] = 0;
      }
    }
  } else {
    asm volatile("setmaxnreg.inc.sync.aligned.u32 232;");
    const int wg = warp >> 2;
    const bool leader = (tid & 127) == 0;
    uint32_t st = 0, ph = 0;
    uint32_t nxt = 0;
#pragma unroll 1
    for (uint32_t n = 0;; n++) {
      uint32_t itq = nxt;
      if (itq == 0) {
        mbar_wait(bars + HB_IFULL + (n & 1) * 8, (n >> 1) & 1);
        itq = lds32(bars + HB_ITEM + (n & 1) * 4);
      }
      itq = __shfl_sync(0xffffffffu, itq, 0);
      nxt = 0;
      auto peek = [&]() {
        if (PEEK && mbar_test(bars + HB_IFULL + ((n + 1) & 1) * 8, ((n + 1) >> 1) & 1)) nxt = lds32(bars + HB_ITEM + ((n + 1) & 1) * 4);
      };
      auto finish = [&](uint32_t inc) {
        if (tid == 0) sts32(bars + HB_INC + (n & 1) * 4, inc);
        if (n & 1) bar_arrive<3, 288>(); else bar_arrive<2, 288>();
      };
      auto again = [&](int level, uint32_t inc) {
        if (PEEK < level) return false;
        nxt = __shfl_sync(0xffffffffu, nxt, 0);
        if (((nxt ^ itq) & 0x6007) != 0) return false;
        finish(inc);
        n++;
        itq = nxt;
        nxt = 0;
        HT(0);
        return true;
      };
      const int type = itq & 7, mt = (itq >> 3) & 15, idx = (itq >> 7) & 63, sz = item_sz(itq);
      uint32_t inc = type == IT_OUT ? (sz == 2 ? 1 : 2) : type == IT_F1 || type == IT_MOD ? 2 >> sz : type != IT_F2;
#define VA (sb + H_VEC + (n & 1) * 3072)
#define MT ((itq >> 3) & 15)
#define IDX ((itq >> 7) & 63)
#define SPLIT (itq >> 15) & 3, (itq >> 17) & 3, (itq & IT_GATHER) != 0
      if (type == IT_END) break;
      HT(0);
      if (type == IT_OUT) {
        if (sz == 0) h_residual<256, false>(sb, VA, mt, idx * 256, st, ph, warp, lane, out, peek);
        else if (sz == 1) { do h_residual<128, false>(sb, VA, MT, IDX * 128, st, ph, warp, lane, out, peek); while (again(5, 2)); }
        else { do h_residual<64, false>(sb, VA, MT, IDX * 64, st, ph, warp, lane, out, peek, SPLIT); while (again(5, 1)); }
      } else if (type == IT_F2) {
        if (sz == 0) h_residual<256, true>(sb, VA, mt, idx * 256, st, ph, warp, lane, out, peek);
        else if (sz == 1) { do h_residual<128, true>(sb, VA, MT, IDX * 128, st, ph, warp, lane, out, peek); while (again(4, 0)); }
        else {
          do {
            h_residual<64, true>(sb, VA, MT, IDX * 64, st, ph, warp, lane, out, peek, SPLIT);
            inc = ((itq >> 17) & 3) && !(itq & IT_GATHER);
          } while (again(4, inc));
        }
      } else if (type == IT_XT) {
        const int rg = idx * 8 + warp;
        const uint32_t* xp = reinterpret_cast<const uint32_t*>(x + (size_t)(mt * 128 + rg * 8 + (lane >> 2)) * D_) + (lane & 3);
        uint8_t* tp = g_x1 + (size_t)mt * 262144 + rg * 512 + tile_lane(0, lane);
        if (lane < 16) g_stat[(mt * 128 + rg * 8) * 2 + lane] = 0.f;
#pragma unroll 1
        for (int b = 0; b < 2; b++) {
          uint32_t v[64];
#pragma unroll
          for (int i = 0; i < 64; i++) v[i] = __ldg(xp + 256 * b + 4 * i);
#pragma unroll
          for (int i = 0; i < 16; i++)
            *reinterpret_cast<uint4*>(tp + tile_off(16 * b + i, 0)) = make_uint4(v[4 * i], v[4 * i + 1], v[4 * i + 2], v[4 * i + 3]);
        }
      } else if (type == IT_F1) {
        if (sz == 1) {
          do {
            float acc[64];
            h_mainloop<128, 0>(acc, sb, 16, st, ph, wg, leader, []() {}, peek);
            h_swiglu<128>(acc, VA, MT, IDX, warp, lane);
          } while (again(3, 1));
        } else {
          do {
            float acc[128];
            h_mainloop<256, 0>(acc, sb, 16, st, ph, wg, leader, []() {}, peek);
            h_swiglu<256>(acc, VA, MT, IDX * 2, warp, lane);
          } while (again(2, 2));
        }
      } else {
        if (type == IT_UV && tid == 0) wait_flag2(&g_flags[FL_MOD], 16);
        bar_sync<1, 256>();
        {
          const uint32_t* src = reinterpret_cast<const uint32_t*>(type == IT_UV ? g_mod + (wg == 0 ? 4 : 3) * D_ : cvec) + ((tid & 127) >> 2) * 16 + (tid & 3);
          uint32_t v[4];
#pragma unroll
          for (int j = 0; j < 4; j++) v[j] = __ldcg(src + 4 * j);
          const uint32_t p = sb + H_STG + ((tid & 127) >> 2) * 512 + (tid & 3) * 16;
          if (type == IT_MOD) {
#pragma unroll 1
            for (int j = 0; j < 4; j++) {
              const float c0 = bf_lo(v[0]), c1 = bf_hi(v[0]);
              v[0] = v[1]; v[1] = v[2]; v[2] = v[3];
              v[3] = pack2(c0 / (1.f + __expf(-c0)), c1 / (1.f + __expf(-c1)));
            }
          }
          if (type == IT_UV && wg == 0) sts128(p, 0x3f803f80u, 0x3f803f80u, 0x3f803f80u, 0x3f803f80u);
          if (type == IT_UV || wg == 0) sts128(type == IT_MOD ? p : wg == 0 ? p + 64 : (p ^ 16) + 128, v[0], v[1], v[2], v[3]);
        }
        fence_async_smem();
        bar_sync<1, 256>();
        float acc[8] = {0.f, 0.f, 0.f, 0.f, 0.f, 0.f, 0.f, 0.f};
        const uint64_t dw = mkdesc(sb + 16384 + wg * (16384 >> sz), 8192, 1024, 1), dv = mkdesc(sb + H_STG, 16, 0, 2);
#pragma unroll 1
        for (int i = 0; i < 16; i++) {
          mbar_wait(bars + HB_FULL + st * 8, ph);
          if (i == 0) HT(1);
          WG_FENCE();
#pragma unroll
          for (int k = 0; k < 4; k++) {
            const uint64_t a = dw + st * (H_STAGE >> 4) + k * 128, b = dv + i * 64 + (k >> 1) * 32 + (k & 1) * 2;
            wg_ss8(acc, a, b); wg_ss8(acc + 4, a + (sz ? 0 : 512), b);
          }
          WG_COMMIT();
          WG_WAIT(0);
          if (leader) mbar_arrive(bars + HB_EMPTY + st * 8);
          if (++st == H_NST) { st = 0; ph ^= 1; }
        }
        HT(2);
        reg_fence<8>(acc);
        const int t = lane & 3, c = (warp & 3) * 16 + (lane >> 2);
#pragma unroll
        for (int j = 0; j < 4; j++) {
          const int cj = c + (j >> 1) * 64 + (j & 1) * 8;
          if (type == IT_MOD) { if (t == 0 && (j < 2 || !sz)) g_mod[2048 + ((idx * 256 + wg * 128) >> sz) + cj] = __float2bfloat16(acc[2 * j]); }
          else if (t < 2) g_uv[idx * 512 + (cj >> 1) * 8 + wg * 4 + t * 2 + (cj & 1)] = (wg == 0 ? 0.5f : 1.f) * (t == 0 ? acc[2 * j] + acc[2 * j + 1] : acc[2 * j]);
        }
      }
      finish(inc);
    }
  }
}

const uint32_t h_items[] = {
  2, 130, 10, 138, 18, 146, 26, 154, 34, 162, 42, 170, 50, 178, 58, 186, 66, 194, 74, 202, 82, 210, 90, 218,
  98, 226, 106, 234, 114, 242, 122, 250, 1, 129, 257, 385, 513, 641, 769, 897, 1025, 1153, 1281, 1409, 4, 132, 260, 388,
  516, 644, 772, 900, 1028, 1156, 1284, 1412, 1540, 1668, 1796, 1924, 2052, 2180, 2308, 16387, 2436, 16515, 16643, 16771, 16899, 17027, 17155, 17283,
  17411, 17539, 17667, 17795, 17923, 18051, 18179, 18307, 2564, 2692, 2820, 2948, 3076, 3204, 3332, 1537, 3460, 1665, 1793, 1921, 16395, 16523, 16651, 16779,
  16907, 17035, 17163, 17291, 17419, 17547, 17675, 17803, 17931, 18059, 18187, 18315, 8211, 8339, 8467, 8595, 8723, 5, 133, 261, 389, 517, 645, 773,
  901, 1029, 1157, 1285, 1413, 1541, 1669, 1797, 1925, 2053, 2181, 2309, 2437, 8851, 8979, 9107, 2565, 2693, 2821, 2949, 3077, 3205, 3333, 3461,
  13, 141, 269, 781, 909, 1037, 1165, 1293, 1421, 1549, 1677, 1805, 1933, 2061, 2189, 2317, 2445, 397, 8219, 525, 8347, 653, 8475, 2573,
  2701, 2829, 8603, 2957, 3085, 8731, 3213, 3341, 17691, 3469, 8198, 8326, 8454, 8582, 17819, 2837, 8710, 8838, 17947, 8966, 18075, 9094, 3093, 18203,
  21, 3221, 18331, 16419, 3349, 16547, 16675, 3477, 16803, 1173, 16931, 1301, 17059, 1429, 2965, 1557, 17187, 1685, 17315, 2197, 17443, 1813, 17571, 2325,
  17699, 1941, 149, 2453, 277, 2069, 405, 2581, 533, 2709, 661, 29, 789, 157, 917, 285, 1045, 413, 17827, 541, 17955, 669, 18083, 797,
  18211, 925, 18339, 1053, 14, 1181, 142, 1309, 270, 1437, 398, 1565, 1693, 1821, 8235, 8363, 8491, 8619, 8747, 8875, 1949, 9003, 9131, 2077,
  2205, 2333, 3229, 2461, 3357, 2589, 3485, 2717, 8243, 2845, 8371, 2973, 8499, 3101, 8627, 8755, 8883, 9011, 9139, 37, 165, 293, 421, 549,
  677, 805, 933, 1061, 1189, 1317, 1445, 1573, 1701, 1829, 1957, 8251, 8379, 8507, 8635, 8763, 8891, 9019, 9147, 2085, 2213, 2341, 2469, 2597,
  2725, 2853, 2981, 3109, 3237, 3365, 3493, 45, 173, 301, 429, 557, 685, 813, 941, 1069, 1453, 1197, 1581, 1325, 9027, 1709, 1837, 1965,
  8259, 8387, 8515, 8643, 8771, 8899, 693, 9155, 2093, 2221, 2349, 2477, 2605, 2733, 2861, 2989, 3117, 3245, 9163, 2101, 2229, 3373, 3501, 53,
  181, 309, 437, 565, 821, 949, 1077, 1205, 1333, 1461, 1589, 1717, 1845, 1973, 8267, 8395, 8523, 8651, 8779, 8907, 9035, 2357, 2485, 2613,
  2741, 2869, 2997, 3125, 3253, 3381, 3509, 61, 189, 317, 445, 573, 701, 829, 957, 1085, 1213, 1341, 1469, 1597, 1725, 2493, 8275, 1853,
  8403, 1981, 8531, 2109, 8659, 2237, 8787, 2365, 8915, 9043, 9171, 2621, 2749, 2877, 3005, 3133, 3261, 3389, 3517, 1733, 69, 453, 197, 1861,
  325, 581, 709, 837, 1477, 965, 1605, 1093, 1989, 1221, 2117, 1349, 12869, 12997, 2245, 2501, 8283, 8411, 8539, 2629, 8667, 2757, 8795, 2885,
  8923, 9179, 3269, 3397, 1229, 3525, 973, 77, 205, 333, 461, 589, 1357, 717, 845, 1101, 3013, 9051, 3141, 1485, 1613, 1741, 1869, 1997,
  8675, 8291, 8803, 8419, 8931, 8547, 9059, 341, 3277, 85, 22, 469, 3405, 597, 3533, 725, 853, 981, 1109, 1237, 1365, 1493, 9187, 2125,
  2253, 2893, 2381, 2509, 3021, 213, 2637, 3149, 2765, 1621, 1749, 1877, 2005, 2133, 2261, 8427, 8299, 2389, 8555, 2517, 8683, 2645, 8811, 2773,
  8939, 2901, 9067, 3029, 9195, 150, 278, 406, 30, 158, 430, 286, 414, 38, 46, 166, 174, 294, 302, 422, 54, 182, 310, 438,
  8307, 8435, 8563, 8691, 8819, 8947, 9075, 9203, 278651, 311419, 344187, 376955, 278779, 311547, 344315, 377083, 180987, 312315, 148347, 345083, 181115, 148731, 181499, 148859,
  3157, 62, 148987, 149243, 278907, 3285, 190, 318, 149115, 311675, 148219, 344443, 279547, 181627, 1757, 377211, 181755, 181883, 1885, 147963, 2013, 180731, 2141, 2269,
  2397, 101, 2525, 182011, 148091, 180859, 3165, 149371, 182139, 280571, 313339, 346107, 279675, 377851, 378875, 312443, 345211, 377979, 446, 2653, 2781, 2909, 3037, 3293,
  3421, 3549, 3413, 733, 229, 989, 741, 1117, 1245, 869, 997, 1373, 1125, 1501, 1253, 1509, 3541, 93, 1629, 221, 349, 477, 1381, 605,
  357, 485, 861, 613, 1637, 1893, 2021, 2149, 2277, 2405, 2533, 2661, 2789, 12269, 2917, 3045, 12397, 3173, 12525, 3301, 12653, 3429, 12781, 12909,
  3557, 13037, 8301, 8429, 13165, 13293, 1765, 8557, 8685, 13421, 13549, 8813, 13677, 9069, 13805, 9197, 13933, 8941, 14061, 9325, 9453, 14189, 14317, 9581,
  9709, 14445, 14573, 9837, 10861, 10989, 11117, 11245, 11373, 11501, 11629, 9965, 14701, 14829, 10093, 10221, 14957, 15213, 15341, 10605, 10733, 15085, 11757, 10349,
  8573, 11885, 10477, 8701, 12013, 2549, 12141, 2677, 8317, 2805, 2933, 8262, 8390, 8518, 8646, 8774, 9030, 9158, 8902, 9038, 9166, 8270, 8398, 8526,
  8654, 8782, 3061, 8910, 3189, 3317, 117, 245, 373, 501, 629, 757, 3445, 3573, 1269, 1397, 1525, 8445, 8829, 8957, 9085, 9213, 9341, 9469,
  9597, 9725, 9853, 10621, 9981, 10109, 10749, 11645, 10237, 11773, 12029, 10365, 11901, 12157, 12285, 10493, 885, 12413, 1653, 1781, 1013, 1909, 1141, 12541,
  2037, 12669, 2165, 12797, 2293, 12925, 2421, 13053, 13181, 13309, 13565, 13437, 13693, 13821, 10877, 11005, 11133, 11517, 13949, 14077, 14205, 14333, 14461, 14589,
  14717, 14845, 14973, 8278, 8406, 8534, 15101, 8662, 15229, 8790, 15357, 9174, 8918, 11261, 8286, 9046, 8542, 11389, 8414, 8670, 8798, 8926, 9054, 9182,
  147558, 180326, 147686, 180454, 147814, 180582, 16870, 16998, 17126, 17254, 17382, 17510, 17638, 17766, 17894, 18022, 18150, 18278, 18406, 16494, 16622, 16750, 16878, 17006,
  17134, 17390, 17518, 17646, 17774, 17902, 18030, 18158, 17262, 18414, 18286, 16894, 17022, 17150, 17278, 17534, 17662, 17790, 18046, 18174, 278774, 16510, 16638, 311542,
  16766, 18302, 344310, 18430, 147574, 17918, 377078, 17406, 180342, 147830, 180598, 148470, 181238, 182006, 149366, 182134, 148598, 181366, 148726, 148854, 181494, 181622, 147958, 180726,
  148086, 180854, 148214, 180982, 148342, 181110, 148982, 181750, 149110, 181878, 149238, 149494, 182262,
};
void build_list(HList& l) {
  l.n = sizeof(h_items) / sizeof(h_items[0]);
  for (uint32_t i = 0; i < l.n; i++) l.it[i] = h_items[i];
}

typedef CUresult (*EncodeFn)(CUtensorMap*, CUtensorMapDataType, cuuint32_t, void*, const cuuint64_t*, const cuuint64_t*,
                             const cuuint32_t*, const cuuint32_t*, CUtensorMapInterleave, CUtensorMapSwizzle,
                             CUtensorMapL2promotion, CUtensorMapFloatOOBfill);

#define PROMO_W CU_TENSOR_MAP_L2_PROMOTION_L2_128B
#define PROMO_O CU_TENSOR_MAP_L2_PROMOTION_L2_128B
#define PROMO_M CU_TENSOR_MAP_L2_PROMOTION_L2_128B
#define PROMO_H CU_TENSOR_MAP_L2_PROMOTION_L2_128B
void make_map(EncodeFn fn, CUtensorMap* m, const void* p, uint64_t cols, uint64_t rows, uint32_t bc, uint32_t br, CUtensorMapSwizzle sw,
              CUtensorMapL2promotion promo) {
  cuuint64_t dims[2] = {cols, rows};
  cuuint64_t strides[1] = {cols * 2};
  cuuint32_t box[2] = {bc, br};
  cuuint32_t es[2] = {1, 1};
  fn(m, CU_TENSOR_MAP_DATA_TYPE_BFLOAT16, 2, const_cast<void*>(p), dims, strides, box, es, CU_TENSOR_MAP_INTERLEAVE_NONE, sw,
     promo, CU_TENSOR_MAP_FLOAT_OOB_FILL_NONE);
}

void make_map_perm(EncodeFn fn, CUtensorMap* m, const void* p, uint64_t cols, uint64_t rows, bool perm) {
  cuuint64_t dims[5] = {cols, 2, 4, 4, rows / 32};
  cuuint64_t strides[4] = {cols * 2, cols * 2 * (perm ? 8 : 2), cols * 2 * (perm ? 2 : 8), cols * 2 * 32};
  cuuint32_t box[5] = {64, 2, 4, 4, 2};
  cuuint32_t es[5] = {1, 1, 1, 1, 1};
  fn(m, CU_TENSOR_MAP_DATA_TYPE_BFLOAT16, 5, const_cast<void*>(p), dims, strides, box, es, CU_TENSOR_MAP_INTERLEAVE_NONE,
     CU_TENSOR_MAP_SWIZZLE_128B, PROMO_H, CU_TENSOR_MAP_FLOAT_OOB_FILL_NONE);
}

}

extern "C" void kernel_launch(void* const* d_in, const int* in_sizes, int n_in, void* d_out, int out_size) {
  const __nv_bfloat16* x = (const __nv_bfloat16*)d_in[0];
  const __nv_bfloat16* mem0 = (const __nv_bfloat16*)d_in[1];
  const __nv_bfloat16* cvec = (const __nv_bfloat16*)d_in[11];
  static EncodeFn enc = nullptr;
  if (!enc) {
    cudaDriverEntryPointQueryResult qr;
    void* fp = nullptr;
    cudaGetDriverEntryPoint("cuTensorMapEncodeTiled", &fp, cudaEnableDefault, &qr);
    enc = (EncodeFn)fp;
    cudaFuncSetAttribute(kernel_R, cudaFuncAttributeMaxDynamicSharedMemorySize, R_SMEM);
    cudaFuncSetAttribute(kernel_H, cudaFuncAttributeMaxDynamicSharedMemorySize, H_SMEM);
  }
  CUtensorMap tmq, tmk, tmv, tmo, tmm;
  make_map(enc, &tmm, d_in[12], 6144, 1024, 64, 64, CU_TENSOR_MAP_SWIZZLE_NONE, PROMO_M);
  make_map(enc, &tmq, d_in[2], 4096, 1024, 64, 64, CU_TENSOR_MAP_SWIZZLE_128B, PROMO_W);
  make_map(enc, &tmk, d_in[3], 4096, 1024, 64, 64, CU_TENSOR_MAP_SWIZZLE_128B, PROMO_W);
  make_map(enc, &tmv, d_in[4], 4096, 1024, 64, 64, CU_TENSOR_MAP_SWIZZLE_128B, PROMO_W);
  make_map(enc, &tmo, d_in[5], 1024, 4096, 16, 128, CU_TENSOR_MAP_SWIZZLE_32B, PROMO_O);
  RDesc dsc;
  for (int k = 0; k < 32; k++) {
    dsc.tok[k] = mkdesc(0x400 + (k < 16 ? R_GA : R_GB) + ((k & 15) >> 2) * 4096 + (k & 3) * 256, 128, 1024, 0);
    dsc.tail_a[k] = mkdesc(0x400 + R_TAIL + k * 2048, 1024, 1024, 1);
    if (k < 16) dsc.tail_b[k] = mkdesc(0x400 + R_GA + k * 256, 128, 4096, 0);
  }
  kernel_R<<<96, 256, R_SMEM, cudaStreamPerThread>>>(tmq, tmk, tmv, tmo, tmm, x, mem0, cvec, dsc);

  CUtensorMap ho, h1, h3, h2, hm;
  make_map_perm(enc, &ho, d_in[5], 1024, 4096, false);
  make_map_perm(enc, &h1, d_in[8], F_, 1024, true);
  make_map_perm(enc, &h3, d_in[9], F_, 1024, true);
  make_map_perm(enc, &h2, d_in[10], 1024, F_, true);
  make_map_perm(enc, &hm, d_in[12], 6144, 1024, true);
  HList list;
  build_list(list);
  {
    bool seen[12 * 16] = {};
    for (int i = (int)list.n - 1; i >= 0; i--) {
      const uint32_t it = list.it[i];
      if ((it >> 17) & 3) {
        const int t = split_tile(it & 7, (it >> 3) & 15, (it >> 7) & 63);
        if (!seen[t]) list.it[i] |= IT_GATHER;
        seen[t] = true;
      }
    }
  }
  cudaLaunchConfig_t cfg = {};
#define H_GRID 132
  cfg.gridDim = dim3(H_GRID); cfg.blockDim = dim3(384); cfg.dynamicSmemBytes = H_SMEM; cfg.stream = cudaStreamPerThread;
  cudaLaunchAttribute at[1];
  at[0].id = cudaLaunchAttributeProgrammaticStreamSerialization;
  at[0].val.programmaticStreamSerializationAllowed = 1;
  cfg.attrs = at;
  cfg.numAttrs = 1;
  cudaLaunchKernelEx(&cfg, kernel_H, ho, h1, h3, h2, hm, x, cvec, (__nv_bfloat16*)d_out, list);
}
```

```cpp
#include <cuda_runtime.h>
#include <cuda_bf16.h>
#include <cuda.h>
#include <stdint.h>
#include <type_traits>

namespace {

constexpr int S_ = 2048, D_ = 1024, NSEG = 64, F_ = 3584;

__device__ __align__(1024) uint8_t g_h[S_ * D_ * 2];
__device__ __align__(1024) uint8_t g_att[S_ * 4096 * 2];
__device__ __align__(1024) uint8_t g_x1[S_ * D_ * 2];
__device__ __align__(1024) uint8_t g_h2[S_ * D_ * 2];
__device__ __align__(1024) uint8_t g_act[S_ * F_ * 2];
__device__ __align__(1024) float g_ws[12 * 16 * 4 * 8192];
__device__ __align__(1024) float g_stat[S_ * 2];
__device__ __align__(1024) float g_uv[F_ * 4];
__device__ __align__(1024) float g_slot[4 * 3 * 8 * 4 * 32 * 4];
__device__ __align__(128) __nv_bfloat16 g_mod[6 * D_];
__device__ __align__(128) float g_modp[3 * 2 * D_];
__device__ __align__(128) uint32_t g_flags[1024];
constexpr int FL_S1 = 0, FL_S2 = 32, FL_MOD = 64, FL_HEAD = 96, FL_EXIT = 128, FL_UV = 160, FL_GO = 192, FL_MODB = 224, FL_MODA = 240, FL_ATT = 256, FL_XT = 384, FL_OUT = 512, FL_F1 = 640, FL_SPL = 768;

#define EVF 1
__device__ __forceinline__ uint32_t smem_u32(const void* p) { return (uint32_t)__cvta_generic_to_shared(p); }
__device__ __forceinline__ uint32_t mapa(uint32_t a, uint32_t r) { uint32_t o; asm("mapa.shared::cluster.u32 %0, %1, %2;" : "=r"(o) : "r"(a), "r"(r)); return o; }
__device__ __forceinline__ uint32_t pack2(float a, float b) { uint32_t r; asm("cvt.rn.bf16x2.f32 %0, %1, %2;" : "=r"(r) : "f"(b), "f"(a)); return r; }
__device__ __forceinline__ float bf_lo(uint32_t w) { return __uint_as_float(w << 16); }
__device__ __forceinline__ float bf_hi(uint32_t w) { return __uint_as_float(w & 0xffff0000u); }
__device__ __forceinline__ float ex2(float x) { float y; asm("ex2.approx.ftz.f32 %0, %1;" : "=f"(y) : "f"(x)); return y; }
__device__ __forceinline__ float rcp(float x) { float y; asm("rcp.approx.ftz.f32 %0, %1;" : "=f"(y) : "f"(x)); return y; }
__device__ __forceinline__ uint32_t clk32() { uint64_t c; asm volatile("mov.u64 %0, %%clock64;" : "=l"(c) :: "memory"); return (uint32_t)c; }

__device__ __forceinline__ void mbar_init(uint32_t b, uint32_t n) { asm volatile("mbarrier.init.shared::cta.b64 [%0], %1;" :: "r"(b), "r"(n) : "memory"); }
__device__ __forceinline__ void mbar_arrive(uint32_t b) { asm volatile("mbarrier.arrive.shared::cta.b64 _, [%0];" :: "r"(b) : "memory"); }
__device__ __forceinline__ void mbar_expect(uint32_t b, uint32_t n) { asm volatile("mbarrier.arrive.expect_tx.shared::cta.b64 _, [%0], %1;" :: "r"(b), "r"(n) : "memory"); }
__device__ __forceinline__ uint32_t mbar_try(uint32_t b, uint32_t par) {
  uint32_t ok;
  asm volatile("{\n.reg .pred p;\nmbarrier.try_wait.parity.shared::cta.b64 p, [%1], %2;\nselp.u32 %0, 1, 0, p;\n}" : "=r"(ok) : "r"(b), "r"(par) : "memory");
  return ok;
}
__device__ __forceinline__ bool mbar_test(uint32_t b, uint32_t par) {
  uint32_t ok;
  asm volatile("{\n.reg .pred p;\nmbarrier.test_wait.parity.shared::cta.b64 p, [%1], %2;\nselp.u32 %0, 1, 0, p;\n}" : "=r"(ok) : "r"(b), "r"(par) : "memory");
  return ok;
}
__device__ __forceinline__ void mbar_wait(uint32_t b, uint32_t par) {
  asm volatile("{\n.reg .pred p;\n"
               "LOOP:\n"
               "mbarrier.try_wait.parity.shared::cta.b64 p, [%0], %1;\n"
               "@!p bra.uni LOOP;\n}" :: "r"(b), "r"(par) : "memory");
}
__device__ __forceinline__ void mbar_wait_safe(uint32_t b, uint32_t par) {
  uint32_t c = 0;
  while (!mbar_try(b, par)) { if (++c > 4000000u) __trap(); }
}
__device__ __forceinline__ bool elect_one() {
  uint32_t p;
  asm volatile("{\n.reg .pred p;\nelect.sync _|p, 0xffffffff;\nselp.u32 %0, 1, 0, p;\n}" : "=r"(p));
  return p;
}
__device__ __forceinline__ void sched_fence(uint32_t x, uint32_t y) { asm volatile("{\n.reg .pred p;\nsetp.eq.u32 p, %0, %1;\n@p trap;\n}" :: "r"(x), "r"(y) : "memory"); }
template <class T> __device__ __forceinline__ T opaque32(T x) { asm volatile("" : "+r"(x)); return x; }
template <class T> __device__ __forceinline__ T opaque64(T x) { asm volatile("" : "+l"(x)); return x; }
template <int ID, int N> __device__ __forceinline__ void bar_sync() { asm volatile("bar.sync %0, %1;" :: "n"(ID), "n"(N) : "memory"); }
template <int ID, int N> __device__ __forceinline__ void bar_arrive() { asm volatile("bar.arrive %0, %1;" :: "n"(ID), "n"(N) : "memory"); }
__device__ __forceinline__ void fence_async_smem() { asm volatile("fence.proxy.async.shared::cta;" ::: "memory"); }
__device__ __forceinline__ void fence_async_all() { asm volatile("fence.proxy.async;" ::: "memory"); }
__device__ __forceinline__ void fence_gpu() { asm volatile("fence.acq_rel.gpu;" ::: "memory"); }
__device__ __forceinline__ void red_add_u32(uint32_t* p, uint32_t v) { asm volatile("red.relaxed.gpu.global.add.u32 [%0], %1;" :: "l"(p), "r"(v) : "memory"); }
__device__ __forceinline__ uint32_t ld_acquire(const uint32_t* p) { uint32_t v; asm volatile("ld.acquire.gpu.global.u32 %0, [%1];" : "=r"(v) : "l"(p) : "memory"); return v; }
__device__ __forceinline__ void wait_flag(const uint32_t* p, uint32_t target) {
  uint32_t c = 0;
  while (ld_acquire(p) < target) { if (++c > 20000000u) __trap(); __nanosleep(20); }
}

__device__ __forceinline__ void wait_flag2(const uint32_t* p, uint32_t target) {
  asm volatile("{\n.reg .pred p;\n.reg .u32 v, c;\nmov.u32 c, 0;\nWL:\nld.acquire.gpu.global.u32 v, [%0];\nsetp.ge.u32 p, v, %1;\n@p bra WD;\n"
               "add.u32 c, c, 1;\nsetp.gt.u32 p, c, 20000000;\n@p trap;\nnanosleep.u32 20;\nbra WL;\nWD:\n}" :: "l"(p), "r"(target) : "memory");
}
__device__ __forceinline__ void tma2d(uint32_t dst, const CUtensorMap* m, int c0, int c1, uint32_t bar) {
  asm volatile("cp.async.bulk.tensor.2d.shared::cluster.global.mbarrier::complete_tx::bytes [%0], [%1, {%3, %4}], [%2];"
               :: "r"(dst), "l"(m), "r"(bar), "r"(c0), "r"(c1) : "memory");
}
__device__ __forceinline__ void tma2d_once(uint32_t dst, const CUtensorMap* m, int c0, int c1, uint32_t bar) {
  asm volatile("{\n.reg .b64 pol;\ncreatepolicy.fractional.L2::evict_first.b64 pol, 1.0;\n"
               "cp.async.bulk.tensor.2d.shared::cluster.global.mbarrier::complete_tx::bytes.L2::cache_hint [%0], [%1, {%3, %4}], [%2], pol;\n}"
               :: "r"(dst), "l"(m), "r"(bar), "r"(c0), "r"(c1) : "memory");
}
__device__ __forceinline__ void tma5d(uint32_t dst, const CUtensorMap* m, int n0, int kb, uint32_t bar) {
  asm volatile("cp.async.bulk.tensor.5d.shared::cluster.global.mbarrier::complete_tx::bytes [%0], [%1, {%3, %5, %5, %5, %4}], [%2];"
               :: "r"(dst), "l"(m), "r"(bar), "r"(n0), "r"(2 * kb), "r"(0) : "memory");
}
__device__ __forceinline__ void tma2d_prefetch(const CUtensorMap* m, int c0, int c1) {
  asm volatile("cp.async.bulk.prefetch.tensor.2d.L2.global [%0, {%1, %2}];" :: "l"(m), "r"(c0), "r"(c1) : "memory");
}
__device__ __forceinline__ void bulk_g2s(uint32_t dst, const void* src, uint32_t bytes, uint32_t bar) {
  asm volatile("cp.async.bulk.shared::cluster.global.mbarrier::complete_tx::bytes [%0], [%1], %2, [%3];"
               :: "r"(dst), "l"(src), "r"(bytes), "r"(bar) : "memory");
}
__device__ __forceinline__ void bulk_s2s(uint32_t dst, uint32_t src, uint32_t bytes, uint32_t bar) {
  asm volatile("cp.async.bulk.shared::cluster.shared::cta.mbarrier::complete_tx::bytes [%0], [%1], %2, [%3];"
               :: "r"(dst), "r"(src), "r"(bytes), "r"(bar) : "memory");
}
__device__ __forceinline__ void st_async1(uint32_t dst, uint32_t a, uint32_t bar) {
  asm volatile("st.async.shared::cluster.mbarrier::complete_tx::bytes.b32 [%0], %1, [%2];" :: "r"(dst), "r"(a), "r"(bar) : "memory");
}
__device__ __forceinline__ void st_async2(uint32_t dst, uint32_t a, uint32_t b, uint32_t bar) {
  asm volatile("st.async.shared::cluster.mbarrier::complete_tx::bytes.v2.b32 [%0], {%1, %2}, [%3];" :: "r"(dst), "r"(a), "r"(b), "r"(bar) : "memory");
}
__device__ __forceinline__ void st_async4(uint32_t dst, const uint32_t* r, uint32_t bar) {
  asm volatile("st.async.shared::cluster.mbarrier::complete_tx::bytes.v4.b32 [%0], {%1, %2, %3, %4}, [%5];"
               :: "r"(dst), "r"(r[0]), "r"(r[1]), "r"(r[2]), "r"(r[3]), "r"(bar) : "memory");
}
__device__ __forceinline__ void sts32(uint32_t a, uint32_t v) { asm volatile("st.shared.b32 [%0], %1;" :: "r"(a), "r"(v) : "memory"); }
__device__ __forceinline__ void sts64(uint32_t a, uint32_t x, uint32_t y) { asm volatile("st.shared.v2.b32 [%0], {%1, %2};" :: "r"(a), "r"(x), "r"(y) : "memory"); }
__device__ __forceinline__ void sts128(uint32_t a, uint32_t x, uint32_t y, uint32_t z, uint32_t w) {
  asm volatile("st.shared.v4.b32 [%0], {%1, %2, %3, %4};" :: "r"(a), "r"(x), "r"(y), "r"(z), "r"(w) : "memory");
}
__device__ __forceinline__ void lds128(uint32_t* r, uint32_t a) {
  asm volatile("ld.shared.v4.b32 {%0, %1, %2, %3}, [%4];" : "=r"(r[0]), "=r"(r[1]), "=r"(r[2]), "=r"(r[3]) : "r"(a) : "memory");
}
__device__ __forceinline__ uint32_t lds32(uint32_t a) { uint32_t r; asm volatile("ld.shared.b32 %0, [%1];" : "=r"(r) : "r"(a) : "memory"); return r; }
__device__ __forceinline__ void lds64(uint32_t* r, uint32_t a) {
  asm volatile("ld.shared.v2.b32 {%0, %1}, [%2];" : "=r"(r[0]), "=r"(r[1]) : "r"(a) : "memory");
}
__device__ __forceinline__ void lds128f(float* r, uint32_t a) {
  asm volatile("ld.shared.v4.f32 {%0, %1, %2, %3}, [%4];" : "=f"(r[0]), "=f"(r[1]), "=f"(r[2]), "=f"(r[3]) : "r"(a) : "memory");
}
__device__ __forceinline__ void lds64f(float* r, uint32_t a) {
  asm volatile("ld.shared.v2.f32 {%0, %1}, [%2];" : "=f"(r[0]), "=f"(r[1]) : "r"(a) : "memory");
}
__device__ __forceinline__ void ldsm4(uint32_t* r, uint32_t a) {
  asm volatile("ldmatrix.sync.aligned.m8n8.x4.shared.b16 {%0, %1, %2, %3}, [%4];" : "=r"(r[0]), "=r"(r[1]), "=r"(r[2]), "=r"(r[3]) : "r"(a) : "memory");
}
__device__ __forceinline__ void ldsm4t(uint32_t* r, uint32_t a) {
  asm volatile("ldmatrix.sync.aligned.m8n8.x4.trans.shared.b16 {%0, %1, %2, %3}, [%4];" : "=r"(r[0]), "=r"(r[1]), "=r"(r[2]), "=r"(r[3]) : "r"(a) : "memory");
}
__device__ __forceinline__ void ldsm2(uint32_t* r, uint32_t a) {
  asm volatile("ldmatrix.sync.aligned.m8n8.x2.shared.b16 {%0, %1}, [%2];" : "=r"(r[0]), "=r"(r[1]) : "r"(a) : "memory");
}
__device__ __forceinline__ void stsm4(uint32_t a, const uint32_t* r) {
  asm volatile("stmatrix.sync.aligned.m8n8.x4.shared.b16 [%0], {%1, %2, %3, %4};" :: "r"(a), "r"(r[0]), "r"(r[1]), "r"(r[2]), "r"(r[3]) : "memory");
}
__device__ __forceinline__ uint32_t hadd2(uint32_t a, uint32_t b) { uint32_t t; asm("add.rn.bf16x2 %0, %1, %2;" : "=r"(t) : "r"(a), "r"(b)); return t; }
__device__ __forceinline__ uint32_t hmax2(uint32_t a, uint32_t b) { uint32_t t; asm("max.bf16x2 %0, %1, %2;" : "=r"(t) : "r"(a), "r"(b)); return t; }
__device__ __forceinline__ void ldsm2t(uint32_t* r, uint32_t a) {
  asm volatile("ldmatrix.sync.aligned.m8n8.x2.trans.shared.b16 {%0, %1}, [%2];" : "=r"(r[0]), "=r"(r[1]) : "r"(a) : "memory");
}
__device__ __forceinline__ uint32_t movm(uint32_t x) { uint32_t y; asm volatile("movmatrix.sync.aligned.m8n8.trans.b16 %0, %1;" : "=r"(y) : "r"(x)); return y; }
__device__ __forceinline__ void hmma(float* d, uint32_t a0, uint32_t a1, uint32_t a2, uint32_t a3, uint32_t b0, uint32_t b1) {
  asm volatile("mma.sync.aligned.m16n8k16.row.col.f32.bf16.bf16.f32 {%0,%1,%2,%3}, {%4,%5,%6,%7}, {%8,%9}, {%0,%1,%2,%3};"
               : "+f"(d[0]), "+f"(d[1]), "+f"(d[2]), "+f"(d[3]) : "r"(a0), "r"(a1), "r"(a2), "r"(a3), "r"(b0), "r"(b1));
}
__device__ __forceinline__ void hmma0(float* d, uint32_t a0, uint32_t a1, uint32_t a2, uint32_t a3, uint32_t b0, uint32_t b1) {
  asm volatile("mma.sync.aligned.m16n8k16.row.col.f32.bf16.bf16.f32 {%0,%1,%2,%3}, {%4,%5,%6,%7}, {%8,%9}, {%10,%10,%10,%10};"
               : "=f"(d[0]), "=f"(d[1]), "=f"(d[2]), "=f"(d[3]) : "r"(a0), "r"(a1), "r"(a2), "r"(a3), "r"(b0), "r"(b1), "f"(0.f));
}
__device__ __forceinline__ void hmma_k8(float* d, uint32_t a0, uint32_t a1, uint32_t b0) {
  asm volatile("mma.sync.aligned.m16n8k8.row.col.f32.bf16.bf16.f32 {%0,%1,%2,%3}, {%4,%5}, {%6}, {%0,%1,%2,%3};"
               : "+f"(d[0]), "+f"(d[1]), "+f"(d[2]), "+f"(d[3]) : "r"(a0), "r"(a1), "r"(b0));
}
__host__ __device__ constexpr uint64_t mkdesc(uint32_t addr, uint32_t lbo, uint32_t sbo, uint32_t sw) {
  return (uint64_t)((addr & 0x3FFFF) >> 4) | ((uint64_t)(lbo >> 4) << 16) | ((uint64_t)(sbo >> 4) << 32) | ((uint64_t)sw << 62);
}
#define WG_FENCE() asm volatile("wgmma.fence.sync.aligned;" ::: "memory")
#define WG_COMMIT() asm volatile("wgmma.commit_group.sync.aligned;" ::: "memory")
#define WG_WAIT(n) asm volatile("wgmma.wait_group.sync.aligned " #n ";" ::: "memory")
template <int N> __device__ __forceinline__ void reg_fence(float* d) {
#pragma unroll
  for (int i = 0; i < N; i++) asm volatile("" : "+f"(d[i]) :: "memory");
}
template <int N> __device__ __forceinline__ void zero_regs(float* d) {
#pragma unroll
  for (int i = 0; i < N; i++) asm volatile("mov.b32 %0, 0;" : "=f"(d[i]));
}
template <int SD>
__device__ __forceinline__ void wg_rs32(float* d, uint32_t a0, uint32_t a1, uint32_t a2, uint32_t a3, uint64_t b) {
  asm volatile("wgmma.mma_async.sync.aligned.m64n32k16.f32.bf16.bf16 {%0,%1,%2,%3,%4,%5,%6,%7,%8,%9,%10,%11,%12,%13,%14,%15}, {%16,%17,%18,%19}, %20, %21, 1, 1, 0;"
               : "+f"(d[0]), "+f"(d[1]), "+f"(d[2]), "+f"(d[3]), "+f"(d[4]), "+f"(d[5]), "+f"(d[6]), "+f"(d[7]),
                 "+f"(d[8]), "+f"(d[9]), "+f"(d[10]), "+f"(d[11]), "+f"(d[12]), "+f"(d[13]), "+f"(d[14]), "+f"(d[15])
               : "r"(a0), "r"(a1), "r"(a2), "r"(a3), "l"(b), "n"(SD));
}
template <int TB>
__device__ __forceinline__ void wg_ss40(float* d, uint64_t a, uint64_t b) {
  asm volatile("wgmma.mma_async.sync.aligned.m64n40k16.f32.bf16.bf16 {%0,%1,%2,%3,%4,%5,%6,%7,%8,%9,%10,%11,%12,%13,%14,%15,%16,%17,%18,%19}, %20, %21, 1, 1, 1, 1, %22;"
               : "+f"(d[0]), "+f"(d[1]), "+f"(d[2]), "+f"(d[3]), "+f"(d[4]), "+f"(d[5]), "+f"(d[6]), "+f"(d[7]),
                 "+f"(d[8]), "+f"(d[9]), "+f"(d[10]), "+f"(d[11]), "+f"(d[12]), "+f"(d[13]), "+f"(d[14]), "+f"(d[15]),
                 "+f"(d[16]), "+f"(d[17]), "+f"(d[18]), "+f"(d[19])
               : "l"(a), "l"(b), "n"(TB));
}
__device__ __forceinline__ void wg_ss8(float* d, uint64_t a, uint64_t b) {
  asm volatile("wgmma.mma_async.sync.aligned.m64n8k16.f32.bf16.bf16 {%0,%1,%2,%3}, %4, %5, 1, 1, 1, 1, 0;"
               : "+f"(d[0]), "+f"(d[1]), "+f"(d[2]), "+f"(d[3]) : "l"(a), "l"(b));
}
template <int T>
__device__ __forceinline__ void wg_ss32(float* d, uint64_t a, uint64_t b) {
  asm volatile("wgmma.mma_async.sync.aligned.m64n32k16.f32.bf16.bf16 {%0,%1,%2,%3,%4,%5,%6,%7,%8,%9,%10,%11,%12,%13,%14,%15}, %16, %17, 1, 1, 1, %18, %18;"
               : "+f"(d[0]), "+f"(d[1]), "+f"(d[2]), "+f"(d[3]), "+f"(d[4]), "+f"(d[5]), "+f"(d[6]), "+f"(d[7]),
                 "+f"(d[8]), "+f"(d[9]), "+f"(d[10]), "+f"(d[11]), "+f"(d[12]), "+f"(d[13]), "+f"(d[14]), "+f"(d[15])
               : "l"(a), "l"(b), "n"(T));
}

constexpr int R_TAIL = 0;
constexpr int R_WO = 65536;
constexpr int R_QK = R_WO + 86016;
constexpr int R_P = R_QK + 10240;
constexpr int R_GA = R_P + 6400;
constexpr int R_M2 = R_GA + 16384;
constexpr int R_M1 = R_M2 + 7168;
constexpr int R_GB = R_M1 + 9216;
constexpr int R_VT = R_GB + 16384;
constexpr int R_VM = R_VT + 8192;
constexpr int R_XS = R_VM + 2048;
constexpr int R_OX = R_XS + 1280;
constexpr int R_BAR = R_OX + 2048;
constexpr int R_TRC = R_BAR + 256;
constexpr int R_SMEM = R_TRC + 1024;
constexpr int B_MB = 0, B_XS = 32, B_VM = 40, B_VT = 48, B_TS = 56, B_FA = 64, B_FB = 72, B_TAIL = 80, B_WO = 88, B_STG = 96, B_WM = 128, B_X = 136;
constexpr int NB_A = 1, NB_B = 2, NB_X = 3, NB_C = 4, NB_D = 5, NB_E = 6, NB_F = 7, NB_G = 8, NB_H = 9, NB_S = 10, NB_E2 = 11, NB_P = 12, NB_W0 = 13;

#define FIN 1
#define POLL_DELAY 750
#define POLL_DELAY1 700
#define POLL_STAG 150
#define POLL_K0 20
#define PF1 3
#define PF2 3
#define PF3 0
#define PF4 0
#define PF5 0
#define PFM 0
#define WO_LATE 0
#define PF6 0
#define NW0 2
#define EARLY_C 0
#define STG1_PF 0
#define S2_LATE 1
#define TAIL_LATE 0
#define STG1_LATE 0
#define CLR_D 2
#define PADN 0
#define PFD 0
#define GO_EARLY 0
#define RF_FIRST 1
#define BX_I 5
#define NCH 4
#define TOP2 0
#define CX_I 13
#define ATT_LATE 0
#define V_FENCE 1
#define SELF_STAS 1
#define Q_FENCE 1
#define ND_K 3
#define TRACE(i)
#define TS(i)

__device__ __forceinline__ int rot_chunk(int c, int rank) {
  int G = c;
  if (c < 9) { G = c + 3 * rank; if (G >= 9) G -= 9; }
  return G;
}
__device__ __forceinline__ int wo_tile(int i, int rank) {
  if (i < 12) return 12 * rank + i;
  const int r = i - 12 + 9 * rank;
  return r < 16 ? 48 + r : 20 + r;
}
__device__ __forceinline__ void load_chunk(uint32_t dst, int seg, int G, uint32_t bar) {
  mbar_expect(bar, 4096);
  bulk_g2s(dst, g_h + (size_t)(seg * 16 + G) * 4096, 4096, bar);
}
__device__ __forceinline__ void load_red(uint32_t* v, const float* p) {
#pragma unroll
  for (int j = 0; j < 2; j++)
    asm volatile("ld.relaxed.gpu.global.v4.u32 {%0, %1, %2, %3}, [%4];"
                 : "=r"(v[4 * j]), "=r"(v[4 * j + 1]), "=r"(v[4 * j + 2]), "=r"(v[4 * j + 3]) : "l"(p + j * 256) : "memory");
}
__device__ __forceinline__ bool red_done(const uint32_t* v) { return __all_sync(0xffffffffu, (v[3] & v[7]) == 0x42000000u); }
__device__ __forceinline__ uint32_t finish_red(uint32_t* v, const float* p) {
  uint32_t tries = 0;
  if (__builtin_expect(!red_done(v), 0)) {
    do { if (++tries > 20000000u) __trap(); load_red(v, p); } while (!red_done(v));
  }
  return tries;
}
__device__ __forceinline__ void exp10(float* sv, const uint32_t* x) {
  constexpr float SC = 0.08838834764831845f * 1.4426950408889634f;
  uint32_t m2 = hmax2(hmax2(hmax2(x[0], x[1]), hmax2(x[2], x[3])), x[4]);
  m2 = hmax2(m2, __shfl_xor_sync(0xffffffffu, m2, 1));
  m2 = hmax2(m2, __shfl_xor_sync(0xffffffffu, m2, 2));
  const float nm = -fmaxf(bf_lo(m2), bf_hi(m2)) * SC;
#pragma unroll
  for (int j = 0; j < 5; j++) { sv[2 * j] = ex2(fmaf(bf_lo(x[j]), SC, nm)); sv[2 * j + 1] = ex2(fmaf(bf_hi(x[j]), SC, nm)); }
}

__device__ __forceinline__ uint32_t arm_size(int w, bool isC) {
  return w == 0 ? (isC ? 1280 : 640) : w == 1 ? (isC ? 0 : 2048) : w == 2 ? (isC ? 0 : 8192) : (isC ? 0 : 1792);
}
struct RDesc { uint64_t tok[32], tail_b[16], tail_a[32]; };

template <int WG>
__device__ __forceinline__ void r_main(const uint32_t (&W)[48][4], const RDesc& dsc, int head, uint32_t rank, int lane_, int w) {
  const uint32_t sb = (rank << 24) + 0x400, bars = sb + R_BAR;
  const uint32_t to1 = rank == 0 ? 2u << 24 : 0u - (1u << 24), to2 = rank == 2 ? 0u - (2u << 24) : 1u << 24;
  const bool isC = rank == 2;
  const int lane = opaque32(lane_), warp = WG * 4 + w;
  const int gl = rot_chunk(4 * (lane & 3) + w, rank);
  const int g0 = __shfl_sync(0xffffffffu, gl, 0), g1 = __shfl_sync(0xffffffffu, gl, 1), g2 = __shfl_sync(0xffffffffu, gl, 2);
  const uint32_t arm_bytes = arm_size(w, isC);

#define L16 opaque32(sb + opaque32(lane) * 16)
#define L8 opaque32(sb + opaque32(lane) * 8)
#define L4 opaque32(sb + opaque32(lane) * 4)
#define LV opaque32(sb + R_VT + ((opaque32(lane) >> 3) & 1) * 512 + (opaque32(lane) >> 4) * 128 + (opaque32(lane) & 7) * 16)
#define SLOT(st) opaque64(slot0 + ((st) & 3) * 12288 + ((st) & 4) * 32)
  float* const slot0 = opaque64(g_slot + (rank * 1024 + warp * 128 + lane) * 4);
  const uint32_t woa = opaque32(sb + R_WO + warp * 12288 + ((lane >> 4) * 8 + (lane & 7)) * 32 + ((((lane >> 3) ^ (lane >> 2)) & 1) << 4));
  const bool has_wo = WG == 0 || isC || w < 3;
  float acc[20];
  uint32_t pk[8] = {0u, 0u, 0u, 0u, 0u, 0u, 0u, 0u};

  auto forward = [&](auto rd, const uint32_t* v, int st, uint32_t tries) {
    constexpr int RD = decltype(rd)::value;
    uint32_t u[6];
#pragma unroll
    for (int j = 0; j < 6; j++) u[j] = movm(v[4 * (j / 3) + j % 3]);
    const bool all3 = RD == 0 || w < 3;
    if (RD == 0) {
      const uint32_t a = L16 + R_M1 + w * 768, a2 = L8 + R_M1 + 512 + w * 768;
      st_async4(a + to1 + 3072, u, bars + to1 + B_MB + 8); st_async2(a2 + to1 + 3072, u[4], u[5], bars + to1 + B_MB + 8);
      sts128(a, u[0], u[1], u[2], u[3]); sts64(a2, u[4], u[5]);
      __syncwarp();
      if (elect_one()) mbar_arrive(bars + B_MB);
      st_async4(a + to2 + 6144, u, bars + to2 + B_MB + 16); st_async2(a2 + to2 + 6144, u[4], u[5], bars + to2 + B_MB + 16);
    } else {
      const uint32_t a = L4 + R_M2 + rank * 2304 + w * 768;
#pragma unroll
      for (int j = 0; j < 6; j++) if (j < 2 || all3) st_async1(a + to1 + j * 128, u[j], bars + to1 + B_MB + 24);
#pragma unroll
      for (int j = 0; j < 6; j++) if (j < 2 || all3) st_async1(a + to2 + j * 128, u[j], bars + to2 + B_MB + 24);
      if (SELF_STAS) {
#pragma unroll
        for (int j = 0; j < 6; j++) if (j < 2 || all3) st_async1(a + j * 128, u[j], bars + B_MB + 24);
      } else {
#pragma unroll
        for (int j = 0; j < 6; j++) if (j < 2 || all3) sts32(a + j * 128, u[j]);
        __syncwarp();
        if (elect_one()) mbar_arrive(bars + B_MB + 24);
      }
    }
  };

  auto send_vt = [&]() {
    if (elect_one()) {
      const uint32_t src = sb + R_VT + warp * 1024;
      bulk_s2s(src + to1, src, 1024, bars + to1 + B_VT);
      bulk_s2s(src + to2, src, 1024, bars + to2 + B_VT);
    }
  };
  auto store_att = [&](int sg) {
    uint32_t* op = reinterpret_cast<uint32_t*>(g_att + (size_t)((sg >> 2) * 64 + head * 2 + rank) * 16384 + (2 * w * 16 + (sg & 3) * 4) * 128) + opaque32(lane);
#pragma unroll
    for (int j = 0; j < 8; j++) op[(j & 1) * 512 + (j >> 1) * 32] = pk[j];
  };

  if (WG == 0) bar_arrive<NB_G, 256>();
#pragma unroll 1
  for (int s = -1; s < NSEG - FIN; s++) {
    const uint32_t par = (s + 1) & 1;
    const uint32_t last = !FIN && s == NSEG - 1;
    TRACE(0);
    {
      float c[NCH][4];
      uint32_t b[3][6];
      const uint32_t ma = L16, m8 = L8;
#pragma unroll
      for (int i = 0; i < 18; i++) {
        if (i < 16) {
          if (i % 4 == 0 && !(i == 4 && TOP2)) mbar_wait(bars + B_MB + (i / 4) * 8, par ^ 1);
          if (i == 0 && TOP2) mbar_wait(bars + B_MB + 8, par ^ 1);
          if (i % 4 == 0) TRACE(1 + i / 4);
          if (i < 12) { lds128(b[i % 3], ma + R_M1 + i * 768); lds64(b[i % 3] + 4, m8 + R_M1 + 512 + i * 768); }
          else { ldsm4(b[i % 3], ma + R_M2 + 4096 + (i - 12) * 768); ldsm2(b[i % 3] + 4, ma + R_M2 + 4096 + 512 + (i - 12) * 768); }
          if (WG == 1 && i == BX_I) {
            bar_sync<NB_G, 256>();
            if (!last && elect_one()) load_chunk(sb + R_GB + w * 4096, s + 1, g0, bars + B_FB);
          }
          if (i == CX_I) {
            if (isC && s >= 0) send_vt();
            if (WG == 1 && ATT_LATE && !isC && s > 0) store_att(s - 1);
          }
          __syncwarp();
        }
        if (i >= 2) {
          const int j = i - 2;
#pragma unroll
          for (int q = 0; q < 3; q++) {
            const uint32_t* f = W[3 * j + q];
            if (3 * j + q < NCH) hmma0(c[3 * j + q], f[0], f[1], f[2], f[3], b[j % 3][2 * q], b[j % 3][2 * q + 1]);
            else hmma(c[(3 * j + q) % NCH], f[0], f[1], f[2], f[3], b[j % 3][2 * q], b[j % 3][2 * q + 1]);
          }
        }
        if (i == 14) zero_regs<16>(acc);
        if (i == 16) mbar_wait(bars + B_FA, last);
      }
#pragma unroll
      for (int j = 0; j < 4; j++) acc[16 + j] = NCH == 3 ? (c[0][j] + c[1][j]) + c[2][j] : (c[0][j] + c[1][j]) + (c[2][j] + c[NCH - 1][j]);
    }
    TRACE(5);
    bar_sync<NB_H, 256>();
    WG_FENCE();
#pragma unroll
    for (int k = 0; k < 16; k++) wg_ss40<0>(acc, dsc.tail_a[WG * 16 + k], dsc.tail_b[k]);
    WG_COMMIT();
    uint32_t vt[4][4];
    {
      const uint32_t a = opaque32(L4 + w * 256 + (isC ? WG * 1024 + R_VM : R_QK + 4096 + WG * 5120));
      const uint32_t qa = L16 + R_QK, xa = opaque32(LV + w * 2048 + (WG == 0 ? 0 : (opaque32(lane) & 8) * 64 + R_QK + 5120 - R_VT));
      const uint32_t d = opaque32(L4 + R_XS + rank * 640 + w * 256);
      if (s == 0) {
        mbar_wait_safe(bars + B_WO, 0);
        if (!GO_EARLY && WG == 1 && head == 0 && rank == 0 && w == 0 && elect_one()) red_add_u32(&g_flags[FL_GO], 1);
      }
      mbar_wait(bars + B_FB, last);
      if (WG == 0) mbar_wait(bars + B_VT, par);
      WG_WAIT(0);
      reg_fence<20>(acc);
      TRACE(6);
      const uint32_t p0 = pack2(acc[16], acc[17]), p1 = pack2(acc[18], acc[19]);
      sts32(a, p0); sts32(a + 128, p1);
      if (isC) {
        st_async1(a + to1, p0, bars + B_VM + to1); st_async1(a + to1 + 128, p1, bars + B_VM + to1);
        st_async1(a + to2, p0, bars + B_VM + to2); st_async1(a + to2 + 128, p1, bars + B_VM + to2);
      }
      if (WG == 0) {
        bar_arrive<NB_A, 256>();
        if (Q_FENCE && !isC) fence_async_smem();
#pragma unroll
        for (int i = 0; i < 4; i++) ldsm4(vt[i], xa + (i >> 1) * 1024 + (i & 1) * 256);
        bar_sync<NB_S, 256>();
      } else {
        bar_sync<NB_A, 256>();
        if (!isC) {
          if (w < 3) {
            uint32_t q[8], k[4][4];
            ldsm4t(q, qa + 4096); ldsm4t(k[0], xa); ldsm4t(k[1], xa + 256);
            ldsm4t(q + 4, qa + 4096 + 512); ldsm4t(k[2], xa + 512); ldsm4t(k[3], xa + 768);
            float x[4], y[4];
            hmma0(x, k[0][0], k[0][1], k[0][2], k[0][3], q[0], q[1]); hmma0(y, k[1][0], k[1][1], k[1][2], k[1][3], q[2], q[3]);
            hmma(x, k[2][0], k[2][1], k[2][2], k[2][3], q[4], q[5]); hmma(y, k[3][0], k[3][1], k[3][2], k[3][3], q[6], q[7]);
            const uint32_t s0 = pack2(x[0] + y[0], x[1] + y[1]), s1 = pack2(x[2] + y[2], x[3] + y[3]);
            st_async1(d + to1, s0, bars + B_XS + to1);
            st_async1(d + to2, s0, bars + B_XS + to2);
            if (w < 2) { st_async1(d + to1 + 128, s1, bars + B_XS + to1); st_async1(d + to2 + 128, s1, bars + B_XS + to2); sts32(d + 128, s1); }
            sts32(d, s0);
          }
        }
        bar_arrive<NB_S, 256>();
      }
    }
    if (WG == 1) {
      if (!last && elect_one()) load_chunk(sb + R_GA + w * 4096, s + 1, g1, bars + B_FA);
      {
        if (w > 0 && elect_one()) mbar_expect(bars + B_MB + 8 * w, w < 3 ? 3072 : SELF_STAS ? 28 * 256 : isC ? 18 * 256 : 19 * 256);
      }
      fence_async_smem();
      bar_sync<NB_B, 256>();
    }
    TRACE(7);
    WG_FENCE();
#pragma unroll
    for (int k = 0; k < 16; k++) wg_rs32<1>(acc, W[k][0], W[k][1], W[k][2], W[k][3], dsc.tok[16 + k]);
    WG_COMMIT();
    uint32_t wa[3][4];
    const uint32_t oxa = L16 + R_OX;
    if (WG == 0) {
      const uint32_t vma = oxa - (R_OX - R_VM) + w * 512, oa = opaque32(L4 + w * 512 + R_OX);
      TRACE(8);
      mbar_wait(bars + B_XS, par);
      TRACE(9);
      float sv[10];
      {
        uint32_t x[10];
        ldsm4t(x, oxa - (R_OX - R_XS)); ldsm4t(x + 4, oxa - (R_OX - R_XS) + 512); ldsm2t(x + 8, oxa - (R_OX - R_XS) + 1024);
        bar_arrive<NB_B, 256>();
#pragma unroll
        for (int j = 0; j < 5; j++) x[j] = hadd2(x[j], x[j + 5]);
        exp10(sv, x);
      }
      WG_WAIT(0);
      bar_arrive<NB_X, 256>();
      mbar_wait(bars + B_VM, par);
      uint32_t vm[4];
      ldsm4(vm, vma);
      uint32_t pb[5];
#pragma unroll
      for (int j = 0; j < 5; j++) pb[j] = pack2(sv[2 * j], sv[2 * j + 1]);
      TRACE(10);
      float o0[4], o1[4], sm[4];
      const uint32_t ONE = 0x3f803f80u;
      hmma0(o0, vt[0][0], vt[0][1], vt[0][2], vt[0][3], pb[0], pb[1]);
      hmma0(o1, vt[2][0], vt[2][1], vt[2][2], vt[2][3], pb[0], pb[1]);
      hmma0(sm, ONE, ONE, ONE, ONE, pb[0], pb[1]);
      hmma(sm, ONE, ONE, ONE, ONE, pb[2], pb[3]);
      hmma(o0, vt[1][0], vt[1][1], vt[1][2], vt[1][3], pb[2], pb[3]);
      hmma(o1, vt[3][0], vt[3][1], vt[3][2], vt[3][3], pb[2], pb[3]);
      hmma_k8(sm, ONE, ONE, pb[4]);
      hmma_k8(o0, vm[0], vm[1], pb[4]);
      hmma_k8(o1, vm[2], vm[3], pb[4]);
#pragma unroll
      for (int i = 0; i < 3; i++) ldsm4t(wa[i], woa + i * 4096);
      __syncwarp();
      const float i0 = rcp(sm[0]), i1 = rcp(sm[1]);
      sts32(oa, pack2(o0[0] * i0, o0[1] * i1)); sts32(oa + 128, pack2(o0[2] * i0, o0[3] * i1));
      sts32(oa + 256, pack2(o1[0] * i0, o1[1] * i1)); sts32(oa + 384, pack2(o1[2] * i0, o1[3] * i1));
      TRACE(11);
      bar_sync<NB_C, 128>();
    } else {
      if (!isC) {
        constexpr uint64_t dQ = mkdesc(0x400 + R_QK, 128, 1024, 0), dK = mkdesc(0x400 + R_QK + 5120, 128, 1024, 0);
        float sc[16];
        zero_regs<16>(sc);
        WG_FENCE();
#pragma unroll
        for (int k = 0; k < 4; k++) wg_ss32<1>(sc, dK + k * 16, dQ + k * 16);
        WG_COMMIT();
        const uint32_t top = rank == 0 ? to2 : to1, e = L4 + R_P + w * 256;
        WG_WAIT(0);
        bar_sync<NB_X, 256>();
        if (!last && elect_one()) load_chunk(sb + R_GB + w * 4096, s + 1, g2, bars + B_FB);
        reg_fence<16>(sc);
        if (w < 3) {
#pragma unroll
          for (int j = 0; j < 8; j++) {
            if ((j & 1) ? (j > 1 && (w == 0 || (w == 1 && j == 7))) : (j >= 4 || w != 1)) {
              const uint32_t t = pack2(sc[2 * j], sc[2 * j + 1]), o = (j >> 1) * 768 + (j & 1) * 128;
              st_async1(e + top + 3072 + o, t, bars + top + B_TS);
              sts32(e + o, t);
            }
          }
          __syncwarp();
          if (elect_one()) mbar_arrive(bars + B_TS);
        }
      } else {
        WG_WAIT(0);
        bar_sync<NB_X, 256>();
        if (!last && elect_one()) load_chunk(sb + R_GB + w * 4096, s + 1, g2, bars + B_FB);
      }
      TRACE(8);
      mbar_wait(bars + B_FA, 1);
      TRACE(11);
    }
    if (has_wo) {
      float* rslot = SLOT(s);
      uint32_t ob[4][4];
      float c[3][4];
      if (WG == 1) {
#pragma unroll
        for (int i = 0; i < 3; i++) ldsm4t(wa[i], woa + i * 4096);
        bar_sync<NB_D, 256>();
      }
      ldsm4t(ob[0], oxa);
      __syncwarp();
#pragma unroll
      for (int k = 0; k < 8; k++) {
        uint32_t nx[3][4];
        if ((k & 1) == 0 && k < 6) { ldsm4t(ob[(k >> 1) + 1], oxa + ((k >> 1) + 1) * 512); __syncwarp(); }
#pragma unroll
        for (int i = 0; i < 3; i++) {
          const uint32_t* o = ob[k >> 1] + (k & 1) * 2;
          if (k < 7) { ldsm4t(nx[i], woa + i * 4096 + (k + 1) * 512); if (i == 2) __syncwarp(); }
          if (k == 0) hmma0(c[i], wa[i][0], wa[i][1], wa[i][2], wa[i][3], o[0], o[1]);
          else hmma(c[i], wa[i][0], wa[i][1], wa[i][2], wa[i][3], o[0], o[1]);
#pragma unroll
          for (int q = 0; q < 4; q++) if (k < 7) wa[i][q] = nx[i][q];
        }
        if (k == ND_K && WG == 0) bar_arrive<NB_D, 256>();
      }
      const float* cv = &c[0][0];
      uint32_t r[6];
#pragma unroll
      for (int j = 0; j < 6; j++) r[j] = pack2(cv[2 * j], cv[2 * j + 1]);
      asm volatile("{\n.reg .pred p;\nsetp.lt.s32 p, %8, 0;\n@p bra.uni SKIP;\n"
                   "red.relaxed.gpu.global.add.noftz.v4.bf16x2 [%0], {%1, %2, %3, %7};\n"
                   "red.relaxed.gpu.global.add.noftz.v4.bf16x2 [%0+1024], {%4, %5, %6, %7};\nSKIP:\n}"
                   :: "l"(rslot), "r"(r[0]), "r"(r[1]), "r"(r[2]), "r"(r[3]), "r"(r[4]), "r"(r[5]), "r"(0x3f800000), "r"(s) : "memory");
    } else {
      bar_arrive<NB_D, 256>();
      if ((s & 3) == 0) {
        fence_gpu();
        if (s > 0 && elect_one()) red_add_u32(&g_flags[FL_ATT + 2 * (s - 4)], 1);
      }
      if (PFD && head < 8 && (PFD > 90 || s + PFD < NSEG) && elect_one())
        asm volatile("cp.async.bulk.prefetch.L2.global [%0], 4096;" :: "l"(g_h + (size_t)((PFD > 90 ? 0 : s + PFD) * 16 + head * 2 + rank) * 4096) : "memory");
      if (rank == 0 || head < 16)
        reinterpret_cast<uint4*>(g_slot)[((s + CLR_D) & 3) * 3072 + ((s + CLR_D) & 4) * 8 + rank * 2048 + head * 64 + opaque32(lane)] = make_uint4(0, 0, 0, 0);
    }
    const uint32_t t_red = clk32();
    uint32_t v[8];
    const float* slot = SLOT(s);
    TRACE(13);
    if (WG == 0) {
      if (!isC) {
        const int ln = opaque32(lane), kg = w - (ln >> 3);
        const uint32_t r16 = sb + R_P + w * 768 + (ln & 7) * 16;
        const uint32_t ta = r16 + (kg >= 0 ? kg * 128 : 640);
        const int dg = (ln >> 2) - 2 * (ln & 3);
        const uint32_t keep = dg > 0 ? 0xffffffffu : dg == 0 ? 0x0000ffffu : 0u;
        mbar_wait(bars + B_TS, par);
        uint32_t x[6], y[4];
        ldsm4t(x, ta); ldsm4t(y, ta + 3072); ldsm2t(x + 4, r16 + 512 + ((ln >> 3) & 1) * 3072);
#pragma unroll
        for (int j = 0; j < 5; j++) x[j] = hadd2(x[j], j < 4 ? y[j] : x[5]);
        x[0] = (x[0] & keep) | (0xff80ff80u & ~keep);
        float sv[10];
        exp10(sv, x);
        float sum = (((sv[0] + sv[1]) + (sv[2] + sv[3])) + ((sv[4] + sv[5]) + (sv[6] + sv[7]))) + (sv[8] + sv[9]);
        sum += __shfl_xor_sync(0xffffffffu, sum, 1);
        sum += __shfl_xor_sync(0xffffffffu, sum, 2);
        const float inv = rcp(sum);
#pragma unroll
        for (int j = 0; j < 5; j++) x[j] = pack2(sv[2 * j] * inv, sv[2 * j + 1] * inv);
        stsm4(r16 + (kg & 3) * 128, x);
        sts32(sb + ln * 4 + w * 768 + R_P + 512, x[4]);
        fence_async_smem();
        bar_arrive<NB_P, 256>();
      }
      while (clk32() - t_red < POLL_DELAY) {}
      load_red(v, slot);
      bar_sync<NB_E, 256>();
    } else {
      mbar_wait(bars + B_FB, 1);
    }
    TRACE(14);
    float ao[16];
    if (WG == 1) zero_regs<16>(ao);
    WG_FENCE();
#pragma unroll
    for (int k = 0; k < 32; k++) {
      if (WG == 0 && k == 16) WG_COMMIT();
      wg_rs32<1>(acc, W[16 + k][0], W[16 + k][1], W[16 + k][2], W[16 + k][3], dsc.tok[k]);
    }
    WG_COMMIT();
    TRACE(12);
    if (WG == 1) {
      if (!isC) {
        constexpr uint64_t dP = mkdesc(0x400 + R_P, 128, 768, 0);
        const uint64_t dV = mkdesc(0x400 + R_VT, 128, 512, 0) + rank * 256, dM = mkdesc(0x400 + R_VM, 0, 128, 0) + rank * 64;
        bar_sync<NB_P, 256>();
        WG_FENCE();
        wg_ss32<0>(ao, dV, dP); wg_ss32<0>(ao, dV + 16, dP + 16); wg_ss32<0>(ao, dM, dP + 32);
        WG_COMMIT();
      }
      bar_arrive<NB_E, 256>();
      if (elect_one()) mbar_expect(bars + B_XS + 8 * w, arm_bytes);
      while (clk32() - t_red < POLL_DELAY1) {}
      load_red(v, slot);
      bar_arrive<NB_W0, 128>();
    } else {
      WG_WAIT(1);
      bar_arrive<NB_F, 256>();
      sched_fence(head, 100);
      v[3] = opaque32(v[3]);
      const uint32_t tries = finish_red(v, slot);
      forward(std::integral_constant<int, 0>(), v, s, tries);
      TRACE(16);
    }
    WG_WAIT(0);
    reg_fence<16>(acc);
    if (WG == 0) bar_arrive<NB_G, 256>();
    TRACE(15);
    {
      uint32_t pq[8];
#pragma unroll
      for (int j = 0; j < 8; j++) pq[j] = pack2(acc[2 * j], acc[2 * j + 1]);
      if (WG == 1) {
        reg_fence<16>(ao);
#pragma unroll
        for (int j = 0; j < 8; j++) pk[j] = pack2(ao[2 * j], ao[2 * j + 1]);
      }
      if (!isC) {
        const uint32_t q = L4 + w * 256 + R_QK + WG * 5120;
#pragma unroll
        for (int j = 0; j < 8; j++) sts32(q + (j >> 1) * 1024 + (j & 1) * 128, pq[j]);
        if (WG == 1 && !ATT_LATE && s >= 0) store_att(s);
      } else {
        const uint32_t a = LV + warp * 1024;
        stsm4(a, pq); stsm4(a + 256, pq + 4);
      }
    }
    TRACE(17);
    if (WG == 1) {
      auto refill = [&]() {
        bar_sync<NB_F, 256>();
        if (s < NSEG - 2 && elect_one()) load_chunk(sb + R_GA + w * 4096, s + 2, 12 + w, bars + B_FA);
      };
      if (RF_FIRST) refill();
      if (has_wo) { v[3] = opaque32(v[3]); const uint32_t tries = finish_red(v, slot); forward(std::integral_constant<int, 1>(), v, s, tries); }
      if (!RF_FIRST) refill();
      TRACE(16);
    }
    if (isC && V_FENCE) { fence_async_smem(); __syncwarp(); }
    TRACE(18);
  }
  {
    constexpr uint32_t par = NSEG & 1;
    if (WG == 1 || isC) {
      float c[NCH][4], m[4];
      uint32_t b[3][6];
      const uint32_t ma = L16, m8 = L8;
#pragma unroll
      for (int i = 0; i < 18; i++) {
        if (i < 16) {
          if (i % 4 == 0) mbar_wait(bars + B_MB + (i / 4) * 8, par ^ 1);
          if (i < 12) { lds128(b[i % 3], ma + R_M1 + i * 768); lds64(b[i % 3] + 4, m8 + R_M1 + 512 + i * 768); }
          else { ldsm4(b[i % 3], ma + R_M2 + 4096 + (i - 12) * 768); ldsm2(b[i % 3] + 4, ma + R_M2 + 4096 + 512 + (i - 12) * 768); }
          if (i == CX_I && isC) send_vt();
          __syncwarp();
        }
        if (i >= 2) {
          const int j = i - 2;
#pragma unroll
          for (int q = 0; q < 3; q++) {
            const uint32_t* f = W[3 * j + q];
            if (3 * j + q < NCH) hmma0(c[3 * j + q], f[0], f[1], f[2], f[3], b[j % 3][2 * q], b[j % 3][2 * q + 1]);
            else hmma(c[(3 * j + q) % NCH], f[0], f[1], f[2], f[3], b[j % 3][2 * q], b[j % 3][2 * q + 1]);
          }
        }
      }
#pragma unroll
      for (int j = 0; j < 4; j++) m[j] = NCH == 3 ? (c[0][j] + c[1][j]) + c[2][j] : (c[0][j] + c[1][j]) + (c[2][j] + c[NCH - 1][j]);
      if (isC) bar_sync<NB_H, 256>();
      WG_FENCE();
#pragma unroll
      for (int k = 0; k < 16; k++) wg_ss8(m, dsc.tail_a[WG * 16 + k], dsc.tail_b[k] + 1024);
      WG_COMMIT();
      const uint32_t a = opaque32(L4 + w * 256 + (isC ? WG * 1024 + R_VM : R_QK + 4096 + WG * 5120));
      WG_WAIT(0);
      reg_fence<4>(m);
      const uint32_t p0 = pack2(m[0], m[1]), p1 = pack2(m[2], m[3]);
      if (isC) {
        st_async1(a + to1, p0, bars + B_VM + to1); st_async1(a + to1 + 128, p1, bars + B_VM + to1);
        st_async1(a + to2, p0, bars + B_VM + to2); st_async1(a + to2 + 128, p1, bars + B_VM + to2);
      } else {
        sts32(a, p0); sts32(a + 128, p1);
      }
    }
    if (WG == 1) bar_sync<NB_G, 256>();
    if (isC) {
      asm volatile("barrier.cluster.arrive.relaxed.aligned;" ::: "memory");
    } else if (WG == 1) {
      constexpr uint64_t dQ = mkdesc(0x400 + R_QK, 128, 1024, 0), dK = mkdesc(0x400 + R_QK + 5120, 128, 1024, 0);
      float sc[16];
      zero_regs<16>(sc);
      fence_async_smem();
      bar_sync<NB_B, 256>();
      WG_FENCE();
#pragma unroll
      for (int k = 0; k < 4; k++) wg_ss32<1>(sc, dK + k * 16, dQ + k * 16);
      WG_COMMIT();
      const uint32_t top = rank == 0 ? to2 : to1, e = L4 + R_P + w * 256;
      WG_WAIT(0);
      reg_fence<16>(sc);
      if (w < 3) {
#pragma unroll
        for (int j = 0; j < 8; j++) {
          if ((j & 1) ? (j > 1 && (w == 0 || (w == 1 && j == 7))) : (j >= 4 || w != 1)) {
            const uint32_t t = pack2(sc[2 * j], sc[2 * j + 1]), o = (j >> 1) * 768 + (j & 1) * 128;
            st_async1(e + top + 3072 + o, t, bars + top + B_TS);
            sts32(e + o, t);
          }
        }
        __syncwarp();
        if (elect_one()) mbar_arrive(bars + B_TS);
      }
      constexpr uint64_t dP = mkdesc(0x400 + R_P, 128, 768, 0);
      const uint64_t dV = mkdesc(0x400 + R_VT, 128, 512, 0) + rank * 256, dM = mkdesc(0x400 + R_VM, 0, 128, 0) + rank * 64;
      float ao[16];
      zero_regs<16>(ao);
      mbar_wait(bars + B_VT, par);
      mbar_wait(bars + B_VM, par);
      asm volatile("barrier.cluster.arrive.relaxed.aligned;" ::: "memory");
      bar_sync<NB_P, 256>();
      WG_FENCE();
      wg_ss32<0>(ao, dV, dP); wg_ss32<0>(ao, dV + 16, dP + 16); wg_ss32<0>(ao, dM, dP + 32);
      WG_COMMIT();
      WG_WAIT(0);
      reg_fence<16>(ao);
#pragma unroll
      for (int j = 0; j < 8; j++) pk[j] = pack2(ao[2 * j], ao[2 * j + 1]);
      store_att(NSEG - 1);
      bar_sync<NB_C, 128>();
      if (w == 0 && elect_one()) { fence_gpu(); red_add_u32(&g_flags[FL_ATT + 8 * 15], 1); }
    } else {
      fence_async_smem();
      bar_arrive<NB_B, 256>();
      const int ln = opaque32(lane), kg = w - (ln >> 3);
      const uint32_t r16 = sb + R_P + w * 768 + (ln & 7) * 16;
      const uint32_t ta = r16 + (kg >= 0 ? kg * 128 : 640);
      const int dg = (ln >> 2) - 2 * (ln & 3);
      const uint32_t keep = dg > 0 ? 0xffffffffu : dg == 0 ? 0x0000ffffu : 0u;
      mbar_wait(bars + B_TS, par);
      asm volatile("barrier.cluster.arrive.relaxed.aligned;" ::: "memory");
      uint32_t x[6], y[4];
      ldsm4t(x, ta); ldsm4t(y, ta + 3072); ldsm2t(x + 4, r16 + 512 + ((ln >> 3) & 1) * 3072);
#pragma unroll
      for (int j = 0; j < 5; j++) x[j] = hadd2(x[j], j < 4 ? y[j] : x[5]);
      x[0] = (x[0] & keep) | (0xff80ff80u & ~keep);
      float sv[10];
      exp10(sv, x);
      float sum = (((sv[0] + sv[1]) + (sv[2] + sv[3])) + ((sv[4] + sv[5]) + (sv[6] + sv[7]))) + (sv[8] + sv[9]);
      sum += __shfl_xor_sync(0xffffffffu, sum, 1);
      sum += __shfl_xor_sync(0xffffffffu, sum, 2);
      const float inv = rcp(sum);
#pragma unroll
      for (int j = 0; j < 5; j++) x[j] = pack2(sv[2 * j] * inv, sv[2 * j + 1] * inv);
      stsm4(r16 + (kg & 3) * 128, x);
      sts32(sb + ln * 4 + w * 768 + R_P + 512, x[4]);
      fence_async_smem();
      bar_arrive<NB_P, 256>();
    }
    asm volatile("barrier.cluster.wait.aligned;" ::: "memory");
  }
#undef L16
#undef L8
#undef L4
#undef SLOT
#undef LV
}

__global__ void __cluster_dims__(3, 1, 1) __launch_bounds__(256, 1)
kernel_R(const __grid_constant__ CUtensorMap tmq, const __grid_constant__ CUtensorMap tmk, const __grid_constant__ CUtensorMap tmv,
         const __grid_constant__ CUtensorMap tmo, const __grid_constant__ CUtensorMap tmm, const __nv_bfloat16* __restrict__ x,
         const __nv_bfloat16* __restrict__ mem0, const __nv_bfloat16* __restrict__ cvec, const __grid_constant__ RDesc dsc) {
  extern __shared__ __align__(1024) uint8_t smem[];
  const uint32_t sb = smem_u32(smem);
  uint32_t rank; asm("mov.u32 %0, %%cluster_ctarank;" : "=r"(rank));
  rank = __shfl_sync(0xffffffffu, rank, 0);
  const int cta = blockIdx.x, head = __shfl_sync(0xffffffffu, cta / 3, 0);
  const int tid = threadIdx.x, lane = tid & 31;
  const int warp = __shfl_sync(0xffffffffu, tid >> 5, 0);
  const int wg = warp >> 2, w = warp & 3;
  const uint32_t bars = sb + R_BAR;
  const CUtensorMap* tmw = rank == 2 ? &tmv : (wg == 0 ? &tmq : &tmk);
  const int fcol = head * 128 + (rank == 2 ? wg * 64 : (int)rank * 64);

  asm volatile("griddepcontrol.launch_dependents;");
  uint32_t W[48][4];
  {
    if (sb != (rank << 24) + 0x400) __trap();
    if (tid == 0) {
      sts64(bars + 248, rank, head);
      mbar_init(bars + B_MB, 4); mbar_init(bars + B_MB + 8, 1); mbar_init(bars + B_MB + 16, 1); mbar_init(bars + B_MB + 24, SELF_STAS ? 1 : rank == 2 ? 5 : 4);
      for (int i = B_XS; i <= B_X; i += 8) mbar_init(bars + i, i == B_FA || i == B_FB || (i == B_TS && rank < 2) ? 4 : 1);
      asm volatile("fence.mbarrier_init.release.cluster;" ::: "memory");
      fence_async_smem();
      if (PFM) asm volatile("prefetch.tensormap [%0];" :: "l"(&tmo) : "memory");
    }
    __syncthreads();
    asm volatile("barrier.cluster.arrive.relaxed.aligned;" ::: "memory");
    TS(0);
    const int nwm = rank == 0 ? 6 : 5, wm0 = rank == 0 ? 0 : 5 * rank + 1, nrg = cta < 64 ? 3 : 2;
    uint16_t cv[2] = {0, 0}, m0[6] = {0, 0, 0, 0, 0, 0};
    if (EARLY_C) {
      const uint16_t* cp = reinterpret_cast<const uint16_t*>(cvec) + wm0 * 64 + tid;
      cv[0] = __ldg(cp);
      if (tid + 256 < nwm * 64) cv[1] = __ldg(cp + 256);
      if (cta >= 72 && tid < 128 && (tid & 32)) {
        const uint16_t* mp = reinterpret_cast<const uint16_t*>(mem0) + 2 * (lane & 3) * D_ + (lane >> 2);
#pragma unroll
        for (int q = 0; q < 3; q++) {
          const int n = 3 * (tid >> 6) + q, col = wo_tile(3 * (cta & 7) + (n >> 1), (cta - 72) >> 3) * 16 + 8 * (n & 1);
          m0[2 * q] = __ldg(mp + col); m0[2 * q + 1] = __ldg(mp + col + D_);
        }
      }
    }
    if (elect_one()) {
      if (warp == 0) { mbar_expect(bars + B_WM, nwm * 8192); mbar_expect(bars + B_X, nrg * 16384); }
      if (warp < nwm) tma2d_once(sb + R_GA + warp * 8192, &tmm, head * 64, (wm0 + warp) * 64, bars + B_WM);
#pragma unroll 1
      for (int r = 0; r < nrg; r++) bulk_g2s(sb + R_TAIL + (r * 8 + warp) * 2064, x + (size_t)((cta + 96 * r) * 8 + warp) * D_, 2048, bars + B_X);
      if (w == 0) mbar_expect(bars + B_STG + wg * 16, 49152);
      if (w < NW0) {
        if (STG1_PF & 1) tma2d_prefetch(tmw, fcol, rot_chunk(w, rank) * 64);
        else tma2d_once(sb + R_WO + wg * 49152 + w * 8192, tmw, fcol, rot_chunk(w, rank) * 64, bars + B_STG + wg * 16);
      }
    }
    float* scr = reinterpret_cast<float*>(smem + R_VT);
    if (EARLY_C) {
#pragma unroll
      for (int j = 0; j < 2; j++) {
        const float c = bf_lo(cv[j]);
        if (tid + 256 * j < nwm * 64) scr[tid + 256 * j] = __bfloat162float(__float2bfloat16(c / (1.f + __expf(-c))));
      }
    } else {
#pragma unroll 1
      for (int i = tid; i < nwm * 64; i += 256) {
        const float c = __bfloat162float(cvec[wm0 * 64 + i]);
        scr[i] = __bfloat162float(__float2bfloat16(c / (1.f + __expf(-c))));
      }
    }
    if (tid < 128) {
      uint32_t e[4] = {0u, 0u, 0u, 0u};
      if (EARLY_C) {
        if (cta >= 72 && (tid & 32)) {
#pragma unroll
          for (int q = 0; q < 3; q++) e[q] = m0[2 * q] | (uint32_t)m0[2 * q + 1] << 16;
          e[3] = 0x42000000u;
        }
      } else if (cta >= 72 && (tid & 32)) {
        const uint16_t* mp = reinterpret_cast<const uint16_t*>(mem0) + 2 * (lane & 3) * D_ + (lane >> 2);
#pragma unroll
        for (int q = 0; q < 3; q++) {
          const int n = 3 * (tid >> 6) + q, col = wo_tile(3 * (cta & 7) + (n >> 1), (cta - 72) >> 3) * 16 + 8 * (n & 1);
          e[q] = mp[col] | (uint32_t)mp[col + D_] << 16;
        }
        e[3] = 0x42000000u;
      }
      reinterpret_cast<uint4*>(g_slot)[cta * 128 + tid] = make_uint4(e[0], e[1], e[2], e[3]);
    }
    __syncthreads();
    TS(1);
    mbar_wait_safe(bars + B_WM, 0);
    if (w < 4 - STG1_LATE && elect_one()) {
      if (STG1_PF & 2) tma2d_prefetch(tmw, fcol, rot_chunk(2 + w, rank) * 64);
      else tma2d_once(sb + R_WO + wg * 49152 + (2 + w) * 8192, tmw, fcol, rot_chunk(2 + w, rank) * 64, bars + B_STG + wg * 16);
    }
    if (NW0 < 2 && w >= NW0 && w < 2 && elect_one()) tma2d_once(sb + R_WO + wg * 49152 + w * 8192, tmw, fcol, rot_chunk(w, rank) * 64, bars + B_STG + wg * 16);
    {
      float a[8];
#pragma unroll
      for (int j = 0; j < 8; j++) a[j] = 0.f;
#pragma unroll 2
      for (int i = 0; i < 2 * nwm; i++) {
        uint32_t u[4];
        lds128(u, sb + R_GA + i * 4096 + tid * 16);
        const float sc = scr[i * 32 + (tid >> 3)];
#pragma unroll
        for (int j = 0; j < 4; j++) { a[2 * j] += sc * bf_lo(u[j]); a[2 * j + 1] += sc * bf_hi(u[j]); }
      }
#pragma unroll
      for (int j = 0; j < 8; j++) { a[j] += __shfl_xor_sync(0xffffffffu, a[j], 8); a[j] += __shfl_xor_sync(0xffffffffu, a[j], 16); }
      if (lane < 8) {
        sts128(sb + R_VT + 1536 + warp * 256 + lane * 32, __float_as_uint(a[0]), __float_as_uint(a[1]), __float_as_uint(a[2]), __float_as_uint(a[3]));
        sts128(sb + R_VT + 1552 + warp * 256 + lane * 32, __float_as_uint(a[4]), __float_as_uint(a[5]), __float_as_uint(a[6]), __float_as_uint(a[7]));
      }
    }
    __syncthreads();
    TS(2);
    if (warp == 7) {
      float t0 = 0.f, t1 = 0.f;
#pragma unroll
      for (int i = 0; i < 8; i++) { float t[2]; lds64f(t, sb + R_VT + 1536 + i * 256 + lane * 8); t0 += t[0]; t1 += t[1]; }
      reinterpret_cast<float2*>(g_modp + rank * 2048 + head * 64)[lane] = make_float2(t0, t1);
      fence_gpu();
      __syncwarp();
      if (lane == 0) red_add_u32(&g_flags[FL_S1], 1);
      __syncwarp();
    }
    mbar_wait_safe(bars + B_X, 0);
#pragma unroll 1
    for (int r = 0; r < nrg; r++) {
      float f[32];
#pragma unroll
      for (int i = 0; i < 4; i++) {
        uint32_t u[4];
        lds128(u, sb + R_TAIL + (r * 8 + warp) * 2064 + i * 512 + lane * 16);
#pragma unroll
        for (int j = 0; j < 4; j++) { f[8 * i + 2 * j] = bf_lo(u[j]); f[8 * i + 2 * j + 1] = bf_hi(u[j]); }
      }
      float t = 0.f;
#pragma unroll
      for (int i = 0; i < 32; i++) t += f[i];
#pragma unroll
      for (int o = 1; o < 32; o <<= 1) t += __shfl_xor_sync(0xffffffffu, t, o);
      const float mean = t * (1.f / D_);
      t = 0.f;
#pragma unroll
      for (int i = 0; i < 32; i++) t = fmaf(f[i] - mean, f[i] - mean, t);
#pragma unroll
      for (int o = 1; o < 32; o <<= 1) t += __shfl_xor_sync(0xffffffffu, t, o);
      const float rstd = rsqrtf(t * (1.f / D_) + 1e-5f);
      if (lane == 0) sts64(sb + R_VT + 3584 + (r * 8 + warp) * 8, __float_as_uint(rstd), __float_as_uint(-mean * rstd));
    }
    TS(3);
    if (STG1_LATE && w >= 4 - STG1_LATE && elect_one()) tma2d_once(sb + R_WO + wg * 49152 + (2 + w) * 8192, tmw, fcol, rot_chunk(2 + w, rank) * 64, bars + B_STG + wg * 16);
    if (w < PF1 && elect_one()) tma2d_prefetch(tmw, fcol, rot_chunk(6 + w, rank) * 64);
    if (tid == 0) wait_flag(&g_flags[FL_S1], 96);
    __syncthreads();
    TS(4);
    {
      float4 p[6];
#pragma unroll
      for (int i = 0; i < 6; i++) p[i] = __ldcg(reinterpret_cast<const float4*>(g_modp + (i >> 1) * 2048) + 2 * tid + (i & 1));
      if (w < PF2 && elect_one()) tma2d_prefetch(tmw, fcol, (9 + w) * 64);
      if (w + 4 < PF2 && elect_one()) tma2d_prefetch(tmw, fcol, (13 + w) * 64);
      sts128(sb + R_VT + 5120 + tid * 16, pack2(p[0].x + p[2].x + p[4].x, p[0].y + p[2].y + p[4].y), pack2(p[0].z + p[2].z + p[4].z, p[0].w + p[2].w + p[4].w),
             pack2(p[1].x + p[3].x + p[5].x, p[1].y + p[3].y + p[5].y), pack2(p[1].z + p[3].z + p[5].z, p[1].w + p[3].w + p[5].w));
      if (STG1_PF && elect_one()) {
        if (STG1_PF & 2) tma2d_once(sb + R_WO + wg * 49152 + (2 + w) * 8192, tmw, fcol, rot_chunk(2 + w, rank) * 64, bars + B_STG + wg * 16);
        if ((STG1_PF & 1) && w < 2) tma2d_once(sb + R_WO + wg * 49152 + w * 8192, tmw, fcol, rot_chunk(w, rank) * 64, bars + B_STG + wg * 16);
      }
    }
    __syncthreads();
#pragma unroll 2
    for (int it = 0; it < 4 * nrg; it++) {
      const int r = it >> 2, rg = cta + 96 * r, c = 16 * warp + (lane >> 3) + 4 * (it & 3);
      uint32_t a[4], b[4], u[4], o[4];
      float t[2];
      lds128(u, sb + R_TAIL + (r * 8 + (lane & 7)) * 2064 + c * 16);
      lds128(a, sb + R_VT + 5120 + c * 16); lds128(b, sb + R_VT + 7168 + c * 16);
      lds64f(t, sb + R_VT + 3584 + (r * 8 + (lane & 7)) * 8);
#pragma unroll
      for (int j = 0; j < 4; j++)
        o[j] = pack2(fmaf(fmaf(bf_lo(u[j]), t[0], t[1]), 1.f + bf_lo(b[j]), bf_lo(a[j])), fmaf(fmaf(bf_hi(u[j]), t[0], t[1]), 1.f + bf_hi(b[j]), bf_hi(a[j])));
      *reinterpret_cast<uint4*>(g_h + (size_t)(rg >> 2) * 65536 + (lane & 7) * 16 + (c & 7) * 128 +
                                (c < 96 ? (c >> 3) * 4096 + (rg & 3) * 1024 : 49152 + (rg & 3) * 4096 + ((c >> 3) - 12) * 1024)) =
          make_uint4(o[0], o[1], o[2], o[3]);
    }
    TS(5);
    __syncthreads();
    TS(6);
    if (w < PF3 && elect_one()) tma2d_once(sb + R_TAIL + warp * 8192, tmw, fcol, 768 + w * 64, bars + B_TAIL);
    if (w < PF6 && elect_one()) tma2d_prefetch(tmw, fcol, 768 + w * 64);
    if (warp == 3 && lane == 0) { fence_gpu(); red_add_u32(&g_flags[FL_S2], 1); }
    __syncwarp();

    const uint32_t a0 = opaque32(sb + R_WO + wg * 49152 + ((lane >> 4) * 8 + (lane & 7)) * 128 + (((2 * w + ((lane >> 3) & 1)) ^ (lane & 7)) << 4));
    mbar_wait_safe(bars + B_STG + wg * 16, 0);
    TS(7);
#pragma unroll
    for (int i = 0; i < 24; i++) ldsm4t(W[i], a0 + i * 2048);
    if (!S2_LATE && tid == 0) wait_flag(&g_flags[FL_S2], 96);
    __syncthreads();
    if (!S2_LATE) asm volatile("fence.proxy.async.global;" ::: "memory");
    if (elect_one()) {
      if (!S2_LATE && wg == 0) load_chunk(sb + R_GA + w * 4096, 0, 12 + w, bars + B_FA);
      if (w == 0) mbar_expect(bars + B_STG + wg * 16 + 8, 49152);
#pragma unroll 1
      for (int c = w; c < 6; c += 4) tma2d_once(sb + R_WO + wg * 49152 + c * 8192, tmw, fcol, rot_chunk(6 + c, rank) * 64, bars + B_STG + wg * 16 + 8);
      if (warp == 0) mbar_expect(bars + B_TAIL, 65536);
      if (w >= PF3 && w < 4 - TAIL_LATE) tma2d_once(sb + R_TAIL + warp * 8192, tmw, fcol, 768 + w * 64, bars + B_TAIL);
      if (wg == 1) mbar_expect(bars + B_XS + 8 * w, w == 2 ? 0 : arm_size(w, rank == 2));
#pragma unroll 1
      for (int i = warp; i < PF4; i += 8) tma2d_prefetch(&tmo, 16 * wo_tile(i, rank), head * 128);
    }
    TS(8);
    if (S2_LATE && tid == 0) wait_flag(&g_flags[FL_S2], 96);
    mbar_wait_safe(bars + B_STG + wg * 16 + 8, 0);
    TS(9);
    if (TAIL_LATE && w >= 4 - TAIL_LATE && elect_one()) tma2d_once(sb + R_TAIL + warp * 8192, tmw, fcol, 768 + w * 64, bars + B_TAIL);
    if (PF5 && elect_one()) {
#pragma unroll 1
      for (int i = warp; i < min(PF5, rank == 2 ? 22 : 21); i += 8) tma2d_prefetch(&tmo, 16 * wo_tile(i, rank), head * 128);
    }
#pragma unroll
    for (int i = 0; i < 24; i++) ldsm4t(W[24 + i], a0 + i * 2048);
    __syncthreads();
    if (S2_LATE) {
      asm volatile("fence.proxy.async.global;" ::: "memory");
      if (wg == 0 && elect_one()) load_chunk(sb + R_GA + w * 4096, 0, 12 + w, bars + B_FA);
    }
    auto load_wo = [&]() {
      if (elect_one()) {
        const int n = rank == 2 ? 22 : 21;
        if (warp == 0) mbar_expect(bars + B_WO, n * 4096);
#pragma unroll 1
        for (int i = warp; i < n; i += 8) tma2d(sb + R_WO + i * 4096, &tmo, 16 * wo_tile(i, rank), head * 128, bars + B_WO);
      }
    };
    if (!WO_LATE) load_wo();
    sts32(sb + R_P + warp * 768 + 640 + lane * 4, wg == 0 ? 0u : 0xff80ff80u);
    mbar_wait_safe(bars + B_TAIL, 0);
    if (GO_EARLY && cta == GO_EARLY - 1 && tid == 0) red_add_u32(&g_flags[FL_GO], 1);
    asm volatile("barrier.cluster.wait.aligned;\nbarrier.cluster.arrive.relaxed.aligned;\nbarrier.cluster.wait.aligned;" ::: "memory");
    if (WO_LATE) load_wo();
  }
  uint32_t rh[2];
  lds64(rh, bars + 248);
  rh[0] = __shfl_sync(0xffffffffu, rh[0], 0); rh[1] = __shfl_sync(0xffffffffu, rh[1], 0);
  if (wg == 0) r_main<0>(W, dsc, rh[1], rh[0], lane, w);
  else r_main<1>(W, dsc, rh[1], rh[0], lane, w);
}

template <int TA, bool FIRST> __device__ __forceinline__ void wg_ss256(float* d, uint64_t a, uint64_t b) {
  if (FIRST)
    asm volatile("wgmma.mma_async.sync.aligned.m64n256k16.f32.bf16.bf16 {%0,%1,%2,%3,%4,%5,%6,%7,%8,%9,%10,%11,%12,%13,%14,%15,%16,%17,%18,%19,%20,%21,%22,%23,%24,%25,%26,%27,%28,%29,%30,%31,%32,%33,%34,%35,%36,%37,%38,%39,%40,%41,%42,%43,%44,%45,%46,%47,%48,%49,%50,%51,%52,%53,%54,%55,%56,%57,%58,%59,%60,%61,%62,%63,%64,%65,%66,%67,%68,%69,%70,%71,%72,%73,%74,%75,%76,%77,%78,%79,%80,%81,%82,%83,%84,%85,%86,%87,%88,%89,%90,%91,%92,%93,%94,%95,%96,%97,%98,%99,%100,%101,%102,%103,%104,%105,%106,%107,%108,%109,%110,%111,%112,%113,%114,%115,%116,%117,%118,%119,%120,%121,%122,%123,%124,%125,%126,%127}, %128, %129, 0, 1, 1, %130, 1;"
               : "=f"(d[0]), "=f"(d[1]), "=f"(d[2]), "=f"(d[3]), "=f"(d[4]), "=f"(d[5]), "=f"(d[6]), "=f"(d[7]),
                 "=f"(d[8]), "=f"(d[9]), "=f"(d[10]), "=f"(d[11]), "=f"(d[12]), "=f"(d[13]), "=f"(d[14]), "=f"(d[15]),
                 "=f"(d[16]), "=f"(d[17]), "=f"(d[18]), "=f"(d[19]), "=f"(d[20]), "=f"(d[21]), "=f"(d[22]), "=f"(d[23]),
                 "=f"(d[24]), "=f"(d[25]), "=f"(d[26]), "=f"(d[27]), "=f"(d[28]), "=f"(d[29]), "=f"(d[30]), "=f"(d[31]),
                 "=f"(d[32]), "=f"(d[33]), "=f"(d[34]), "=f"(d[35]), "=f"(d[36]), "=f"(d[37]), "=f"(d[38]), "=f"(d[39]),
                 "=f"(d[40]), "=f"(d[41]), "=f"(d[42]), "=f"(d[43]), "=f"(d[44]), "=f"(d[45]), "=f"(d[46]), "=f"(d[47]),
                 "=f"(d[48]), "=f"(d[49]), "=f"(d[50]), "=f"(d[51]), "=f"(d[52]), "=f"(d[53]), "=f"(d[54]), "=f"(d[55]),
                 "=f"(d[56]), "=f"(d[57]), "=f"(d[58]), "=f"(d[59]), "=f"(d[60]), "=f"(d[61]), "=f"(d[62]), "=f"(d[63]),
                 "=f"(d[64]), "=f"(d[65]), "=f"(d[66]), "=f"(d[67]), "=f"(d[68]), "=f"(d[69]), "=f"(d[70]), "=f"(d[71]),
                 "=f"(d[72]), "=f"(d[73]), "=f"(d[74]), "=f"(d[75]), "=f"(d[76]), "=f"(d[77]), "=f"(d[78]), "=f"(d[79]),
                 "=f"(d[80]), "=f"(d[81]), "=f"(d[82]), "=f"(d[83]), "=f"(d[84]), "=f"(d[85]), "=f"(d[86]), "=f"(d[87]),
                 "=f"(d[88]), "=f"(d[89]), "=f"(d[90]), "=f"(d[91]), "=f"(d[92]), "=f"(d[93]), "=f"(d[94]), "=f"(d[95]),
                 "=f"(d[96]), "=f"(d[97]), "=f"(d[98]), "=f"(d[99]), "=f"(d[100]), "=f"(d[101]), "=f"(d[102]), "=f"(d[103]),
                 "=f"(d[104]), "=f"(d[105]), "=f"(d[106]), "=f"(d[107]), "=f"(d[108]), "=f"(d[109]), "=f"(d[110]), "=f"(d[111]),
                 "=f"(d[112]), "=f"(d[113]), "=f"(d[114]), "=f"(d[115]), "=f"(d[116]), "=f"(d[117]), "=f"(d[118]), "=f"(d[119]),
                 "=f"(d[120]), "=f"(d[121]), "=f"(d[122]), "=f"(d[123]), "=f"(d[124]), "=f"(d[125]), "=f"(d[126]), "=f"(d[127])
               : "l"(a), "l"(b), "n"(TA));
  else
    asm volatile("wgmma.mma_async.sync.aligned.m64n256k16.f32.bf16.bf16 {%0,%1,%2,%3,%4,%5,%6,%7,%8,%9,%10,%11,%12,%13,%14,%15,%16,%17,%18,%19,%20,%21,%22,%23,%24,%25,%26,%27,%28,%29,%30,%31,%32,%33,%34,%35,%36,%37,%38,%39,%40,%41,%42,%43,%44,%45,%46,%47,%48,%49,%50,%51,%52,%53,%54,%55,%56,%57,%58,%59,%60,%61,%62,%63,%64,%65,%66,%67,%68,%69,%70,%71,%72,%73,%74,%75,%76,%77,%78,%79,%80,%81,%82,%83,%84,%85,%86,%87,%88,%89,%90,%91,%92,%93,%94,%95,%96,%97,%98,%99,%100,%101,%102,%103,%104,%105,%106,%107,%108,%109,%110,%111,%112,%113,%114,%115,%116,%117,%118,%119,%120,%121,%122,%123,%124,%125,%126,%127}, %128, %129, 1, 1, 1, %130, 1;"
               : "+f"(d[0]), "+f"(d[1]), "+f"(d[2]), "+f"(d[3]), "+f"(d[4]), "+f"(d[5]), "+f"(d[6]), "+f"(d[7]),
                 "+f"(d[8]), "+f"(d[9]), "+f"(d[10]), "+f"(d[11]), "+f"(d[12]), "+f"(d[13]), "+f"(d[14]), "+f"(d[15]),
                 "+f"(d[16]), "+f"(d[17]), "+f"(d[18]), "+f"(d[19]), "+f"(d[20]), "+f"(d[21]), "+f"(d[22]), "+f"(d[23]),
                 "+f"(d[24]), "+f"(d[25]), "+f"(d[26]), "+f"(d[27]), "+f"(d[28]), "+f"(d[29]), "+f"(d[30]), "+f"(d[31]),
                 "+f"(d[32]), "+f"(d[33]), "+f"(d[34]), "+f"(d[35]), "+f"(d[36]), "+f"(d[37]), "+f"(d[38]), "+f"(d[39]),
                 "+f"(d[40]), "+f"(d[41]), "+f"(d[42]), "+f"(d[43]), "+f"(d[44]), "+f"(d[45]), "+f"(d[46]), "+f"(d[47]),
                 "+f"(d[48]), "+f"(d[49]), "+f"(d[50]), "+f"(d[51]), "+f"(d[52]), "+f"(d[53]), "+f"(d[54]), "+f"(d[55]),
                 "+f"(d[56]), "+f"(d[57]), "+f"(d[58]), "+f"(d[59]), "+f"(d[60]), "+f"(d[61]), "+f"(d[62]), "+f"(d[63]),
                 "+f"(d[64]), "+f"(d[65]), "+f"(d[66]), "+f"(d[67]), "+f"(d[68]), "+f"(d[69]), "+f"(d[70]), "+f"(d[71]),
                 "+f"(d[72]), "+f"(d[73]), "+f"(d[74]), "+f"(d[75]), "+f"(d[76]), "+f"(d[77]), "+f"(d[78]), "+f"(d[79]),
                 "+f"(d[80]), "+f"(d[81]), "+f"(d[82]), "+f"(d[83]), "+f"(d[84]), "+f"(d[85]), "+f"(d[86]), "+f"(d[87]),
                 "+f"(d[88]), "+f"(d[89]), "+f"(d[90]), "+f"(d[91]), "+f"(d[92]), "+f"(d[93]), "+f"(d[94]), "+f"(d[95]),
                 "+f"(d[96]), "+f"(d[97]), "+f"(d[98]), "+f"(d[99]), "+f"(d[100]), "+f"(d[101]), "+f"(d[102]), "+f"(d[103]),
                 "+f"(d[104]), "+f"(d[105]), "+f"(d[106]), "+f"(d[107]), "+f"(d[108]), "+f"(d[109]), "+f"(d[110]), "+f"(d[111]),
                 "+f"(d[112]), "+f"(d[113]), "+f"(d[114]), "+f"(d[115]), "+f"(d[116]), "+f"(d[117]), "+f"(d[118]), "+f"(d[119]),
                 "+f"(d[120]), "+f"(d[121]), "+f"(d[122]), "+f"(d[123]), "+f"(d[124]), "+f"(d[125]), "+f"(d[126]), "+f"(d[127])
               : "l"(a), "l"(b), "n"(TA));
}
template <int TA, bool FIRST> __device__ __forceinline__ void wg_ss128(float* d, uint64_t a, uint64_t b) {
  if (FIRST)
    asm volatile("wgmma.mma_async.sync.aligned.m64n128k16.f32.bf16.bf16 {%0,%1,%2,%3,%4,%5,%6,%7,%8,%9,%10,%11,%12,%13,%14,%15,%16,%17,%18,%19,%20,%21,%22,%23,%24,%25,%26,%27,%28,%29,%30,%31,%32,%33,%34,%35,%36,%37,%38,%39,%40,%41,%42,%43,%44,%45,%46,%47,%48,%49,%50,%51,%52,%53,%54,%55,%56,%57,%58,%59,%60,%61,%62,%63}, %64, %65, 0, 1, 1, %66, 1;"
               : "=f"(d[0]), "=f"(d[1]), "=f"(d[2]), "=f"(d[3]), "=f"(d[4]), "=f"(d[5]), "=f"(d[6]), "=f"(d[7]),
                 "=f"(d[8]), "=f"(d[9]), "=f"(d[10]), "=f"(d[11]), "=f"(d[12]), "=f"(d[13]), "=f"(d[14]), "=f"(d[15]),
                 "=f"(d[16]), "=f"(d[17]), "=f"(d[18]), "=f"(d[19]), "=f"(d[20]), "=f"(d[21]), "=f"(d[22]), "=f"(d[23]),
                 "=f"(d[24]), "=f"(d[25]), "=f"(d[26]), "=f"(d[27]), "=f"(d[28]), "=f"(d[29]), "=f"(d[30]), "=f"(d[31]),
                 "=f"(d[32]), "=f"(d[33]), "=f"(d[34]), "=f"(d[35]), "=f"(d[36]), "=f"(d[37]), "=f"(d[38]), "=f"(d[39]),
                 "=f"(d[40]), "=f"(d[41]), "=f"(d[42]), "=f"(d[43]), "=f"(d[44]), "=f"(d[45]), "=f"(d[46]), "=f"(d[47]),
                 "=f"(d[48]), "=f"(d[49]), "=f"(d[50]), "=f"(d[51]), "=f"(d[52]), "=f"(d[53]), "=f"(d[54]), "=f"(d[55]),
                 "=f"(d[56]), "=f"(d[57]), "=f"(d[58]), "=f"(d[59]), "=f"(d[60]), "=f"(d[61]), "=f"(d[62]), "=f"(d[63])
               : "l"(a), "l"(b), "n"(TA));
  else
    asm volatile("wgmma.mma_async.sync.aligned.m64n128k16.f32.bf16.bf16 {%0,%1,%2,%3,%4,%5,%6,%7,%8,%9,%10,%11,%12,%13,%14,%15,%16,%17,%18,%19,%20,%21,%22,%23,%24,%25,%26,%27,%28,%29,%30,%31,%32,%33,%34,%35,%36,%37,%38,%39,%40,%41,%42,%43,%44,%45,%46,%47,%48,%49,%50,%51,%52,%53,%54,%55,%56,%57,%58,%59,%60,%61,%62,%63}, %64, %65, 1, 1, 1, %66, 1;"
               : "+f"(d[0]), "+f"(d[1]), "+f"(d[2]), "+f"(d[3]), "+f"(d[4]), "+f"(d[5]), "+f"(d[6]), "+f"(d[7]),
                 "+f"(d[8]), "+f"(d[9]), "+f"(d[10]), "+f"(d[11]), "+f"(d[12]), "+f"(d[13]), "+f"(d[14]), "+f"(d[15]),
                 "+f"(d[16]), "+f"(d[17]), "+f"(d[18]), "+f"(d[19]), "+f"(d[20]), "+f"(d[21]), "+f"(d[22]), "+f"(d[23]),
                 "+f"(d[24]), "+f"(d[25]), "+f"(d[26]), "+f"(d[27]), "+f"(d[28]), "+f"(d[29]), "+f"(d[30]), "+f"(d[31]),
                 "+f"(d[32]), "+f"(d[33]), "+f"(d[34]), "+f"(d[35]), "+f"(d[36]), "+f"(d[37]), "+f"(d[38]), "+f"(d[39]),
                 "+f"(d[40]), "+f"(d[41]), "+f"(d[42]), "+f"(d[43]), "+f"(d[44]), "+f"(d[45]), "+f"(d[46]), "+f"(d[47]),
                 "+f"(d[48]), "+f"(d[49]), "+f"(d[50]), "+f"(d[51]), "+f"(d[52]), "+f"(d[53]), "+f"(d[54]), "+f"(d[55]),
                 "+f"(d[56]), "+f"(d[57]), "+f"(d[58]), "+f"(d[59]), "+f"(d[60]), "+f"(d[61]), "+f"(d[62]), "+f"(d[63])
               : "l"(a), "l"(b), "n"(TA));
}
template <int TA, bool FIRST> __device__ __forceinline__ void wg_ss64(float* d, uint64_t a, uint64_t b) {
  if (FIRST)
    asm volatile("wgmma.mma_async.sync.aligned.m64n64k16.f32.bf16.bf16 {%0,%1,%2,%3,%4,%5,%6,%7,%8,%9,%10,%11,%12,%13,%14,%15,%16,%17,%18,%19,%20,%21,%22,%23,%24,%25,%26,%27,%28,%29,%30,%31}, %32, %33, 0, 1, 1, %34, 1;"
               : "=f"(d[0]), "=f"(d[1]), "=f"(d[2]), "=f"(d[3]), "=f"(d[4]), "=f"(d[5]), "=f"(d[6]), "=f"(d[7]),
                 "=f"(d[8]), "=f"(d[9]), "=f"(d[10]), "=f"(d[11]), "=f"(d[12]), "=f"(d[13]), "=f"(d[14]), "=f"(d[15]),
                 "=f"(d[16]), "=f"(d[17]), "=f"(d[18]), "=f"(d[19]), "=f"(d[20]), "=f"(d[21]), "=f"(d[22]), "=f"(d[23]),
                 "=f"(d[24]), "=f"(d[25]), "=f"(d[26]), "=f"(d[27]), "=f"(d[28]), "=f"(d[29]), "=f"(d[30]), "=f"(d[31])
               : "l"(a), "l"(b), "n"(TA));
  else
    asm volatile("wgmma.mma_async.sync.aligned.m64n64k16.f32.bf16.bf16 {%0,%1,%2,%3,%4,%5,%6,%7,%8,%9,%10,%11,%12,%13,%14,%15,%16,%17,%18,%19,%20,%21,%22,%23,%24,%25,%26,%27,%28,%29,%30,%31}, %32, %33, 1, 1, 1, %34, 1;"
               : "+f"(d[0]), "+f"(d[1]), "+f"(d[2]), "+f"(d[3]), "+f"(d[4]), "+f"(d[5]), "+f"(d[6]), "+f"(d[7]),
                 "+f"(d[8]), "+f"(d[9]), "+f"(d[10]), "+f"(d[11]), "+f"(d[12]), "+f"(d[13]), "+f"(d[14]), "+f"(d[15]),
                 "+f"(d[16]), "+f"(d[17]), "+f"(d[18]), "+f"(d[19]), "+f"(d[20]), "+f"(d[21]), "+f"(d[22]), "+f"(d[23]),
                 "+f"(d[24]), "+f"(d[25]), "+f"(d[26]), "+f"(d[27]), "+f"(d[28]), "+f"(d[29]), "+f"(d[30]), "+f"(d[31])
               : "l"(a), "l"(b), "n"(TA));
}

constexpr int H_STAGE = 49152, H_NST = 4;
constexpr int H_STG = H_NST * H_STAGE;
constexpr int H_VEC = H_STG + 16384;
constexpr int H_BAR = H_VEC + 6144;
constexpr int H_SMEM = H_BAR + 256;
constexpr int HB_FULL = 0, HB_EMPTY = 32, HB_IFULL = 64, HB_IEMPTY = 80, HB_ITEM = 96, HB_INC = 104, HB_HAVE = 116, HB_NEXT = 160;
enum { IT_END = 0, IT_MOD = 1, IT_XT = 2, IT_OUT = 3, IT_UV = 4, IT_F1 = 5, IT_F2 = 6 };
constexpr int MAX_ITEMS = 1400;
#define D_MOD 4
#define D_UV 2
#define UV_WAIT 0
#define PF_MAPS 1
#define R_LATE 1
#define CH_FENCE 1
#define CH_FENCE1 1
#define N_UV1 20
#define FINE 1
#define B_EARLY 1
#define VEC_EARLY 1
#define HOLD 1
#define PEEK 4
#define ECL0 2
#define ECL1 6
constexpr uint32_t IT_GATHER = 0x80000000u;
__host__ __device__ __forceinline__ int split_tile(int type, int mt, int idx) { return ((type == IT_F2 ? 0 : mt >= 12 ? 4 : 8) + (mt & 3)) * 16 + idx; }
__device__ __forceinline__ int item_sz(uint32_t it) { return (it >> 13) & 3; }
struct HList { uint32_t n; uint32_t it[MAX_ITEMS]; };
__device__ __forceinline__ void item_deps(int type, int mt, int lane, int& f, uint32_t& target) {
  f = FL_GO; target = 1;
  if (type == IT_OUT) { f = lane == 0 ? FL_ATT + 8 * mt : lane == 1 ? FL_XT + 8 * mt : lane == 9 ? FL_MODA : FL_MOD; target = lane == 0 ? 64 : lane == 1 ? 2 : lane == 9 ? 8 : 16; }
  else if (type == IT_F1) { f = lane < 8 ? FL_OUT + 8 * mt + lane : FL_UV; target = lane < 8 ? 2 : 28; }
  else if (type == IT_F2) { f = lane < 8 ? FL_F1 + 8 * mt + lane : FL_MODB; target = 8; }
}
#define HT(i)

__device__ __forceinline__ uint32_t tile_lane(int warp, int lane) { return warp * 1024 + (lane >> 2) * 64 + (((lane & 3) ^ (lane >> 3)) << 4); }
__device__ __forceinline__ constexpr uint32_t tile_off(int c, int h) { return (c >> 1) * 16384 + (c & 1) * 8192 + h * 512; }

template <int BN, int TA, class PRE, class POST>
__device__ __forceinline__ void h_mainloop(float* acc, uint32_t sb, int nst, uint32_t& st, uint32_t& ph, int wg, bool leader, PRE pre, POST post) {
  constexpr int KS = BN == 64 ? 8 : 4;
  constexpr uint32_t BOFF = BN == 64 ? 32768 : 16384;
  const uint64_t da0 = TA ? mkdesc(sb + wg * 1024, 2048, 128, 0) : mkdesc(sb + wg * 4096, 16, 512, 2);
  auto release = [&](uint32_t s) { if (leader) mbar_arrive(sb + H_BAR + HB_EMPTY + s * 8); };
  const uint64_t db0 = mkdesc(sb + BOFF, 8192, 1024, 1);
  constexpr uint32_t kh = 512;
  uint32_t prev = 0;
  auto stage = [&](auto first) {
    constexpr bool FIRST = decltype(first)::value;
    mbar_wait(sb + H_BAR + HB_FULL + st * 8, ph);
    if (FIRST) HT(1);
    const uint64_t da = da0 + st * (H_STAGE >> 4), db = db0 + st * (H_STAGE >> 4);
    WG_FENCE();
#pragma unroll
    for (int k = 0; k < KS; k++) {
      const uint64_t a = da + (k >> 2) * 1024 + (TA ? (k & 3) * 256 : ((k >> 1) & 1) * kh + (k & 1) * 2), b = db + k * 128;
      if (FIRST && k == 0) { if (BN == 256) wg_ss256<TA, true>(acc, a, b); else if (BN == 128) wg_ss128<TA, true>(acc, a, b); else wg_ss64<TA, true>(acc, a, b); }
      else { if (BN == 256) wg_ss256<TA, false>(acc, a, b); else if (BN == 128) wg_ss128<TA, false>(acc, a, b); else wg_ss64<TA, false>(acc, a, b); }
    }
    WG_COMMIT();
  };
  stage(std::true_type());
  pre();
  prev = st;
  if (++st == H_NST) { st = 0; ph ^= 1; }
#pragma unroll 1
  for (int i = 1; i < nst; i++) {
    stage(std::false_type());
    WG_WAIT(1);
    release(prev);
    prev = st;
    if (++st == H_NST) { st = 0; ph ^= 1; }
  }
  post();
  WG_WAIT(0);
  HT(2);
  reg_fence<BN / 2>(acc);
  release(prev);
}

template <int BN, bool FINAL, class POST>
__device__ __forceinline__ void h_residual(uint32_t sb, uint32_t va, int mt, int n0, uint32_t& st, uint32_t& ph, int warp, int lane, __nv_bfloat16* out,
                                           POST post, int part = 0, int lgp = 0, bool gather = false) {
  const size_t toff = (size_t)(mt * 16 + (n0 >> 6)) * 16384 + tile_lane(warp, lane);
  uint4 r[BN / 16];
  auto load_r = [&]() {
#pragma unroll
    for (int i = 0; i < BN / 16; i++) r[i] = __ldcg(reinterpret_cast<const uint4*>(g_x1 + toff + tile_off(i >> 1, i & 1)));
  };
  const bool partial = BN == 64 && lgp > 0 && !gather;
  if (!R_LATE && !partial) load_r();
  float acc[BN / 2];
  h_mainloop<BN, FINAL ? 0 : 1>(acc, sb, ((FINAL ? 56 : 64) / (BN == 64 ? 2 : 1)) >> lgp, st, ph, warp >> 2, (warp & 3) == 0 && lane == 0,
                                [&]() { if (R_LATE && !partial) load_r(); }, post);
  if (BN == 64 && lgp > 0) {
    if (partial) {
      float4* ws = reinterpret_cast<float4*>(g_ws) + (size_t)split_tile(FINAL ? IT_F2 : IT_OUT, mt, n0 >> 6) * 8192 + part * 2048 + warp * 32 + lane;
#pragma unroll
      for (int i = 0; i < 8; i++) ws[i * 256] = make_float4(acc[4 * i], acc[4 * i + 1], acc[4 * i + 2], acc[4 * i + 3]);
      return;
    }
#pragma unroll 1
    for (int p = 1; p < (1 << lgp); p++) {
      mbar_wait(sb + H_BAR + HB_FULL + st * 8, ph);
#pragma unroll
      for (int i = 0; i < 8; i++) {
        float o[4];
        lds128f(o, sb + st * H_STAGE + i * 4096 + warp * 512 + lane * 16);
        acc[4 * i] += o[0]; acc[4 * i + 1] += o[1]; acc[4 * i + 2] += o[2]; acc[4 * i + 3] += o[3];
      }
      reg_fence<32>(acc);
      bar_sync<1, 256>();
      if ((warp & 3) == 0 && lane == 0) mbar_arrive(sb + H_BAR + HB_EMPTY + st * 8);
      if (++st == H_NST) { st = 0; ph ^= 1; }
    }
  }
  float sm[4] = {0.f, 0.f, 0.f, 0.f};
  const uint32_t stg = sb + H_STG + warp * 2048;
#pragma unroll
  for (int c = 0; c < BN / 32; c++) {
    uint32_t y[2][4] = {{r[2 * c].x, r[2 * c].y, r[2 * c].z, r[2 * c].w}, {r[2 * c + 1].x, r[2 * c + 1].y, r[2 * c + 1].z, r[2 * c + 1].w}}, z[2][4];
#pragma unroll
    for (int j = 0; j < 4; j++) {
      const uint32_t gt = lds32(va + c * 64 + j * 16 + (lane & 3) * 4);
      const uint32_t cb = FINAL ? 0 : lds32(va + 512 + c * 64 + j * 16 + (lane & 3) * 4);
#pragma unroll
      for (int h = 0; h < 2; h++) {
        const float* a = acc + c * 16 + j * 4 + h * 2;
        y[h][j] = pack2(fmaf(bf_lo(gt), a[0], bf_lo(y[h][j])), fmaf(bf_hi(gt), a[1], bf_hi(y[h][j])));
        if (!FINAL) {
          const float p = bf_lo(y[h][j]), q = bf_hi(y[h][j]);
          sm[2 * h] += p + q;
          sm[2 * h + 1] = fmaf(p, p, fmaf(q, q, sm[2 * h + 1]));
          z[h][j] = pack2(fmaf(p, bf_lo(cb), p), fmaf(q, bf_hi(cb), q));
        }
      }
    }
    if (!FINAL) {
#pragma unroll
      for (int h = 0; h < 2; h++) {
        const size_t o = toff + tile_off(c, h);
        *reinterpret_cast<uint4*>(g_x1 + o) = make_uint4(y[h][0], y[h][1], y[h][2], y[h][3]);
        *reinterpret_cast<uint4*>(g_h2 + o) = make_uint4(z[h][0], z[h][1], z[h][2], z[h][3]);
      }
    } else {
#pragma unroll
      for (int h = 0; h < 2; h++) stsm4(stg + (h * 8 + (lane & 7)) * 128 + ((((c & 1) * 4 + (lane >> 3)) ^ (lane & 7)) << 4), y[h]);
      if (c & 1) {
        __syncwarp();
#pragma unroll
        for (int j = 0; j < 4; j++) {
          const int rr = 4 * j + (lane >> 3);
          uint32_t v[4];
          lds128(v, stg + rr * 128 + (((lane & 7) ^ (rr & 7)) << 4));
          *reinterpret_cast<uint4*>(out + (size_t)(mt * 128 + warp * 16 + rr) * D_ + n0 + (c >> 1) * 64 + (lane & 7) * 8) = make_uint4(v[0], v[1], v[2], v[3]);
        }
        __syncwarp();
      }
    }
    if (CH_FENCE && c + 1 < BN / 32) sched_fence(lane, 100);
  }
  if (!FINAL) {
#pragma unroll
    for (int j = 0; j < 4; j++) { sm[j] += __shfl_xor_sync(0xffffffffu, sm[j], 1); sm[j] += __shfl_xor_sync(0xffffffffu, sm[j], 2); }
    const int t = lane & 3;
    const float sv = t == 0 ? sm[0] : t == 1 ? sm[1] : t == 2 ? sm[2] : sm[3];
    asm volatile("red.relaxed.gpu.global.add.f32 [%0], %1;" :: "l"(g_stat + (mt * 128 + warp * 16 + (t >> 1) * 8 + (lane >> 2)) * 2 + (t & 1)), "f"(sv) : "memory");
  }
}

__device__ __forceinline__ float silu_mul(float hg, float u) {
  float t; asm("tanh.approx.f32 %0, %1;" : "=f"(t) : "f"(hg));
  const float h = hg * u;
  return fmaf(h, t, h);
}

template <int BN>
__device__ __forceinline__ void h_swiglu(const float* acc, uint32_t va, int mt, int kb0, int warp, int lane) {
  uint8_t* ap = g_act + (size_t)(mt * 56 + kb0) * 16384 + tile_lane(warp, lane);
  float rs[2], nm[2], rh[2];
#pragma unroll
  for (int h = 0; h < 2; h++) {
    float t[2];
    lds64f(t, va + 2048 + (warp * 16 + h * 8 + (lane >> 2)) * 8);
    const float mean = t[0] * (1.f / D_);
    rs[h] = rsqrtf(fmaxf(t[1] * (1.f / D_) - mean * mean, 0.f) + 1e-5f);
    nm[h] = -mean * rs[h];
    rh[h] = 0.5f * rs[h];
  }
#pragma unroll
  for (int c = 0; c < BN / 64; c++) {
    uint32_t y[2][4];
#pragma unroll
    for (int j = 0; j < 4; j++) {
      const float* g = acc + 16 * c + 4 * j; const float* u = g + BN / 4;
      float p[4], q[4], o[4];
      lds128f(p, va + (4 * c + j) * 128 + (lane & 3) * 32); lds128f(q, va + (4 * c + j) * 128 + (lane & 3) * 32 + 16);
#pragma unroll
      for (int e = 0; e < 4; e++)
        o[e] = silu_mul(fmaf(rh[e >> 1], g[e], fmaf(nm[e >> 1], p[e & 1], p[2 + (e & 1)])), fmaf(rs[e >> 1], u[e], fmaf(nm[e >> 1], q[e & 1], q[2 + (e & 1)])));
      y[0][j] = pack2(o[0], o[1]); y[1][j] = pack2(o[2], o[3]);
    }
#pragma unroll
    for (int h = 0; h < 2; h++)
      *reinterpret_cast<uint4*>(ap + tile_off(c, h)) = make_uint4(y[h][0], y[h][1], y[h][2], y[h][3]);
    if (CH_FENCE1 && c + 1 < BN / 64) sched_fence(lane, 100);
  }
}

__global__ void __launch_bounds__(384, 1)
kernel_H(const __grid_constant__ CUtensorMap tmo, const __grid_constant__ CUtensorMap tm1, const __grid_constant__ CUtensorMap tm3,
         const __grid_constant__ CUtensorMap tm2, const __grid_constant__ CUtensorMap tmm, const __nv_bfloat16* __restrict__ x,
         const __nv_bfloat16* __restrict__ cvec, __nv_bfloat16* __restrict__ out, const __grid_constant__ HList list) {
  extern __shared__ __align__(1024) uint8_t smem[];
  constexpr uint32_t sb = 0x400, bars = sb + H_BAR;
  const int tid = threadIdx.x, lane = tid & 31;
  const int warp = __shfl_sync(0xffffffffu, tid >> 5, 0);
  if (tid == 0) {
    if (smem_u32(smem) != sb) __trap();
    for (int i = 0; i < H_NST; i++) { mbar_init(bars + HB_FULL + i * 8, 1); mbar_init(bars + HB_EMPTY + i * 8, 2); }
    for (int i = 0; i < 2; i++) { mbar_init(bars + HB_IFULL + i * 8, 1); mbar_init(bars + HB_IEMPTY + i * 8, 3); }
    mbar_init(bars + HB_NEXT, 1);
    fence_async_smem();
    if (PF_MAPS) {
      const CUtensorMap* maps[5] = {&tmm, &tm1, &tm3, &tmo, &tm2};
#pragma unroll
      for (int i = 0; i < 5; i++) asm volatile("prefetch.tensormap [%0];" :: "l"(maps[i]) : "memory");
    }
  }
  __syncthreads();
  if (warp >= 8) {
    asm volatile("setmaxnreg.dec.sync.aligned.u32 40;");
    if (warp == 8) {
      uint32_t st = 0, ph = 1;
#pragma unroll 1
      for (uint32_t n = 0;; n++) {
        mbar_wait(bars + HB_IFULL + (n & 1) * 8, (n >> 1) & 1);
        const uint32_t it = __shfl_sync(0xffffffffu, lds32(bars + HB_ITEM + (n & 1) * 4), 0);
        uint32_t have = __shfl_sync(0xffffffffu, lds32(bars + HB_HAVE + (n & 1) * 4), 0);
        if (elect_one()) mbar_arrive(bars + HB_IEMPTY + (n & 1) * 8);
        const int type = it & 7, mt = (it >> 3) & 15, idx = (it >> 7) & 63, sz = item_sz(it), part = (it >> 15) & 3, lgp = (it >> 17) & 3;
        if (type == IT_END) break;
        int f; uint32_t target, first = 0;
        item_deps(type, mt, opaque32(lane), f, target);
        if (type == IT_OUT) first = 3;
        const int gsh = type == IT_F1 ? 1 : type == IT_F2 ? 3 : 6;
        if (type >= IT_F1) first = FINE ? 1u << ((part * (56 >> lgp)) >> gsh) : type == IT_F1 ? 255u : 127u;
        auto need = [&](int g) {
          if (!((have >> g) & 1)) {
            if (lane == g) wait_flag2(&g_flags[f], target);
            __syncwarp();
            asm volatile("fence.proxy.async.global;" ::: "memory");
            have |= 1u << g;
          }
        };
        const bool has_a = type == IT_OUT || type >= IT_F1;
        if ((have & first) != first) {
          uint32_t c = 0;
          while (((have = __ballot_sync(0xffffffffu, ld_acquire(&g_flags[f]) >= target)) & first) != first) { if (++c > 20000000u) __trap(); __nanosleep(20); }
          asm volatile("fence.proxy.async.global;" ::: "memory");
        }
        if (type == IT_XT && elect_one()) mbar_arrive(bars + HB_NEXT);
        if (type != IT_XT) {
          const uint8_t* ap = type == IT_OUT ? g_att + (size_t)mt * 64 * 16384 : type == IT_F1 ? g_h2 + (size_t)mt * 16 * 16384 : g_act + (size_t)mt * 56 * 16384;
          const int nkb = (type == IT_OUT ? 64 : type == IT_F2 ? 56 : 16) >> lgp;
          const uint32_t abytes = has_a ? (sz == 2 ? 32768 : 16384) : 0, bytes = (sz == 0 ? 32768 : 16384) + abytes;
          const int dk = sz == 2 ? 1 : 0;
          const uint32_t late = type == IT_OUT ? 0x300 : type == IT_F1 ? 0x1ff : 0x100;
          const int kvec = !has_a || (lgp && !(it & IT_GATHER)) ? -1 : VEC_EARLY && (have & late) == late ? part * nkb + 1 + dk : (part + 1) * nkb - 1 - dk;
          const int knext = max(part * nkb, (part + 1) * nkb - ((sz == 0 ? ECL0 : ECL1) << dk));
#pragma unroll 1
          for (int kb = part * nkb; kb < (part + 1) * nkb; kb += 1 + dk) {
            const uint32_t d = sb + st * H_STAGE, fb = bars + HB_FULL + st * 8;
            mbar_wait(bars + HB_EMPTY + st * 8, ph);
            if (has_a) need(kb >> gsh);
            if (kb == kvec) {
              need(8);
              if (type == IT_OUT) need(9);
              if (elect_one()) {
                const bool f1 = type == IT_F1;
                const int c0 = f1 ? idx * (128 >> sz) : idx * (256 >> sz);
                const uint32_t v = sb + H_VEC + (n & 1) * 3072;
                const uint32_t n0 = (f1 ? 2048 : 512) >> sz, n1 = f1 ? 1024 : n0;
                asm volatile("mbarrier.expect_tx.relaxed.cta.shared::cta.b64 [%0], %1;" :: "r"(fb), "r"(n0 + n1) : "memory");
                bulk_g2s(v, f1 ? (const void*)(g_uv + c0 * 4) : (const void*)(g_mod + (type == IT_OUT ? 2 : 5) * D_ + c0), n0, fb);
                bulk_g2s(v + (f1 ? 2048 : 512), f1 ? (const void*)(g_stat + mt * 256) : (const void*)(g_mod + 4 * D_ + c0), n1, fb);
              }
            }
            if (elect_one()) {
              mbar_expect(fb, bytes);
              if (has_a) bulk_g2s(d, ap + (size_t)kb * 16384, abytes, fb);
              if (kb == knext) mbar_arrive(bars + HB_NEXT);
            }
            if (++st == H_NST) { st = 0; ph ^= 1; }
          }
          if (it & IT_GATHER) {
            const uint32_t i2 = opaque32(it), np = 1u << ((i2 >> 17) & 3);
            const int tile = split_tile(i2 & 7, (i2 >> 3) & 15, (i2 >> 7) & 63);
            if (lane == 0) wait_flag2(&g_flags[FL_SPL + tile], np - 1);
            __syncwarp();
            asm volatile("fence.proxy.async.global;" ::: "memory");
#pragma unroll 1
            for (uint32_t p = 1; p < np; p++) {
              const uint32_t fb = bars + HB_FULL + st * 8;
              mbar_wait(bars + HB_EMPTY + st * 8, ph);
              if (elect_one()) {
                mbar_expect(fb, 32768);
                bulk_g2s(sb + st * H_STAGE, g_ws + (size_t)tile * 32768 + (((i2 >> 15) & 3) ^ p) * 8192, 32768, fb);
              }
              if (++st == H_NST) { st = 0; ph ^= 1; }
            }
          }
        }
      }
    } else if (warp >= 10) {
      const int hb = warp - 10;
      uint32_t st = 0, ph = 1;
#pragma unroll 1
      for (uint32_t n = 0;; n++) {
        mbar_wait(bars + HB_IFULL + (n & 1) * 8, (n >> 1) & 1);
        const uint32_t it = __shfl_sync(0xffffffffu, lds32(bars + HB_ITEM + (n & 1) * 4), 0);
        const int type = it & 7, idx = (it >> 7) & 63, sz = item_sz(it), part = (it >> 15) & 3, lgp = (it >> 17) & 3;
        if (type == IT_END) break;
        if (elect_one()) mbar_arrive(bars + HB_IEMPTY + (n & 1) * 8);
        if (type == IT_XT) continue;
        const bool ffn1 = type == IT_F1 || type == IT_UV;
        const int nkb = (type == IT_OUT ? 64 : type == IT_F2 ? 56 : 16) >> lgp;
        const CUtensorMap* tb = type == IT_OUT ? &tmo : ffn1 ? &tm1 : type == IT_F2 ? &tm2 : &tmm;
        const CUtensorMap* tc = ffn1 ? &tm3 : tb;
        const int c0 = ffn1 ? idx * (128 >> sz) : idx * (256 >> sz) + (type == IT_MOD ? 2048 : 0), c2 = ffn1 ? c0 : c0 + 128;
        const int dk = sz == 2 ? 1 : 0;
        const CUtensorMap* t0 = hb == 1 && sz == 1 ? tc : tb;
        const int ca = hb == 0 || sz == 2 || (sz == 1 && ffn1) ? c0 : c0 + 64;
        const uint32_t off = (sz == 2 ? 32768 : 16384) + hb * 8192;
        const uint32_t cold = type == IT_MOD ? D_MOD : type == IT_UV ? D_UV : H_NST;
        if (type == IT_MOD || type == IT_UV) {
          if (lane == 0) wait_flag2(&g_flags[UV_WAIT && type == IT_UV ? FL_MOD : FL_GO], UV_WAIT && type == IT_UV ? UV_WAIT : 1);
          __syncwarp();
        }
#pragma unroll 1
        for (int kb = part * nkb; kb < (part + 1) * nkb; kb += 1 + dk) {
          const uint32_t d = sb + st * H_STAGE + off, fb = bars + HB_FULL + st * 8;
          mbar_wait(bars + HB_EMPTY + st * 8, ph);
          if (cold < H_NST) mbar_wait(bars + HB_FULL + ((st - cold) & 3) * 8, st >= cold ? ph ^ 1 : ph);
          if (elect_one()) {
            tma5d(d, t0, ca, kb + hb * dk, fb);
            if (sz == 0) tma5d(d + 16384, tc, c2 + hb * 64, kb, fb);
          }
          if (++st == H_NST) { st = 0; ph ^= 1; }
        }
        if (it & IT_GATHER) {
#pragma unroll 1
          for (int p = 1; p < (1 << lgp); p++) {
            mbar_wait(bars + HB_EMPTY + st * 8, ph);
            if (++st == H_NST) { st = 0; ph ^= 1; }
          }
        }
      }
    } else if (warp == 9) {
      uint32_t have;
      auto claim = [&]() {
        uint32_t q = 0;
        if (lane == 0) q = atomicAdd(&g_flags[FL_HEAD], 1);
        q = __shfl_sync(0xffffffffu, q, 0);
        const uint32_t it = q < list.n ? list.it[q] : 0;
        int f; uint32_t target;
        item_deps(it & 7, (it >> 3) & 15, lane, f, target);
        have = __ballot_sync(0xffffffffu, ld_acquire(&g_flags[f]) >= target);
        asm volatile("fence.proxy.async.global;" ::: "memory");
        return it | (q << 19);
      };
      auto hand_out = [&](uint32_t n, uint32_t it) {
        mbar_wait(bars + HB_IEMPTY + (n & 1) * 8, ((n >> 1) & 1) ^ 1);
        if (elect_one()) {
          sts32(bars + HB_ITEM + (n & 1) * 4, it);
          sts32(bars + HB_HAVE + (n & 1) * 4, have);
          mbar_arrive(bars + HB_IFULL + (n & 1) * 8);
        }
      };
      uint32_t next = claim();
      hand_out(0, next);
#pragma unroll 1
      for (uint32_t n = 0;; n++) {
        const uint32_t itq = next;
        const int type = itq & 7, mt = (itq >> 3) & 15;
        if (type == IT_END) break;
        mbar_wait(bars + HB_NEXT, n & 1);
        next = claim();
        const bool split = (itq >> 17) & 3, gath = itq & IT_GATHER;
        const bool hold = split && (gath ? (type == IT_OUT ? HOLD & 2 : false) : type == IT_OUT ? HOLD & 1 : HOLD & 4);
        if (!hold) hand_out(n + 1, next);
        if (n & 1) bar_sync<3, 288>(); else bar_sync<2, 288>();
        if (lane == 0) {
          const uint32_t inc = lds32(bars + HB_INC + (n & 1) * 4);
          if (inc) {
            fence_gpu();
            const int idx = (itq >> 7) & 63, sz = item_sz(itq);
            const int mv = (idx >> sz) >> 2;
            uint32_t* fl = &g_flags[type == IT_MOD ? (mv == 0 ? FL_MODA : mv == 3 ? FL_MODB : FL_MOD) : type == IT_UV ? FL_UV : type == IT_XT ? FL_XT + 8 * mt
                                    : type == IT_OUT ? FL_OUT + 8 * mt + ((2 * idx) >> sz) : FL_F1 + 8 * mt + (idx >> (2 + sz))];
            if (((itq >> 17) & 3) && !(itq & IT_GATHER)) fl = &g_flags[FL_SPL + split_tile(type, mt, idx)];
            red_add_u32(fl, inc);
            if (type == IT_OUT && sz == 0) red_add_u32(fl + 1, inc);
          }
        }
        __syncwarp();
        if (hold) hand_out(n + 1, next);
      }
      asm volatile("griddepcontrol.wait;" ::: "memory");
      uint32_t k = 0;
      if (lane == 0) { fence_gpu(); k = atomicAdd(&g_flags[FL_EXIT], 1); }
      k = __shfl_sync(0xffffffffu, k, 0);
      if (k == gridDim.x - 1) {
        fence_gpu();
        for (int i = lane; i < 1024; i += 32) g_flags[i] = 0;
      }
    }
  } else {
    asm volatile("setmaxnreg.inc.sync.aligned.u32 232;");
    const int wg = warp >> 2;
    const bool leader = (tid & 127) == 0;
    uint32_t st = 0, ph = 0;
    uint32_t nxt = 0;
#pragma unroll 1
    for (uint32_t n = 0;; n++) {
      uint32_t itq = nxt;
      if (itq == 0) {
        mbar_wait(bars + HB_IFULL + (n & 1) * 8, (n >> 1) & 1);
        itq = lds32(bars + HB_ITEM + (n & 1) * 4);
      }
      itq = __shfl_sync(0xffffffffu, itq, 0);
      nxt = 0;
      auto peek = [&]() {
        if (PEEK && mbar_test(bars + HB_IFULL + ((n + 1) & 1) * 8, ((n + 1) >> 1) & 1)) nxt = lds32(bars + HB_ITEM + ((n + 1) & 1) * 4);
      };
      auto finish = [&](uint32_t inc) {
        if (tid == 0) sts32(bars + HB_INC + (n & 1) * 4, inc);
        if (n & 1) bar_arrive<3, 288>(); else bar_arrive<2, 288>();
      };
      auto again = [&](int level, uint32_t inc) {
        if (PEEK < level) return false;
        nxt = __shfl_sync(0xffffffffu, nxt, 0);
        if (((nxt ^ itq) & 0x6007) != 0) return false;
        finish(inc);
        n++;
        itq = nxt;
        nxt = 0;
        HT(0);
        return true;
      };
      const int type = itq & 7, mt = (itq >> 3) & 15, idx = (itq >> 7) & 63, sz = item_sz(itq);
      uint32_t inc = type == IT_OUT ? (sz == 2 ? 1 : 2) : type == IT_F1 || type == IT_MOD ? 2 >> sz : type != IT_F2;
#define VA (sb + H_VEC + (n & 1) * 3072)
#define MT ((itq >> 3) & 15)
#define IDX ((itq >> 7) & 63)
#define SPLIT (itq >> 15) & 3, (itq >> 17) & 3, (itq & IT_GATHER) != 0
      if (type == IT_END) break;
      HT(0);
      if (type == IT_OUT) {
        if (sz == 0) h_residual<256, false>(sb, VA, mt, idx * 256, st, ph, warp, lane, out, peek);
        else if (sz == 1) { do h_residual<128, false>(sb, VA, MT, IDX * 128, st, ph, warp, lane, out, peek); while (again(5, 2)); }
        else { do h_residual<64, false>(sb, VA, MT, IDX * 64, st, ph, warp, lane, out, peek, SPLIT); while (again(5, 1)); }
      } else if (type == IT_F2) {
        if (sz == 0) h_residual<256, true>(sb, VA, mt, idx * 256, st, ph, warp, lane, out, peek);
        else if (sz == 1) { do h_residual<128, true>(sb, VA, MT, IDX * 128, st, ph, warp, lane, out, peek); while (again(4, 0)); }
        else {
          do {
            h_residual<64, true>(sb, VA, MT, IDX * 64, st, ph, warp, lane, out, peek, SPLIT);
            inc = ((itq >> 17) & 3) && !(itq & IT_GATHER);
          } while (again(4, inc));
        }
      } else if (type == IT_XT) {
        const int rg = idx * 8 + warp;
        const uint32_t* xp = reinterpret_cast<const uint32_t*>(x + (size_t)(mt * 128 + rg * 8 + (lane >> 2)) * D_) + (lane & 3);
        uint8_t* tp = g_x1 + (size_t)mt * 262144 + rg * 512 + tile_lane(0, lane);
        if (lane < 16) g_stat[(mt * 128 + rg * 8) * 2 + lane] = 0.f;
#pragma unroll 1
        for (int b = 0; b < 2; b++) {
          uint32_t v[64];
#pragma unroll
          for (int i = 0; i < 64; i++) v[i] = __ldg(xp + 256 * b + 4 * i);
#pragma unroll
          for (int i = 0; i < 16; i++)
            *reinterpret_cast<uint4*>(tp + tile_off(16 * b + i, 0)) = make_uint4(v[4 * i], v[4 * i + 1], v[4 * i + 2], v[4 * i + 3]);
        }
      } else if (type == IT_F1) {
        if (sz == 1) {
          do {
            float acc[64];
            h_mainloop<128, 0>(acc, sb, 16, st, ph, wg, leader, []() {}, peek);
            h_swiglu<128>(acc, VA, MT, IDX, warp, lane);
          } while (again(3, 1));
        } else {
          do {
            float acc[128];
            h_mainloop<256, 0>(acc, sb, 16, st, ph, wg, leader, []() {}, peek);
            h_swiglu<256>(acc, VA, MT, IDX * 2, warp, lane);
          } while (again(2, 2));
        }
      } else {
        if (type == IT_UV && tid == 0) wait_flag2(&g_flags[FL_MOD], 16);
        bar_sync<1, 256>();
        {
          const uint32_t* src = reinterpret_cast<const uint32_t*>(type == IT_UV ? g_mod + (wg == 0 ? 4 : 3) * D_ : cvec) + ((tid & 127) >> 2) * 16 + (tid & 3);
          uint32_t v[4];
#pragma unroll
          for (int j = 0; j < 4; j++) v[j] = __ldcg(src + 4 * j);
          const uint32_t p = sb + H_STG + ((tid & 127) >> 2) * 512 + (tid & 3) * 16;
          if (type == IT_MOD) {
#pragma unroll 1
            for (int j = 0; j < 4; j++) {
              const float c0 = bf_lo(v[0]), c1 = bf_hi(v[0]);
              v[0] = v[1]; v[1] = v[2]; v[2] = v[3];
              v[3] = pack2(c0 / (1.f + __expf(-c0)), c1 / (1.f + __expf(-c1)));
            }
          }
          if (type == IT_UV && wg == 0) sts128(p, 0x3f803f80u, 0x3f803f80u, 0x3f803f80u, 0x3f803f80u);
          if (type == IT_UV || wg == 0) sts128(type == IT_MOD ? p : wg == 0 ? p + 64 : (p ^ 16) + 128, v[0], v[1], v[2], v[3]);
        }
        fence_async_smem();
        bar_sync<1, 256>();
        float acc[8] = {0.f, 0.f, 0.f, 0.f, 0.f, 0.f, 0.f, 0.f};
        const uint64_t dw = mkdesc(sb + 16384 + wg * (16384 >> sz), 8192, 1024, 1), dv = mkdesc(sb + H_STG, 16, 0, 2);
#pragma unroll 1
        for (int i = 0; i < 16; i++) {
          mbar_wait(bars + HB_FULL + st * 8, ph);
          if (i == 0) HT(1);
          WG_FENCE();
#pragma unroll
          for (int k = 0; k < 4; k++) {
            const uint64_t a = dw + st * (H_STAGE >> 4) + k * 128, b = dv + i * 64 + (k >> 1) * 32 + (k & 1) * 2;
            wg_ss8(acc, a, b); wg_ss8(acc + 4, a + (sz ? 0 : 512), b);
          }
          WG_COMMIT();
          WG_WAIT(0);
          if (leader) mbar_arrive(bars + HB_EMPTY + st * 8);
          if (++st == H_NST) { st = 0; ph ^= 1; }
        }
        HT(2);
        reg_fence<8>(acc);
        const int t = lane & 3, c = (warp & 3) * 16 + (lane >> 2);
#pragma unroll
        for (int j = 0; j < 4; j++) {
          const int cj = c + (j >> 1) * 64 + (j & 1) * 8;
          if (type == IT_MOD) { if (t == 0 && (j < 2 || !sz)) g_mod[2048 + ((idx * 256 + wg * 128) >> sz) + cj] = __float2bfloat16(acc[2 * j]); }
          else if (t < 2) g_uv[idx * 512 + (cj >> 1) * 8 + wg * 4 + t * 2 + (cj & 1)] = (wg == 0 ? 0.5f : 1.f) * (t == 0 ? acc[2 * j] + acc[2 * j + 1] : acc[2 * j]);
        }
      }
      finish(inc);
    }
  }
}

const uint32_t h_items[] = {
  2, 130, 10, 138, 18, 146, 26, 154, 34, 162, 42, 170, 50, 178, 58, 186, 66, 194, 74, 202, 82, 210, 90, 218,
  98, 226, 106, 234, 114, 242, 122, 250, 1, 129, 257, 385, 513, 641, 769, 897, 1025, 1153, 1281, 1409, 4, 132, 260, 388,
  516, 644, 772, 900, 1028, 1156, 1284, 1412, 1540, 1668, 1796, 1924, 2052, 2180, 2308, 16387, 2436, 16515, 16643, 16771, 16899, 17027, 17155, 17283,
  17411, 17539, 17667, 17795, 17923, 18051, 18179, 18307, 2564, 2692, 2820, 2948, 3076, 3204, 3332, 1537, 3460, 1665, 1793, 1921, 16395, 16523, 16651, 16779,
  16907, 17035, 17163, 17291, 17419, 17547, 17675, 17803, 17931, 18059, 18187, 18315, 8211, 8339, 8467, 8595, 8723, 5, 133, 261, 389, 517, 645, 773,
  901, 1029, 1157, 1285, 1413, 1541, 1669, 1797, 1925, 2053, 2181, 2309, 2437, 8851, 8979, 9107, 2565, 2693, 2821, 2949, 3077, 3205, 3333, 3461,
  13, 141, 269, 781, 909, 1037, 1165, 1293, 1421, 1549, 1677, 1805, 1933, 2061, 2189, 2317, 2445, 397, 8219, 525, 8347, 653, 8475, 2573,
  2701, 2829, 8603, 2957, 3085, 8731, 3213, 3341, 17691, 3469, 8198, 8326, 8454, 8582, 17819, 2837, 8710, 8838, 17947, 8966, 18075, 9094, 3093, 18203,
  21, 3221, 18331, 16419, 3349, 16547, 16675, 3477, 16803, 1173, 16931, 1301, 17059, 1429, 2965, 1557, 17187, 1685, 17315, 2197, 17443, 1813, 17571, 2325,
  17699, 1941, 149, 2453, 277, 2069, 405, 2581, 533, 2709, 661, 29, 789, 157, 917, 285, 1045, 413, 17827, 541, 17955, 669, 18083, 797,
  18211, 925, 18339, 1053, 14, 1181, 142, 1309, 270, 1437, 398, 1565, 1693, 1821, 8235, 8363, 8491, 8619, 8747, 8875, 1949, 9003, 9131, 2077,
  2205, 2333, 3229, 2461, 3357, 2589, 3485, 2717, 8243, 2845, 8371, 2973, 8499, 3101, 8627, 8755, 8883, 9011, 9139, 37, 165, 293, 421, 549,
  677, 805, 933, 1061, 1189, 1317, 1445, 1573, 1701, 1829, 1957, 8251, 8379, 8507, 8635, 8763, 8891, 9019, 9147, 2085, 2213, 2341, 2469, 2597,
  2725, 2853, 2981, 3109, 3237, 3365, 3493, 45, 173, 301, 429, 557, 685, 813, 941, 1069, 1453, 1197, 1581, 1325, 9027, 1709, 1837, 1965,
  8259, 8387, 8515, 8643, 8771, 8899, 693, 9155, 2093, 2221, 2349, 2477, 2605, 2733, 2861, 2989, 3117, 3245, 9163, 2101, 2229, 3373, 3501, 53,
  181, 309, 437, 565, 821, 949, 1077, 1205, 1333, 1461, 1589, 1717, 1845, 1973, 8267, 8395, 8523, 8651, 8779, 8907, 9035, 2357, 2485, 2613,
  2741, 2869, 2997, 3125, 3253, 3381, 3509, 61, 189, 317, 445, 573, 701, 829, 957, 1085, 1213, 1341, 1469, 1597, 1725, 2493, 8275, 1853,
  8403, 1981, 8531, 2109, 8659, 2237, 8787, 2365, 8915, 9043, 9171, 2621, 2749, 2877, 3005, 3133, 3261, 3389, 3517, 1733, 69, 453, 197, 1861,
  325, 581, 709, 837, 1477, 965, 1605, 1093, 1989, 1221, 2117, 1349, 12869, 12997, 2245, 2501, 8283, 8411, 8539, 2629, 8667, 2757, 8795, 2885,
  8923, 9179, 3269, 3397, 1229, 3525, 973, 77, 205, 333, 461, 589, 1357, 717, 845, 1101, 3013, 9051, 3141, 1485, 1613, 1741, 1869, 1997,
  8675, 8291, 8803, 8419, 8931, 8547, 9059, 341, 3277, 85, 22, 469, 3405, 597, 3533, 725, 853, 981, 1109, 1237, 1365, 1493, 9187, 2125,
  2253, 2893, 2381, 2509, 3021, 213, 2637, 3149, 2765, 1621, 1749, 1877, 2005, 2133, 2261, 8427, 8299, 2389, 8555, 2517, 8683, 2645, 8811, 2773,
  8939, 2901, 9067, 3029, 9195, 150, 278, 406, 30, 158, 430, 286, 414, 38, 46, 166, 174, 294, 302, 422, 54, 182, 310, 438,
  8307, 8435, 8563, 8691, 8819, 8947, 9075, 9203, 278651, 311419, 344187, 376955, 278779, 311547, 344315, 377083, 180987, 312315, 148347, 345083, 181115, 148731, 181499, 148859,
  3157, 62, 148987, 149243, 278907, 3285, 190, 318, 149115, 311675, 148219, 344443, 279547, 181627, 1757, 377211, 181755, 181883, 1885, 147963, 2013, 180731, 2141, 2269,
  2397, 101, 2525, 182011, 148091, 180859, 3165, 149371, 182139, 280571, 313339, 346107, 279675, 377851, 378875, 312443, 345211, 377979, 446, 2653, 2781, 2909, 3037, 3293,
  3421, 3549, 3413, 733, 229, 989, 741, 1117, 1245, 869, 997, 1373, 1125, 1501, 1253, 1509, 3541, 93, 1629, 221, 349, 477, 1381, 605,
  357, 485, 861, 613, 1637, 1893, 2021, 2149, 2277, 2405, 2533, 2661, 2789, 12269, 2917, 3045, 12397, 3173, 12525, 3301, 12653, 3429, 12781, 12909,
  3557, 13037, 8301, 8429, 13165, 13293, 1765, 8557, 8685, 13421, 13549, 8813, 13677, 9069, 13805, 9197, 13933, 8941, 14061, 9325, 9453, 14189, 14317, 9581,
  9709, 14445, 14573, 9837, 10861, 10989, 11117, 11245, 11373, 11501, 11629, 9965, 14701, 14829, 10093, 10221, 14957, 15213, 15341, 10605, 10733, 15085, 11757, 10349,
  8573, 11885, 10477, 8701, 12013, 2549, 12141, 2677, 8317, 2805, 2933, 8262, 8390, 8518, 8646, 8774, 9030, 9158, 8902, 9038, 9166, 8270, 8398, 8526,
  8654, 8782, 3061, 8910, 3189, 3317, 117, 245, 373, 501, 629, 757, 3445, 3573, 1269, 1397, 1525, 8445, 8829, 8957, 9085, 9213, 9341, 9469,
  9597, 9725, 9853, 10621, 9981, 10109, 10749, 11645, 10237, 11773, 12029, 10365, 11901, 12157, 12285, 10493, 885, 12413, 1653, 1781, 1013, 1909, 1141, 12541,
  2037, 12669, 2165, 12797, 2293, 12925, 2421, 13053, 13181, 13309, 13565, 13437, 13693, 13821, 10877, 11005, 11133, 11517, 13949, 14077, 14205, 14333, 14461, 14589,
  14717, 14845, 14973, 8278, 8406, 8534, 15101, 8662, 15229, 8790, 15357, 9174, 8918, 11261, 8286, 9046, 8542, 11389, 8414, 8670, 8798, 8926, 9054, 9182,
  147558, 180326, 147686, 180454, 147814, 180582, 16870, 16998, 17126, 17254, 17382, 17510, 17638, 17766, 17894, 18022, 18150, 18278, 18406, 16494, 16622, 16750, 16878, 17006,
  17134, 17390, 17518, 17646, 17774, 17902, 18030, 18158, 17262, 18414, 18286, 16894, 17022, 17150, 17278, 17534, 17662, 17790, 18046, 18174, 278774, 16510, 16638, 311542,
  16766, 18302, 344310, 18430, 147574, 17918, 377078, 17406, 180342, 147830, 180598, 148470, 181238, 182006, 149366, 182134, 148598, 181366, 148726, 148854, 181494, 181622, 147958, 180726,
  148086, 180854, 148214, 180982, 148342, 181110, 148982, 181750, 149110, 181878, 149238, 149494, 182262,
};
void build_list(HList& l) {
  l.n = sizeof(h_items) / sizeof(h_items[0]);
  for (uint32_t i = 0; i < l.n; i++) l.it[i] = h_items[i];
}

typedef CUresult (*EncodeFn)(CUtensorMap*, CUtensorMapDataType, cuuint32_t, void*, const cuuint64_t*, const cuuint64_t*,
                             const cuuint32_t*, const cuuint32_t*, CUtensorMapInterleave, CUtensorMapSwizzle,
                             CUtensorMapL2promotion, CUtensorMapFloatOOBfill);

#define PROMO_W CU_TENSOR_MAP_L2_PROMOTION_L2_128B
#define PROMO_O CU_TENSOR_MAP_L2_PROMOTION_L2_128B
#define PROMO_M CU_TENSOR_MAP_L2_PROMOTION_L2_128B
#define PROMO_H CU_TENSOR_MAP_L2_PROMOTION_L2_128B
void make_map(EncodeFn fn, CUtensorMap* m, const void* p, uint64_t cols, uint64_t rows, uint32_t bc, uint32_t br, CUtensorMapSwizzle sw,
              CUtensorMapL2promotion promo) {
  cuuint64_t dims[2] = {cols, rows};
  cuuint64_t strides[1] = {cols * 2};
  cuuint32_t box[2] = {bc, br};
  cuuint32_t es[2] = {1, 1};
  fn(m, CU_TENSOR_MAP_DATA_TYPE_BFLOAT16, 2, const_cast<void*>(p), dims, strides, box, es, CU_TENSOR_MAP_INTERLEAVE_NONE, sw,
     promo, CU_TENSOR_MAP_FLOAT_OOB_FILL_NONE);
}

void make_map_perm(EncodeFn fn, CUtensorMap* m, const void* p, uint64_t cols, uint64_t rows, bool perm) {
  cuuint64_t dims[5] = {cols, 2, 4, 4, rows / 32};
  cuuint64_t strides[4] = {cols * 2, cols * 2 * (perm ? 8 : 2), cols * 2 * (perm ? 2 : 8), cols * 2 * 32};
  cuuint32_t box[5] = {64, 2, 4, 4, 2};
  cuuint32_t es[5] = {1, 1, 1, 1, 1};
  fn(m, CU_TENSOR_MAP_DATA_TYPE_BFLOAT16, 5, const_cast<void*>(p), dims, strides, box, es, CU_TENSOR_MAP_INTERLEAVE_NONE,
     CU_TENSOR_MAP_SWIZZLE_128B, PROMO_H, CU_TENSOR_MAP_FLOAT_OOB_FILL_NONE);
}

}

extern "C" void kernel_launch(void* const* d_in, const int* in_sizes, int n_in, void* d_out, int out_size) {
  const __nv_bfloat16* x = (const __nv_bfloat16*)d_in[0];
  const __nv_bfloat16* mem0 = (const __nv_bfloat16*)d_in[1];
  const __nv_bfloat16* cvec = (const __nv_bfloat16*)d_in[11];
  static EncodeFn enc = nullptr;
  if (!enc) {
    cudaDriverEntryPointQueryResult qr;
    void* fp = nullptr;
    cudaGetDriverEntryPoint("cuTensorMapEncodeTiled", &fp, cudaEnableDefault, &qr);
    enc = (EncodeFn)fp;
    cudaFuncSetAttribute(kernel_R, cudaFuncAttributeMaxDynamicSharedMemorySize, R_SMEM);
    cudaFuncSetAttribute(kernel_H, cudaFuncAttributeMaxDynamicSharedMemorySize, H_SMEM);
  }
  CUtensorMap tmq, tmk, tmv, tmo, tmm;
  make_map(enc, &tmm, d_in[12], 6144, 1024, 64, 64, CU_TENSOR_MAP_SWIZZLE_NONE, PROMO_M);
  make_map(enc, &tmq, d_in[2], 4096, 1024, 64, 64, CU_TENSOR_MAP_SWIZZLE_128B, PROMO_W);
  make_map(enc, &tmk, d_in[3], 4096, 1024, 64, 64, CU_TENSOR_MAP_SWIZZLE_128B, PROMO_W);
  make_map(enc, &tmv, d_in[4], 4096, 1024, 64, 64, CU_TENSOR_MAP_SWIZZLE_128B, PROMO_W);
  make_map(enc, &tmo, d_in[5], 1024, 4096, 16, 128, CU_TENSOR_MAP_SWIZZLE_32B, PROMO_O);
  RDesc dsc;
  for (int k = 0; k < 32; k++) {
    dsc.tok[k] = mkdesc(0x400 + (k < 16 ? R_GA : R_GB) + ((k & 15) >> 2) * 4096 + (k & 3) * 256, 128, 1024, 0);
    dsc.tail_a[k] = mkdesc(0x400 + R_TAIL + k * 2048, 1024, 1024, 1);
    if (k < 16) dsc.tail_b[k] = mkdesc(0x400 + R_GA + k * 256, 128, 4096, 0);
  }
  kernel_R<<<96, 256, R_SMEM, cudaStreamPerThread>>>(tmq, tmk, tmv, tmo, tmm, x, mem0, cvec, dsc);

  CUtensorMap ho, h1, h3, h2, hm;
  make_map_perm(enc, &ho, d_in[5], 1024, 4096, false);
  make_map_perm(enc, &h1, d_in[8], F_, 1024, true);
  make_map_perm(enc, &h3, d_in[9], F_, 1024, true);
  make_map_perm(enc, &h2, d_in[10], 1024, F_, true);
  make_map_perm(enc, &hm, d_in[12], 6144, 1024, true);
  HList list;
  build_list(list);
  {
    bool seen[12 * 16] = {};
    for (int i = (int)list.n - 1; i >= 0; i--) {
      const uint32_t it = list.it[i];
      if ((it >> 17) & 3) {
        const int t = split_tile(it & 7, (it >> 3) & 15, (it >> 7) & 63);
        if (!seen[t]) list.it[i] |= IT_GATHER;
        seen[t] = true;
      }
    }
  }
  cudaLaunchConfig_t cfg = {};
#define H_GRID 132
  cfg.gridDim = dim3(H_GRID); cfg.blockDim = dim3(384); cfg.dynamicSmemBytes = H_SMEM; cfg.stream = cudaStreamPerThread;
  cudaLaunchAttribute at[1];
  at[0].id = cudaLaunchAttributeProgrammaticStreamSerialization;
  at[0].val.programmaticStreamSerializationAllowed = 1;
  cfg.attrs = at;
  cfg.numAttrs = 1;
  cudaLaunchKernelEx(&cfg, kernel_H, ho, h1, h3, h2, hm, x, cvec, (__nv_bfloat16*)d_out, list);
}
```

```cpp
#include <cuda_runtime.h>
#include <cuda_bf16.h>
#include <cuda.h>
#include <stdint.h>
#include <type_traits>

namespace {

constexpr int S_ = 2048, D_ = 1024, NSEG = 64, F_ = 3584;

__device__ __align__(1024) uint8_t g_h[S_ * D_ * 2];
__device__ __align__(1024) uint8_t g_att[S_ * 4096 * 2];
__device__ __align__(1024) uint8_t g_x1[S_ * D_ * 2];
__device__ __align__(1024) uint8_t g_h2[S_ * D_ * 2];
__device__ __align__(1024) uint8_t g_act[S_ * F_ * 2];
__device__ __align__(1024) float g_ws[12 * 16 * 4 * 8192];
__device__ __align__(1024) float g_stat[S_ * 2];
__device__ __align__(1024) float g_uv[F_ * 4];
__device__ __align__(1024) float g_slot[4 * 3 * 8 * 4 * 32 * 4];
__device__ __align__(128) __nv_bfloat16 g_mod[6 * D_];
__device__ __align__(128) float g_modp[3 * 2 * D_];
__device__ __align__(128) uint32_t g_flags[1024];
constexpr int FL_S1 = 0, FL_S2 = 32, FL_MOD = 64, FL_HEAD = 96, FL_EXIT = 128, FL_UV = 160, FL_GO = 192, FL_MODB = 224, FL_MODA = 240, FL_ATT = 256, FL_XT = 384, FL_OUT = 512, FL_F1 = 640, FL_SPL = 768;

#define EVF 1
__device__ __forceinline__ uint32_t smem_u32(const void* p) { return (uint32_t)__cvta_generic_to_shared(p); }
__device__ __forceinline__ uint32_t mapa(uint32_t a, uint32_t r) { uint32_t o; asm("mapa.shared::cluster.u32 %0, %1, %2;" : "=r"(o) : "r"(a), "r"(r)); return o; }
__device__ __forceinline__ uint32_t pack2(float a, float b) { uint32_t r; asm("cvt.rn.bf16x2.f32 %0, %1, %2;" : "=r"(r) : "f"(b), "f"(a)); return r; }
__device__ __forceinline__ float bf_lo(uint32_t w) { return __uint_as_float(w << 16); }
__device__ __forceinline__ float bf_hi(uint32_t w) { return __uint_as_float(w & 0xffff0000u); }
__device__ __forceinline__ float ex2(float x) { float y; asm("ex2.approx.ftz.f32 %0, %1;" : "=f"(y) : "f"(x)); return y; }
__device__ __forceinline__ float rcp(float x) { float y; asm("rcp.approx.ftz.f32 %0, %1;" : "=f"(y) : "f"(x)); return y; }
__device__ __forceinline__ uint32_t clk32() { uint64_t c; asm volatile("mov.u64 %0, %%clock64;" : "=l"(c) :: "memory"); return (uint32_t)c; }

__device__ __forceinline__ void mbar_init(uint32_t b, uint32_t n) { asm volatile("mbarrier.init.shared::cta.b64 [%0], %1;" :: "r"(b), "r"(n) : "memory"); }
__device__ __forceinline__ void mbar_arrive(uint32_t b) { asm volatile("mbarrier.arrive.shared::cta.b64 _, [%0];" :: "r"(b) : "memory"); }
__device__ __forceinline__ void mbar_expect(uint32_t b, uint32_t n) { asm volatile("mbarrier.arrive.expect_tx.shared::cta.b64 _, [%0], %1;" :: "r"(b), "r"(n) : "memory"); }
__device__ __forceinline__ uint32_t mbar_try(uint32_t b, uint32_t par) {
  uint32_t ok;
  asm volatile("{\n.reg .pred p;\nmbarrier.try_wait.parity.shared::cta.b64 p, [%1], %2;\nselp.u32 %0, 1, 0, p;\n}" : "=r"(ok) : "r"(b), "r"(par) : "memory");
  return ok;
}
__device__ __forceinline__ bool mbar_test(uint32_t b, uint32_t par) {
  uint32_t ok;
  asm volatile("{\n.reg .pred p;\nmbarrier.test_wait.parity.shared::cta.b64 p, [%1], %2;\nselp.u32 %0, 1, 0, p;\n}" : "=r"(ok) : "r"(b), "r"(par) : "memory");
  return ok;
}
__device__ __forceinline__ void mbar_wait(uint32_t b, uint32_t par) {
  asm volatile("{\n.reg .pred p;\n"
               "LOOP:\n"
               "mbarrier.try_wait.parity.shared::cta.b64 p, [%0], %1;\n"
               "@!p bra.uni LOOP;\n}" :: "r"(b), "r"(par) : "memory");
}
__device__ __forceinline__ void mbar_wait_safe(uint32_t b, uint32_t par) {
  uint32_t c = 0;
  while (!mbar_try(b, par)) { if (++c > 4000000u) __trap(); }
}
__device__ __forceinline__ bool elect_one() {
  uint32_t p;
  asm volatile("{\n.reg .pred p;\nelect.sync _|p, 0xffffffff;\nselp.u32 %0, 1, 0, p;\n}" : "=r"(p));
  return p;
}
__device__ __forceinline__ void sched_fence(uint32_t x, uint32_t y) { asm volatile("{\n.reg .pred p;\nsetp.eq.u32 p, %0, %1;\n@p trap;\n}" :: "r"(x), "r"(y) : "memory"); }
template <class T> __device__ __forceinline__ T opaque32(T x) { asm volatile("" : "+r"(x)); return x; }
template <class T> __device__ __forceinline__ T opaque64(T x) { asm volatile("" : "+l"(x)); return x; }
template <int ID, int N> __device__ __forceinline__ void bar_sync() { asm volatile("bar.sync %0, %1;" :: "n"(ID), "n"(N) : "memory"); }
template <int ID, int N> __device__ __forceinline__ void bar_arrive() { asm volatile("bar.arrive %0, %1;" :: "n"(ID), "n"(N) : "memory"); }
__device__ __forceinline__ void fence_async_smem() { asm volatile("fence.proxy.async.shared::cta;" ::: "memory"); }
__device__ __forceinline__ void fence_async_all() { asm volatile("fence.proxy.async;" ::: "memory"); }
__device__ __forceinline__ void fence_gpu() { asm volatile("fence.acq_rel.gpu;" ::: "memory"); }
__device__ __forceinline__ void red_add_u32(uint32_t* p, uint32_t v) { asm volatile("red.relaxed.gpu.global.add.u32 [%0], %1;" :: "l"(p), "r"(v) : "memory"); }
__device__ __forceinline__ uint32_t ld_acquire(const uint32_t* p) { uint32_t v; asm volatile("ld.acquire.gpu.global.u32 %0, [%1];" : "=r"(v) : "l"(p) : "memory"); return v; }
__device__ __forceinline__ void wait_flag(const uint32_t* p, uint32_t target) {
  uint32_t c = 0;
  while (ld_acquire(p) < target) { if (++c > 20000000u) __trap(); __nanosleep(20); }
}

__device__ __forceinline__ void wait_flag2(const uint32_t* p, uint32_t target) {
  asm volatile("{\n.reg .pred p;\n.reg .u32 v, c;\nmov.u32 c, 0;\nWL:\nld.acquire.gpu.global.u32 v, [%0];\nsetp.ge.u32 p, v, %1;\n@p bra WD;\n"
               "add.u32 c, c, 1;\nsetp.gt.u32 p, c, 20000000;\n@p trap;\nnanosleep.u32 20;\nbra WL;\nWD:\n}" :: "l"(p), "r"(target) : "memory");
}
__device__ __forceinline__ void tma2d(uint32_t dst, const CUtensorMap* m, int c0, int c1, uint32_t bar) {
  asm volatile("cp.async.bulk.tensor.2d.shared::cluster.global.mbarrier::complete_tx::bytes [%0], [%1, {%3, %4}], [%2];"
               :: "r"(dst), "l"(m), "r"(bar), "r"(c0), "r"(c1) : "memory");
}
__device__ __forceinline__ void tma2d_once(uint32_t dst, const CUtensorMap* m, int c0, int c1, uint32_t bar) {
  asm volatile("{\n.reg .b64 pol;\ncreatepolicy.fractional.L2::evict_first.b64 pol, 1.0;\n"
               "cp.async.bulk.tensor.2d.shared::cluster.global.mbarrier::complete_tx::bytes.L2::cache_hint [%0], [%1, {%3, %4}], [%2], pol;\n}"
               :: "r"(dst), "l"(m), "r"(bar), "r"(c0), "r"(c1) : "memory");
}
__device__ __forceinline__ void tma5d(uint32_t dst, const CUtensorMap* m, int n0, int kb, uint32_t bar) {
  asm volatile("cp.async.bulk.tensor.5d.shared::cluster.global.mbarrier::complete_tx::bytes [%0], [%1, {%3, %5, %5, %5, %4}], [%2];"
               :: "r"(dst), "l"(m), "r"(bar), "r"(n0), "r"(2 * kb), "r"(0) : "memory");
}
__device__ __forceinline__ void tma2d_prefetch(const CUtensorMap* m, int c0, int c1) {
  asm volatile("cp.async.bulk.prefetch.tensor.2d.L2.global [%0, {%1, %2}];" :: "l"(m), "r"(c0), "r"(c1) : "memory");
}
__device__ __forceinline__ void bulk_g2s(uint32_t dst, const void* src, uint32_t bytes, uint32_t bar) {
  asm volatile("cp.async.bulk.shared::cluster.global.mbarrier::complete_tx::bytes [%0], [%1], %2, [%3];"
               :: "r"(dst), "l"(src), "r"(bytes), "r"(bar) : "memory");
}
__device__ __forceinline__ void bulk_s2s(uint32_t dst, uint32_t src, uint32_t bytes, uint32_t bar) {
  asm volatile("cp.async.bulk.shared::cluster.shared::cta.mbarrier::complete_tx::bytes [%0], [%1], %2, [%3];"
               :: "r"(dst), "r"(src), "r"(bytes), "r"(bar) : "memory");
}
__device__ __forceinline__ void st_async1(uint32_t dst, uint32_t a, uint32_t bar) {
  asm volatile("st.async.shared::cluster.mbarrier::complete_tx::bytes.b32 [%0], %1, [%2];" :: "r"(dst), "r"(a), "r"(bar) : "memory");
}
__device__ __forceinline__ void st_async2(uint32_t dst, uint32_t a, uint32_t b, uint32_t bar) {
  asm volatile("st.async.shared::cluster.mbarrier::complete_tx::bytes.v2.b32 [%0], {%1, %2}, [%3];" :: "r"(dst), "r"(a), "r"(b), "r"(bar) : "memory");
}
__device__ __forceinline__ void st_async4(uint32_t dst, const uint32_t* r, uint32_t bar) {
  asm volatile("st.async.shared::cluster.mbarrier::complete_tx::bytes.v4.b32 [%0], {%1, %2, %3, %4}, [%5];"
               :: "r"(dst), "r"(r[0]), "r"(r[1]), "r"(r[2]), "r"(r[3]), "r"(bar) : "memory");
}
__device__ __forceinline__ void sts32(uint32_t a, uint32_t v) { asm volatile("st.shared.b32 [%0], %1;" :: "r"(a), "r"(v) : "memory"); }
__device__ __forceinline__ void sts64(uint32_t a, uint32_t x, uint32_t y) { asm volatile("st.shared.v2.b32 [%0], {%1, %2};" :: "r"(a), "r"(x), "r"(y) : "memory"); }
__device__ __forceinline__ void sts128(uint32_t a, uint32_t x, uint32_t y, uint32_t z, uint32_t w) {
  asm volatile("st.shared.v4.b32 [%0], {%1, %2, %3, %4};" :: "r"(a), "r"(x), "r"(y), "r"(z), "r"(w) : "memory");
}
__device__ __forceinline__ void lds128(uint32_t* r, uint32_t a) {
  asm volatile("ld.shared.v4.b32 {%0, %1, %2, %3}, [%4];" : "=r"(r[0]), "=r"(r[1]), "=r"(r[2]), "=r"(r[3]) : "r"(a) : "memory");
}
__device__ __forceinline__ uint32_t lds32(uint32_t a) { uint32_t r; asm volatile("ld.shared.b32 %0, [%1];" : "=r"(r) : "r"(a) : "memory"); return r; }
__device__ __forceinline__ void lds64(uint32_t* r, uint32_t a) {
  asm volatile("ld.shared.v2.b32 {%0, %1}, [%2];" : "=r"(r[0]), "=r"(r[1]) : "r"(a) : "memory");
}
__device__ __forceinline__ void lds128f(float* r, uint32_t a) {
  asm volatile("ld.shared.v4.f32 {%0, %1, %2, %3}, [%4];" : "=f"(r[0]), "=f"(r[1]), "=f"(r[2]), "=f"(r[3]) : "r"(a) : "memory");
}
__device__ __forceinline__ void lds64f(float* r, uint32_t a) {
  asm volatile("ld.shared.v2.f32 {%0, %1}, [%2];" : "=f"(r[0]), "=f"(r[1]) : "r"(a) : "memory");
}
__device__ __forceinline__ void ldsm4(uint32_t* r, uint32_t a) {
  asm volatile("ldmatrix.sync.aligned.m8n8.x4.shared.b16 {%0, %1, %2, %3}, [%4];" : "=r"(r[0]), "=r"(r[1]), "=r"(r[2]), "=r"(r[3]) : "r"(a) : "memory");
}
__device__ __forceinline__ void ldsm4t(uint32_t* r, uint32_t a) {
  asm volatile("ldmatrix.sync.aligned.m8n8.x4.trans.shared.b16 {%0, %1, %2, %3}, [%4];" : "=r"(r[0]), "=r"(r[1]), "=r"(r[2]), "=r"(r[3]) : "r"(a) : "memory");
}
__device__ __forceinline__ void ldsm2(uint32_t* r, uint32_t a) {
  asm volatile("ldmatrix.sync.aligned.m8n8.x2.shared.b16 {%0, %1}, [%2];" : "=r"(r[0]), "=r"(r[1]) : "r"(a) : "memory");
}
__device__ __forceinline__ void stsm4(uint32_t a, const uint32_t* r) {
  asm volatile("stmatrix.sync.aligned.m8n8.x4.shared.b16 [%0], {%1, %2, %3, %4};" :: "r"(a), "r"(r[0]), "r"(r[1]), "r"(r[2]), "r"(r[3]) : "memory");
}
__device__ __forceinline__ uint32_t hadd2(uint32_t a, uint32_t b) { uint32_t t; asm("add.rn.bf16x2 %0, %1, %2;" : "=r"(t) : "r"(a), "r"(b)); return t; }
__device__ __forceinline__ uint32_t hmax2(uint32_t a, uint32_t b) { uint32_t t; asm("max.bf16x2 %0, %1, %2;" : "=r"(t) : "r"(a), "r"(b)); return t; }
__device__ __forceinline__ void ldsm2t(uint32_t* r, uint32_t a) {
  asm volatile("ldmatrix.sync.aligned.m8n8.x2.trans.shared.b16 {%0, %1}, [%2];" : "=r"(r[0]), "=r"(r[1]) : "r"(a) : "memory");
}
__device__ __forceinline__ uint32_t movm(uint32_t x) { uint32_t y; asm volatile("movmatrix.sync.aligned.m8n8.trans.b16 %0, %1;" : "=r"(y) : "r"(x)); return y; }
__device__ __forceinline__ void hmma(float* d, uint32_t a0, uint32_t a1, uint32_t a2, uint32_t a3, uint32_t b0, uint32_t b1) {
  asm volatile("mma.sync.aligned.m16n8k16.row.col.f32.bf16.bf16.f32 {%0,%1,%2,%3}, {%4,%5,%6,%7}, {%8,%9}, {%0,%1,%2,%3};"
               : "+f"(d[0]), "+f"(d[1]), "+f"(d[2]), "+f"(d[3]) : "r"(a0), "r"(a1), "r"(a2), "r"(a3), "r"(b0), "r"(b1));
}
__device__ __forceinline__ void hmma0(float* d, uint32_t a0, uint32_t a1, uint32_t a2, uint32_t a3, uint32_t b0, uint32_t b1) {
  asm volatile("mma.sync.aligned.m16n8k16.row.col.f32.bf16.bf16.f32 {%0,%1,%2,%3}, {%4,%5,%6,%7}, {%8,%9}, {%10,%10,%10,%10};"
               : "=f"(d[0]), "=f"(d[1]), "=f"(d[2]), "=f"(d[3]) : "r"(a0), "r"(a1), "r"(a2), "r"(a3), "r"(b0), "r"(b1), "f"(0.f));
}
__device__ __forceinline__ void hmma_k8(float* d, uint32_t a0, uint32_t a1, uint32_t b0) {
  asm volatile("mma.sync.aligned.m16n8k8.row.col.f32.bf16.bf16.f32 {%0,%1,%2,%3}, {%4,%5}, {%6}, {%0,%1,%2,%3};"
               : "+f"(d[0]), "+f"(d[1]), "+f"(d[2]), "+f"(d[3]) : "r"(a0), "r"(a1), "r"(b0));
}
__host__ __device__ constexpr uint64_t mkdesc(uint32_t addr, uint32_t lbo, uint32_t sbo, uint32_t sw) {
  return (uint64_t)((addr & 0x3FFFF) >> 4) | ((uint64_t)(lbo >> 4) << 16) | ((uint64_t)(sbo >> 4) << 32) | ((uint64_t)sw << 62);
}
#define WG_FENCE() asm volatile("wgmma.fence.sync.aligned;" ::: "memory")
#define WG_COMMIT() asm volatile("wgmma.commit_group.sync.aligned;" ::: "memory")
#define WG_WAIT(n) asm volatile("wgmma.wait_group.sync.aligned " #n ";" ::: "memory")
template <int N> __device__ __forceinline__ void reg_fence(float* d) {
#pragma unroll
  for (int i = 0; i < N; i++) asm volatile("" : "+f"(d[i]) :: "memory");
}
template <int N> __device__ __forceinline__ void zero_regs(float* d) {
#pragma unroll
  for (int i = 0; i < N; i++) asm volatile("mov.b32 %0, 0;" : "=f"(d[i]));
}
template <int SD>
__device__ __forceinline__ void wg_rs32(float* d, uint32_t a0, uint32_t a1, uint32_t a2, uint32_t a3, uint64_t b) {
  asm volatile("wgmma.mma_async.sync.aligned.m64n32k16.f32.bf16.bf16 {%0,%1,%2,%3,%4,%5,%6,%7,%8,%9,%10,%11,%12,%13,%14,%15}, {%16,%17,%18,%19}, %20, %21, 1, 1, 0;"
               : "+f"(d[0]), "+f"(d[1]), "+f"(d[2]), "+f"(d[3]), "+f"(d[4]), "+f"(d[5]), "+f"(d[6]), "+f"(d[7]),
                 "+f"(d[8]), "+f"(d[9]), "+f"(d[10]), "+f"(d[11]), "+f"(d[12]), "+f"(d[13]), "+f"(d[14]), "+f"(d[15])
               : "r"(a0), "r"(a1), "r"(a2), "r"(a3), "l"(b), "n"(SD));
}
template <int TB>
__device__ __forceinline__ void wg_ss40(float* d, uint64_t a, uint64_t b) {
  asm volatile("wgmma.mma_async.sync.aligned.m64n40k16.f32.bf16.bf16 {%0,%1,%2,%3,%4,%5,%6,%7,%8,%9,%10,%11,%12,%13,%14,%15,%16,%17,%18,%19}, %20, %21, 1, 1, 1, 1, %22;"
               : "+f"(d[0]), "+f"(d[1]), "+f"(d[2]), "+f"(d[3]), "+f"(d[4]), "+f"(d[5]), "+f"(d[6]), "+f"(d[7]),
                 "+f"(d[8]), "+f"(d[9]), "+f"(d[10]), "+f"(d[11]), "+f"(d[12]), "+f"(d[13]), "+f"(d[14]), "+f"(d[15]),
                 "+f"(d[16]), "+f"(d[17]), "+f"(d[18]), "+f"(d[19])
               : "l"(a), "l"(b), "n"(TB));
}
__device__ __forceinline__ void wg_ss8(float* d, uint64_t a, uint64_t b) {
  asm volatile("wgmma.mma_async.sync.aligned.m64n8k16.f32.bf16.bf16 {%0,%1,%2,%3}, %4, %5, 1, 1, 1, 1, 0;"
               : "+f"(d[0]), "+f"(d[1]), "+f"(d[2]), "+f"(d[3]) : "l"(a), "l"(b));
}
template <int T>
__device__ __forceinline__ void wg_ss32(float* d, uint64_t a, uint64_t b) {
  asm volatile("wgmma.mma_async.sync.aligned.m64n32k16.f32.bf16.bf16 {%0,%1,%2,%3,%4,%5,%6,%7,%8,%9,%10,%11,%12,%13,%14,%15}, %16, %17, 1, 1, 1, %18, %18;"
               : "+f"(d[0]), "+f"(d[1]), "+f"(d[2]), "+f"(d[3]), "+f"(d[4]), "+f"(d[5]), "+f"(d[6]), "+f"(d[7]),
                 "+f"(d[8]), "+f"(d[9]), "+f"(d[10]), "+f"(d[11]), "+f"(d[12]), "+f"(d[13]), "+f"(d[14]), "+f"(d[15])
               : "l"(a), "l"(b), "n"(T));
}

constexpr int R_TAIL = 0;
constexpr int R_WO = 65536;
constexpr int R_QK = R_WO + 86016;
constexpr int R_P = R_QK + 10240;
constexpr int R_GA = R_P + 6400;
constexpr int R_M2 = R_GA + 16384;
constexpr int R_M1 = R_M2 + 7168;
constexpr int R_GB = R_M1 + 9216;
constexpr int R_VT = R_GB + 16384;
constexpr int R_VM = R_VT + 8192;
constexpr int R_XS = R_VM + 2048;
constexpr int R_OX = R_XS + 1280;
constexpr int R_BAR = R_OX + 2048;
constexpr int R_TRC = R_BAR + 256;
constexpr int R_SMEM = R_TRC + 1024;
constexpr int B_MB = 0, B_XS = 32, B_VM = 40, B_VT = 48, B_TS = 56, B_FA = 64, B_FB = 72, B_TAIL = 80, B_WO = 88, B_STG = 96, B_WM = 128, B_X = 136;
constexpr int NB_A = 1, NB_B = 2, NB_X = 3, NB_C = 4, NB_D = 5, NB_E = 6, NB_F = 7, NB_G = 8, NB_H = 9, NB_S = 10, NB_E2 = 11, NB_P = 12, NB_W0 = 13;

#define FIN 1
#define POLL_DELAY 750
#define POLL_DELAY1 700
#define POLL_STAG 150
#define POLL_K0 20
#define PF1 3
#define PF2 0
#define PF3 1
#define PF4 0
#define NW0 3
#define S2_LATE 1
#define NW2 1
#define CLR_D 2
#define PADN 0
#define PFD 0
#define GO_EARLY 0
#define RF_FIRST 1
#define BX_I 5
#define NCH 4
#define TOP2 0
#define CX_I 13
#define ATT_LATE 0
#define V_FENCE 1
#define SELF_STAS 1
#define Q_FENCE 1
#define ND_K 3
#define TRACE(i)
#define TS(i)

__device__ __forceinline__ int rot_chunk(int c, int rank) {
  int G = c;
  if (c < 9) { G = c + 3 * rank; if (G >= 9) G -= 9; }
  return G;
}
__device__ __forceinline__ int wo_tile(int i, int rank) {
  if (i < 12) return 12 * rank + i;
  const int r = i - 12 + 9 * rank;
  return r < 16 ? 48 + r : 20 + r;
}
__device__ __forceinline__ void load_chunk(uint32_t dst, int seg, int G, uint32_t bar) {
  mbar_expect(bar, 4096);
  bulk_g2s(dst, g_h + (size_t)(seg * 16 + G) * 4096, 4096, bar);
}
__device__ __forceinline__ void load_red(uint32_t* v, const float* p) {
#pragma unroll
  for (int j = 0; j < 2; j++)
    asm volatile("ld.relaxed.gpu.global.v4.u32 {%0, %1, %2, %3}, [%4];"
                 : "=r"(v[4 * j]), "=r"(v[4 * j + 1]), "=r"(v[4 * j + 2]), "=r"(v[4 * j + 3]) : "l"(p + j * 256) : "memory");
}
__device__ __forceinline__ bool red_done(const uint32_t* v) { return __all_sync(0xffffffffu, (v[3] & v[7]) == 0x42000000u); }
__device__ __forceinline__ uint32_t finish_red(uint32_t* v, const float* p) {
  uint32_t tries = 0;
  if (__builtin_expect(!red_done(v), 0)) {
    do { if (++tries > 20000000u) __trap(); load_red(v, p); } while (!red_done(v));
  }
  return tries;
}
__device__ __forceinline__ void exp10(float* sv, const uint32_t* x) {
  constexpr float SC = 0.08838834764831845f * 1.4426950408889634f;
  uint32_t m2 = hmax2(hmax2(hmax2(x[0], x[1]), hmax2(x[2], x[3])), x[4]);
  m2 = hmax2(m2, __shfl_xor_sync(0xffffffffu, m2, 1));
  m2 = hmax2(m2, __shfl_xor_sync(0xffffffffu, m2, 2));
  const float nm = -fmaxf(bf_lo(m2), bf_hi(m2)) * SC;
#pragma unroll
  for (int j = 0; j < 5; j++) { sv[2 * j] = ex2(fmaf(bf_lo(x[j]), SC, nm)); sv[2 * j + 1] = ex2(fmaf(bf_hi(x[j]), SC, nm)); }
}

__device__ __forceinline__ uint32_t arm_size(int w, bool isC) {
  return w == 0 ? (isC ? 1280 : 640) : w == 1 ? (isC ? 0 : 2048) : w == 2 ? (isC ? 0 : 8192) : (isC ? 0 : 1792);
}
struct RDesc { uint64_t tok[32], tail_b[16], tail_a[32]; };

template <int WG>
__device__ __forceinline__ void r_main(const uint32_t (&W)[48][4], const RDesc& dsc, int head, uint32_t rank, int lane_, int w) {
  const uint32_t sb = (rank << 24) + 0x400, bars = sb + R_BAR;
  const uint32_t to1 = rank == 0 ? 2u << 24 : 0u - (1u << 24), to2 = rank == 2 ? 0u - (2u << 24) : 1u << 24;
  const bool isC = rank == 2;
  const int lane = opaque32(lane_), warp = WG * 4 + w;
  const int gl = rot_chunk(4 * (lane & 3) + w, rank);
  const int g0 = __shfl_sync(0xffffffffu, gl, 0), g1 = __shfl_sync(0xffffffffu, gl, 1), g2 = __shfl_sync(0xffffffffu, gl, 2);
  const uint32_t arm_bytes = arm_size(w, isC);

#define L16 opaque32(sb + opaque32(lane) * 16)
#define L8 opaque32(sb + opaque32(lane) * 8)
#define L4 opaque32(sb + opaque32(lane) * 4)
#define LV opaque32(sb + R_VT + ((opaque32(lane) >> 3) & 1) * 512 + (opaque32(lane) >> 4) * 128 + (opaque32(lane) & 7) * 16)
#define SLOT(st) opaque64(slot0 + ((st) & 3) * 12288 + ((st) & 4) * 32)
  float* const slot0 = opaque64(g_slot + (rank * 1024 + warp * 128 + lane) * 4);
  const uint32_t woa = opaque32(sb + R_WO + warp * 12288 + ((lane >> 4) * 8 + (lane & 7)) * 32 + ((((lane >> 3) ^ (lane >> 2)) & 1) << 4));
  const bool has_wo = WG == 0 || isC || w < 3;
  float acc[20];
  uint32_t pk[8] = {0u, 0u, 0u, 0u, 0u, 0u, 0u, 0u};

  auto forward = [&](auto rd, const uint32_t* v, int st, uint32_t tries) {
    constexpr int RD = decltype(rd)::value;
    uint32_t u[6];
#pragma unroll
    for (int j = 0; j < 6; j++) u[j] = movm(v[4 * (j / 3) + j % 3]);
    const bool all3 = RD == 0 || w < 3;
    if (RD == 0) {
      const uint32_t a = L16 + R_M1 + w * 768, a2 = L8 + R_M1 + 512 + w * 768;
      st_async4(a + to1 + 3072, u, bars + to1 + B_MB + 8); st_async2(a2 + to1 + 3072, u[4], u[5], bars + to1 + B_MB + 8);
      sts128(a, u[0], u[1], u[2], u[3]); sts64(a2, u[4], u[5]);
      __syncwarp();
      if (elect_one()) mbar_arrive(bars + B_MB);
      st_async4(a + to2 + 6144, u, bars + to2 + B_MB + 16); st_async2(a2 + to2 + 6144, u[4], u[5], bars + to2 + B_MB + 16);
    } else {
      const uint32_t a = L4 + R_M2 + rank * 2304 + w * 768;
#pragma unroll
      for (int j = 0; j < 6; j++) if (j < 2 || all3) st_async1(a + to1 + j * 128, u[j], bars + to1 + B_MB + 24);
#pragma unroll
      for (int j = 0; j < 6; j++) if (j < 2 || all3) st_async1(a + to2 + j * 128, u[j], bars + to2 + B_MB + 24);
      if (SELF_STAS) {
#pragma unroll
        for (int j = 0; j < 6; j++) if (j < 2 || all3) st_async1(a + j * 128, u[j], bars + B_MB + 24);
      } else {
#pragma unroll
        for (int j = 0; j < 6; j++) if (j < 2 || all3) sts32(a + j * 128, u[j]);
        __syncwarp();
        if (elect_one()) mbar_arrive(bars + B_MB + 24);
      }
    }
  };

  auto send_vt = [&]() {
    if (elect_one()) {
      const uint32_t src = sb + R_VT + warp * 1024;
      bulk_s2s(src + to1, src, 1024, bars + to1 + B_VT);
      bulk_s2s(src + to2, src, 1024, bars + to2 + B_VT);
    }
  };
  auto store_att = [&](int sg) {
    uint32_t* op = reinterpret_cast<uint32_t*>(g_att + (size_t)((sg >> 2) * 64 + head * 2 + rank) * 16384 + (2 * w * 16 + (sg & 3) * 4) * 128) + opaque32(lane);
#pragma unroll
    for (int j = 0; j < 8; j++) op[(j & 1) * 512 + (j >> 1) * 32] = pk[j];
  };

  if (WG == 0) bar_arrive<NB_G, 256>();
#pragma unroll 1
  for (int s = -1; s < NSEG - FIN; s++) {
    const uint32_t par = (s + 1) & 1;
    const uint32_t last = !FIN && s == NSEG - 1;
    TRACE(0);
    {
      float c[NCH][4];
      uint32_t b[3][6];
      const uint32_t ma = L16, m8 = L8;
#pragma unroll
      for (int i = 0; i < 18; i++) {
        if (i < 16) {
          if (i % 4 == 0 && !(i == 4 && TOP2)) mbar_wait(bars + B_MB + (i / 4) * 8, par ^ 1);
          if (i == 0 && TOP2) mbar_wait(bars + B_MB + 8, par ^ 1);
          if (i % 4 == 0) TRACE(1 + i / 4);
          if (i < 12) { lds128(b[i % 3], ma + R_M1 + i * 768); lds64(b[i % 3] + 4, m8 + R_M1 + 512 + i * 768); }
          else { ldsm4(b[i % 3], ma + R_M2 + 4096 + (i - 12) * 768); ldsm2(b[i % 3] + 4, ma + R_M2 + 4096 + 512 + (i - 12) * 768); }
          if (WG == 1 && i == BX_I) {
            bar_sync<NB_G, 256>();
            if (!last && elect_one()) load_chunk(sb + R_GB + w * 4096, s + 1, g0, bars + B_FB);
          }
          if (i == CX_I) {
            if (isC && s >= 0) send_vt();
            if (WG == 1 && ATT_LATE && !isC && s > 0) store_att(s - 1);
          }
          __syncwarp();
        }
        if (i >= 2) {
          const int j = i - 2;
#pragma unroll
          for (int q = 0; q < 3; q++) {
            const uint32_t* f = W[3 * j + q];
            if (3 * j + q < NCH) hmma0(c[3 * j + q], f[0], f[1], f[2], f[3], b[j % 3][2 * q], b[j % 3][2 * q + 1]);
            else hmma(c[(3 * j + q) % NCH], f[0], f[1], f[2], f[3], b[j % 3][2 * q], b[j % 3][2 * q + 1]);
          }
        }
        if (i == 14) zero_regs<16>(acc);
        if (i == 16) mbar_wait(bars + B_FA, last);
      }
#pragma unroll
      for (int j = 0; j < 4; j++) acc[16 + j] = NCH == 3 ? (c[0][j] + c[1][j]) + c[2][j] : (c[0][j] + c[1][j]) + (c[2][j] + c[NCH - 1][j]);
    }
    TRACE(5);
    bar_sync<NB_H, 256>();
    WG_FENCE();
#pragma unroll
    for (int k = 0; k < 16; k++) wg_ss40<0>(acc, dsc.tail_a[WG * 16 + k], dsc.tail_b[k]);
    WG_COMMIT();
    uint32_t vt[4][4];
    {
      const uint32_t a = opaque32(L4 + w * 256 + (isC ? WG * 1024 + R_VM : R_QK + 4096 + WG * 5120));
      const uint32_t qa = L16 + R_QK, xa = opaque32(LV + w * 2048 + (WG == 0 ? 0 : (opaque32(lane) & 8) * 64 + R_QK + 5120 - R_VT));
      const uint32_t d = opaque32(L4 + R_XS + rank * 640 + w * 256);
      if (s == 0) {
        mbar_wait_safe(bars + B_WO, 0);
        if (!GO_EARLY && WG == 1 && head == 0 && rank == 0 && w == 0 && elect_one()) red_add_u32(&g_flags[FL_GO], 1);
      }
      mbar_wait(bars + B_FB, last);
      if (WG == 0) mbar_wait(bars + B_VT, par);
      WG_WAIT(0);
      reg_fence<20>(acc);
      TRACE(6);
      const uint32_t p0 = pack2(acc[16], acc[17]), p1 = pack2(acc[18], acc[19]);
      sts32(a, p0); sts32(a + 128, p1);
      if (isC) {
        st_async1(a + to1, p0, bars + B_VM + to1); st_async1(a + to1 + 128, p1, bars + B_VM + to1);
        st_async1(a + to2, p0, bars + B_VM + to2); st_async1(a + to2 + 128, p1, bars + B_VM + to2);
      }
      if (WG == 0) {
        bar_arrive<NB_A, 256>();
        if (Q_FENCE && !isC) fence_async_smem();
#pragma unroll
        for (int i = 0; i < 4; i++) ldsm4(vt[i], xa + (i >> 1) * 1024 + (i & 1) * 256);
        bar_sync<NB_S, 256>();
      } else {
        bar_sync<NB_A, 256>();
        if (!isC) {
          if (w < 3) {
            uint32_t q[8], k[4][4];
            ldsm4t(q, qa + 4096); ldsm4t(k[0], xa); ldsm4t(k[1], xa + 256);
            ldsm4t(q + 4, qa + 4096 + 512); ldsm4t(k[2], xa + 512); ldsm4t(k[3], xa + 768);
            float x[4], y[4];
            hmma0(x, k[0][0], k[0][1], k[0][2], k[0][3], q[0], q[1]); hmma0(y, k[1][0], k[1][1], k[1][2], k[1][3], q[2], q[3]);
            hmma(x, k[2][0], k[2][1], k[2][2], k[2][3], q[4], q[5]); hmma(y, k[3][0], k[3][1], k[3][2], k[3][3], q[6], q[7]);
            const uint32_t s0 = pack2(x[0] + y[0], x[1] + y[1]), s1 = pack2(x[2] + y[2], x[3] + y[3]);
            st_async1(d + to1, s0, bars + B_XS + to1);
            st_async1(d + to2, s0, bars + B_XS + to2);
            if (w < 2) { st_async1(d + to1 + 128, s1, bars + B_XS + to1); st_async1(d + to2 + 128, s1, bars + B_XS + to2); sts32(d + 128, s1); }
            sts32(d, s0);
          }
        }
        bar_arrive<NB_S, 256>();
      }
    }
    if (WG == 1) {
      if (!last && elect_one()) load_chunk(sb + R_GA + w * 4096, s + 1, g1, bars + B_FA);
      {
        if (w > 0 && elect_one()) mbar_expect(bars + B_MB + 8 * w, w < 3 ? 3072 : SELF_STAS ? 28 * 256 : isC ? 18 * 256 : 19 * 256);
      }
      fence_async_smem();
      bar_sync<NB_B, 256>();
    }
    TRACE(7);
    WG_FENCE();
#pragma unroll
    for (int k = 0; k < 16; k++) wg_rs32<1>(acc, W[k][0], W[k][1], W[k][2], W[k][3], dsc.tok[16 + k]);
    WG_COMMIT();
    uint32_t wa[3][4];
    const uint32_t oxa = L16 + R_OX;
    if (WG == 0) {
      const uint32_t vma = oxa - (R_OX - R_VM) + w * 512, oa = opaque32(L4 + w * 512 + R_OX);
      TRACE(8);
      mbar_wait(bars + B_XS, par);
      TRACE(9);
      float sv[10];
      {
        uint32_t x[10];
        ldsm4t(x, oxa - (R_OX - R_XS)); ldsm4t(x + 4, oxa - (R_OX - R_XS) + 512); ldsm2t(x + 8, oxa - (R_OX - R_XS) + 1024);
        bar_arrive<NB_B, 256>();
#pragma unroll
        for (int j = 0; j < 5; j++) x[j] = hadd2(x[j], x[j + 5]);
        exp10(sv, x);
      }
      WG_WAIT(0);
      bar_arrive<NB_X, 256>();
      mbar_wait(bars + B_VM, par);
      uint32_t vm[4];
      ldsm4(vm, vma);
      uint32_t pb[5];
#pragma unroll
      for (int j = 0; j < 5; j++) pb[j] = pack2(sv[2 * j], sv[2 * j + 1]);
      TRACE(10);
      float o0[4], o1[4], sm[4];
      const uint32_t ONE = 0x3f803f80u;
      hmma0(o0, vt[0][0], vt[0][1], vt[0][2], vt[0][3], pb[0], pb[1]);
      hmma0(o1, vt[2][0], vt[2][1], vt[2][2], vt[2][3], pb[0], pb[1]);
      hmma0(sm, ONE, ONE, ONE, ONE, pb[0], pb[1]);
      hmma(sm, ONE, ONE, ONE, ONE, pb[2], pb[3]);
      hmma(o0, vt[1][0], vt[1][1], vt[1][2], vt[1][3], pb[2], pb[3]);
      hmma(o1, vt[3][0], vt[3][1], vt[3][2], vt[3][3], pb[2], pb[3]);
      hmma_k8(sm, ONE, ONE, pb[4]);
      hmma_k8(o0, vm[0], vm[1], pb[4]);
      hmma_k8(o1, vm[2], vm[3], pb[4]);
#pragma unroll
      for (int i = 0; i < 3; i++) ldsm4t(wa[i], woa + i * 4096);
      __syncwarp();
      const float i0 = rcp(sm[0]), i1 = rcp(sm[1]);
      sts32(oa, pack2(o0[0] * i0, o0[1] * i1)); sts32(oa + 128, pack2(o0[2] * i0, o0[3] * i1));
      sts32(oa + 256, pack2(o1[0] * i0, o1[1] * i1)); sts32(oa + 384, pack2(o1[2] * i0, o1[3] * i1));
      TRACE(11);
      bar_sync<NB_C, 128>();
    } else {
      if (!isC) {
        constexpr uint64_t dQ = mkdesc(0x400 + R_QK, 128, 1024, 0), dK = mkdesc(0x400 + R_QK + 5120, 128, 1024, 0);
        float sc[16];
        zero_regs<16>(sc);
        WG_FENCE();
#pragma unroll
        for (int k = 0; k < 4; k++) wg_ss32<1>(sc, dK + k * 16, dQ + k * 16);
        WG_COMMIT();
        const uint32_t top = rank == 0 ? to2 : to1, e = L4 + R_P + w * 256;
        WG_WAIT(0);
        bar_sync<NB_X, 256>();
        if (!last && elect_one()) load_chunk(sb + R_GB + w * 4096, s + 1, g2, bars + B_FB);
        reg_fence<16>(sc);
        if (w < 3) {
#pragma unroll
          for (int j = 0; j < 8; j++) {
            if ((j & 1) ? (j > 1 && (w == 0 || (w == 1 && j == 7))) : (j >= 4 || w != 1)) {
              const uint32_t t = pack2(sc[2 * j], sc[2 * j + 1]), o = (j >> 1) * 768 + (j & 1) * 128;
              st_async1(e + top + 3072 + o, t, bars + top + B_TS);
              sts32(e + o, t);
            }
          }
          __syncwarp();
          if (elect_one()) mbar_arrive(bars + B_TS);
        }
      } else {
        WG_WAIT(0);
        bar_sync<NB_X, 256>();
        if (!last && elect_one()) load_chunk(sb + R_GB + w * 4096, s + 1, g2, bars + B_FB);
      }
      TRACE(8);
      mbar_wait(bars + B_FA, 1);
      TRACE(11);
    }
    if (has_wo) {
      float* rslot = SLOT(s);
      uint32_t ob[4][4];
      float c[3][4];
      if (WG == 1) {
#pragma unroll
        for (int i = 0; i < 3; i++) ldsm4t(wa[i], woa + i * 4096);
        bar_sync<NB_D, 256>();
      }
      ldsm4t(ob[0], oxa);
      __syncwarp();
#pragma unroll
      for (int k = 0; k < 8; k++) {
        uint32_t nx[3][4];
        if ((k & 1) == 0 && k < 6) { ldsm4t(ob[(k >> 1) + 1], oxa + ((k >> 1) + 1) * 512); __syncwarp(); }
#pragma unroll
        for (int i = 0; i < 3; i++) {
          const uint32_t* o = ob[k >> 1] + (k & 1) * 2;
          if (k < 7) { ldsm4t(nx[i], woa + i * 4096 + (k + 1) * 512); if (i == 2) __syncwarp(); }
          if (k == 0) hmma0(c[i], wa[i][0], wa[i][1], wa[i][2], wa[i][3], o[0], o[1]);
          else hmma(c[i], wa[i][0], wa[i][1], wa[i][2], wa[i][3], o[0], o[1]);
#pragma unroll
          for (int q = 0; q < 4; q++) if (k < 7) wa[i][q] = nx[i][q];
        }
        if (k == ND_K && WG == 0) bar_arrive<NB_D, 256>();
      }
      const float* cv = &c[0][0];
      uint32_t r[6];
#pragma unroll
      for (int j = 0; j < 6; j++) r[j] = pack2(cv[2 * j], cv[2 * j + 1]);
      asm volatile("{\n.reg .pred p;\nsetp.lt.s32 p, %8, 0;\n@p bra.uni SKIP;\n"
                   "red.relaxed.gpu.global.add.noftz.v4.bf16x2 [%0], {%1, %2, %3, %7};\n"
                   "red.relaxed.gpu.global.add.noftz.v4.bf16x2 [%0+1024], {%4, %5, %6, %7};\nSKIP:\n}"
                   :: "l"(rslot), "r"(r[0]), "r"(r[1]), "r"(r[2]), "r"(r[3]), "r"(r[4]), "r"(r[5]), "r"(0x3f800000), "r"(s) : "memory");
    } else {
      bar_arrive<NB_D, 256>();
      if ((s & 3) == 0) {
        fence_gpu();
        if (s > 0 && elect_one()) red_add_u32(&g_flags[FL_ATT + 2 * (s - 4)], 1);
      }
      if (PFD && head < 8 && (PFD > 90 || s + PFD < NSEG) && elect_one())
        asm volatile("cp.async.bulk.prefetch.L2.global [%0], 4096;" :: "l"(g_h + (size_t)((PFD > 90 ? 0 : s + PFD) * 16 + head * 2 + rank) * 4096) : "memory");
      if (rank == 0 || head < 16)
        reinterpret_cast<uint4*>(g_slot)[((s + CLR_D) & 3) * 3072 + ((s + CLR_D) & 4) * 8 + rank * 2048 + head * 64 + opaque32(lane)] = make_uint4(0, 0, 0, 0);
    }
    const uint32_t t_red = clk32();
    uint32_t v[8];
    const float* slot = SLOT(s);
    TRACE(13);
    if (WG == 0) {
      if (!isC) {
        const int ln = opaque32(lane), kg = w - (ln >> 3);
        const uint32_t r16 = sb + R_P + w * 768 + (ln & 7) * 16;
        const uint32_t ta = r16 + (kg >= 0 ? kg * 128 : 640);
        const int dg = (ln >> 2) - 2 * (ln & 3);
        const uint32_t keep = dg > 0 ? 0xffffffffu : dg == 0 ? 0x0000ffffu : 0u;
        mbar_wait(bars + B_TS, par);
        uint32_t x[6], y[4];
        ldsm4t(x, ta); ldsm4t(y, ta + 3072); ldsm2t(x + 4, r16 + 512 + ((ln >> 3) & 1) * 3072);
#pragma unroll
        for (int j = 0; j < 5; j++) x[j] = hadd2(x[j], j < 4 ? y[j] : x[5]);
        x[0] = (x[0] & keep) | (0xff80ff80u & ~keep);
        float sv[10];
        exp10(sv, x);
        float sum = (((sv[0] + sv[1]) + (sv[2] + sv[3])) + ((sv[4] + sv[5]) + (sv[6] + sv[7]))) + (sv[8] + sv[9]);
        sum += __shfl_xor_sync(0xffffffffu, sum, 1);
        sum += __shfl_xor_sync(0xffffffffu, sum, 2);
        const float inv = rcp(sum);
#pragma unroll
        for (int j = 0; j < 5; j++) x[j] = pack2(sv[2 * j] * inv, sv[2 * j + 1] * inv);
        stsm4(r16 + (kg & 3) * 128, x);
        sts32(sb + ln * 4 + w * 768 + R_P + 512, x[4]);
        fence_async_smem();
        bar_arrive<NB_P, 256>();
      }
      while (clk32() - t_red < POLL_DELAY) {}
      load_red(v, slot);
      bar_sync<NB_E, 256>();
    } else {
      mbar_wait(bars + B_FB, 1);
    }
    TRACE(14);
    float ao[16];
    if (WG == 1) zero_regs<16>(ao);
    WG_FENCE();
#pragma unroll
    for (int k = 0; k < 32; k++) {
      if (WG == 0 && k == 16) WG_COMMIT();
      wg_rs32<1>(acc, W[16 + k][0], W[16 + k][1], W[16 + k][2], W[16 + k][3], dsc.tok[k]);
    }
    WG_COMMIT();
    TRACE(12);
    if (WG == 1) {
      if (!isC) {
        constexpr uint64_t dP = mkdesc(0x400 + R_P, 128, 768, 0);
        const uint64_t dV = mkdesc(0x400 + R_VT, 128, 512, 0) + rank * 256, dM = mkdesc(0x400 + R_VM, 0, 128, 0) + rank * 64;
        bar_sync<NB_P, 256>();
        WG_FENCE();
        wg_ss32<0>(ao, dV, dP); wg_ss32<0>(ao, dV + 16, dP + 16); wg_ss32<0>(ao, dM, dP + 32);
        WG_COMMIT();
      }
      bar_arrive<NB_E, 256>();
      if (elect_one()) mbar_expect(bars + B_XS + 8 * w, arm_bytes);
      while (clk32() - t_red < POLL_DELAY1) {}
      load_red(v, slot);
      bar_arrive<NB_W0, 128>();
    } else {
      WG_WAIT(1);
      bar_arrive<NB_F, 256>();
      sched_fence(head, 100);
      v[3] = opaque32(v[3]);
      const uint32_t tries = finish_red(v, slot);
      forward(std::integral_constant<int, 0>(), v, s, tries);
      TRACE(16);
    }
    WG_WAIT(0);
    reg_fence<16>(acc);
    if (WG == 0) bar_arrive<NB_G, 256>();
    TRACE(15);
    {
      uint32_t pq[8];
#pragma unroll
      for (int j = 0; j < 8; j++) pq[j] = pack2(acc[2 * j], acc[2 * j + 1]);
      if (WG == 1) {
        reg_fence<16>(ao);
#pragma unroll
        for (int j = 0; j < 8; j++) pk[j] = pack2(ao[2 * j], ao[2 * j + 1]);
      }
      if (!isC) {
        const uint32_t q = L4 + w * 256 + R_QK + WG * 5120;
#pragma unroll
        for (int j = 0; j < 8; j++) sts32(q + (j >> 1) * 1024 + (j & 1) * 128, pq[j]);
        if (WG == 1 && !ATT_LATE && s >= 0) store_att(s);
      } else {
        const uint32_t a = LV + warp * 1024;
        stsm4(a, pq); stsm4(a + 256, pq + 4);
      }
    }
    TRACE(17);
    if (WG == 1) {
      auto refill = [&]() {
        bar_sync<NB_F, 256>();
        if (s < NSEG - 2 && elect_one()) load_chunk(sb + R_GA + w * 4096, s + 2, 12 + w, bars + B_FA);
      };
      if (RF_FIRST) refill();
      if (has_wo) { v[3] = opaque32(v[3]); const uint32_t tries = finish_red(v, slot); forward(std::integral_constant<int, 1>(), v, s, tries); }
      if (!RF_FIRST) refill();
      TRACE(16);
    }
    if (isC && V_FENCE) { fence_async_smem(); __syncwarp(); }
    TRACE(18);
  }
  {
    constexpr uint32_t par = NSEG & 1;
    if (WG == 1 || isC) {
      float c[NCH][4], m[4];
      uint32_t b[3][6];
      const uint32_t ma = L16, m8 = L8;
#pragma unroll
      for (int i = 0; i < 18; i++) {
        if (i < 16) {
          if (i % 4 == 0) mbar_wait(bars + B_MB + (i / 4) * 8, par ^ 1);
          if (i < 12) { lds128(b[i % 3], ma + R_M1 + i * 768); lds64(b[i % 3] + 4, m8 + R_M1 + 512 + i * 768); }
          else { ldsm4(b[i % 3], ma + R_M2 + 4096 + (i - 12) * 768); ldsm2(b[i % 3] + 4, ma + R_M2 + 4096 + 512 + (i - 12) * 768); }
          if (i == CX_I && isC) send_vt();
          __syncwarp();
        }
        if (i >= 2) {
          const int j = i - 2;
#pragma unroll
          for (int q = 0; q < 3; q++) {
            const uint32_t* f = W[3 * j + q];
            if (3 * j + q < NCH) hmma0(c[3 * j + q], f[0], f[1], f[2], f[3], b[j % 3][2 * q], b[j % 3][2 * q + 1]);
            else hmma(c[(3 * j + q) % NCH], f[0], f[1], f[2], f[3], b[j % 3][2 * q], b[j % 3][2 * q + 1]);
          }
        }
      }
#pragma unroll
      for (int j = 0; j < 4; j++) m[j] = NCH == 3 ? (c[0][j] + c[1][j]) + c[2][j] : (c[0][j] + c[1][j]) + (c[2][j] + c[NCH - 1][j]);
      if (isC) bar_sync<NB_H, 256>();
      WG_FENCE();
#pragma unroll
      for (int k = 0; k < 16; k++) wg_ss8(m, dsc.tail_a[WG * 16 + k], dsc.tail_b[k] + 1024);
      WG_COMMIT();
      const uint32_t a = opaque32(L4 + w * 256 + (isC ? WG * 1024 + R_VM : R_QK + 4096 + WG * 5120));
      WG_WAIT(0);
      reg_fence<4>(m);
      const uint32_t p0 = pack2(m[0], m[1]), p1 = pack2(m[2], m[3]);
      if (isC) {
        st_async1(a + to1, p0, bars + B_VM + to1); st_async1(a + to1 + 128, p1, bars + B_VM + to1);
        st_async1(a + to2, p0, bars + B_VM + to2); st_async1(a + to2 + 128, p1, bars + B_VM + to2);
      } else {
        sts32(a, p0); sts32(a + 128, p1);
      }
    }
    if (WG == 1) bar_sync<NB_G, 256>();
    if (isC) {
      asm volatile("barrier.cluster.arrive.relaxed.aligned;" ::: "memory");
    } else if (WG == 1) {
      constexpr uint64_t dQ = mkdesc(0x400 + R_QK, 128, 1024, 0), dK = mkdesc(0x400 + R_QK + 5120, 128, 1024, 0);
      float sc[16];
      zero_regs<16>(sc);
      fence_async_smem();
      bar_sync<NB_B, 256>();
      WG_FENCE();
#pragma unroll
      for (int k = 0; k < 4; k++) wg_ss32<1>(sc, dK + k * 16, dQ + k * 16);
      WG_COMMIT();
      const uint32_t top = rank == 0 ? to2 : to1, e = L4 + R_P + w * 256;
      WG_WAIT(0);
      reg_fence<16>(sc);
      if (w < 3) {
#pragma unroll
        for (int j = 0; j < 8; j++) {
          if ((j & 1) ? (j > 1 && (w == 0 || (w == 1 && j == 7))) : (j >= 4 || w != 1)) {
            const uint32_t t = pack2(sc[2 * j], sc[2 * j + 1]), o = (j >> 1) * 768 + (j & 1) * 128;
            st_async1(e + top + 3072 + o, t, bars + top + B_TS);
            sts32(e + o, t);
          }
        }
        __syncwarp();
        if (elect_one()) mbar_arrive(bars + B_TS);
      }
      constexpr uint64_t dP = mkdesc(0x400 + R_P, 128, 768, 0);
      const uint64_t dV = mkdesc(0x400 + R_VT, 128, 512, 0) + rank * 256, dM = mkdesc(0x400 + R_VM, 0, 128, 0) + rank * 64;
      float ao[16];
      zero_regs<16>(ao);
      mbar_wait(bars + B_VT, par);
      mbar_wait(bars + B_VM, par);
      asm volatile("barrier.cluster.arrive.relaxed.aligned;" ::: "memory");
      bar_sync<NB_P, 256>();
      WG_FENCE();
      wg_ss32<0>(ao, dV, dP); wg_ss32<0>(ao, dV + 16, dP + 16); wg_ss32<0>(ao, dM, dP + 32);
      WG_COMMIT();
      WG_WAIT(0);
      reg_fence<16>(ao);
#pragma unroll
      for (int j = 0; j < 8; j++) pk[j] = pack2(ao[2 * j], ao[2 * j + 1]);
      store_att(NSEG - 1);
      bar_sync<NB_C, 128>();
      if (w == 0 && elect_one()) { fence_gpu(); red_add_u32(&g_flags[FL_ATT + 8 * 15], 1); }
    } else {
      fence_async_smem();
      bar_arrive<NB_B, 256>();
      const int ln = opaque32(lane), kg = w - (ln >> 3);
      const uint32_t r16 = sb + R_P + w * 768 + (ln & 7) * 16;
      const uint32_t ta = r16 + (kg >= 0 ? kg * 128 : 640);
      const int dg = (ln >> 2) - 2 * (ln & 3);
      const uint32_t keep = dg > 0 ? 0xffffffffu : dg == 0 ? 0x0000ffffu : 0u;
      mbar_wait(bars + B_TS, par);
      asm volatile("barrier.cluster.arrive.relaxed.aligned;" ::: "memory");
      uint32_t x[6], y[4];
      ldsm4t(x, ta); ldsm4t(y, ta + 3072); ldsm2t(x + 4, r16 + 512 + ((ln >> 3) & 1) * 3072);
#pragma unroll
      for (int j = 0; j < 5; j++) x[j] = hadd2(x[j], j < 4 ? y[j] : x[5]);
      x[0] = (x[0] & keep) | (0xff80ff80u & ~keep);
      float sv[10];
      exp10(sv, x);
      float sum = (((sv[0] + sv[1]) + (sv[2] + sv[3])) + ((sv[4] + sv[5]) + (sv[6] + sv[7]))) + (sv[8] + sv[9]);
      sum += __shfl_xor_sync(0xffffffffu, sum, 1);
      sum += __shfl_xor_sync(0xffffffffu, sum, 2);
      const float inv = rcp(sum);
#pragma unroll
      for (int j = 0; j < 5; j++) x[j] = pack2(sv[2 * j] * inv, sv[2 * j + 1] * inv);
      stsm4(r16 + (kg & 3) * 128, x);
      sts32(sb + ln * 4 + w * 768 + R_P + 512, x[4]);
      fence_async_smem();
      bar_arrive<NB_P, 256>();
    }
    asm volatile("barrier.cluster.wait.aligned;" ::: "memory");
  }
#undef L16
#undef L8
#undef L4
#undef SLOT
#undef LV
}

__global__ void __cluster_dims__(3, 1, 1) __launch_bounds__(256, 1)
kernel_R(const __grid_constant__ CUtensorMap tmq, const __grid_constant__ CUtensorMap tmk, const __grid_constant__ CUtensorMap tmv,
         const __grid_constant__ CUtensorMap tmo, const __grid_constant__ CUtensorMap tmm, const __nv_bfloat16* __restrict__ x,
         const __nv_bfloat16* __restrict__ mem0, const __nv_bfloat16* __restrict__ cvec, const __grid_constant__ RDesc dsc) {
  extern __shared__ __align__(1024) uint8_t smem[];
  const uint32_t sb = smem_u32(smem);
  uint32_t rank; asm("mov.u32 %0, %%cluster_ctarank;" : "=r"(rank));
  rank = __shfl_sync(0xffffffffu, rank, 0);
  const int cta = blockIdx.x, head = __shfl_sync(0xffffffffu, cta / 3, 0);
  const int tid = threadIdx.x, lane = tid & 31;
  const int warp = __shfl_sync(0xffffffffu, tid >> 5, 0);
  const int wg = warp >> 2, w = warp & 3;
  const uint32_t bars = sb + R_BAR;
  const CUtensorMap* tmw = rank == 2 ? &tmv : (wg == 0 ? &tmq : &tmk);
  const int fcol = head * 128 + (rank == 2 ? wg * 64 : (int)rank * 64);

  asm volatile("griddepcontrol.launch_dependents;");
  uint32_t W[48][4];
  {
    if (sb != (rank << 24) + 0x400) __trap();
    if (tid == 0) {
      sts64(bars + 248, rank, head);
      mbar_init(bars + B_MB, 4); mbar_init(bars + B_MB + 8, 1); mbar_init(bars + B_MB + 16, 1); mbar_init(bars + B_MB + 24, SELF_STAS ? 1 : rank == 2 ? 5 : 4);
      for (int i = B_XS; i <= B_X; i += 8) mbar_init(bars + i, i == B_FA || i == B_FB || (i == B_TS && rank < 2) ? 4 : 1);
      asm volatile("fence.mbarrier_init.release.cluster;" ::: "memory");
      fence_async_smem();
    }
    __syncthreads();
    asm volatile("barrier.cluster.arrive.relaxed.aligned;" ::: "memory");
    TS(0);
    const int nwm = rank == 0 ? 6 : 5, wm0 = rank == 0 ? 0 : 5 * rank + 1, nrg = cta < 64 ? 3 : 2;
    if (elect_one()) {
      if (warp == 0) { mbar_expect(bars + B_WM, nwm * 8192); mbar_expect(bars + B_X, nrg * 16384); }
      if (warp < nwm) tma2d_once(sb + R_GA + warp * 8192, &tmm, head * 64, (wm0 + warp) * 64, bars + B_WM);
#pragma unroll 1
      for (int r = 0; r < nrg; r++) bulk_g2s(sb + R_TAIL + (r * 8 + warp) * 2064, x + (size_t)((cta + 96 * r) * 8 + warp) * D_, 2048, bars + B_X);
      if (w == 0) mbar_expect(bars + B_STG + wg * 16, 49152);
      if (w < NW0) tma2d_once(sb + R_WO + wg * 49152 + w * 8192, tmw, fcol, rot_chunk(w, rank) * 64, bars + B_STG + wg * 16);
    }
    float* scr = reinterpret_cast<float*>(smem + R_VT);
#pragma unroll 1
    for (int i = tid; i < nwm * 64; i += 256) {
      const float c = __bfloat162float(cvec[wm0 * 64 + i]);
      scr[i] = __bfloat162float(__float2bfloat16(c / (1.f + __expf(-c))));
    }
    if (tid < 128) {
      uint32_t e[4] = {0u, 0u, 0u, 0u};
      if (cta >= 72 && (tid & 32)) {
        const uint16_t* mp = reinterpret_cast<const uint16_t*>(mem0) + 2 * (lane & 3) * D_ + (lane >> 2);
#pragma unroll
        for (int q = 0; q < 3; q++) {
          const int n = 3 * (tid >> 6) + q, col = wo_tile(3 * (cta & 7) + (n >> 1), (cta - 72) >> 3) * 16 + 8 * (n & 1);
          e[q] = mp[col] | (uint32_t)mp[col + D_] << 16;
        }
        e[3] = 0x42000000u;
      }
      reinterpret_cast<uint4*>(g_slot)[cta * 128 + tid] = make_uint4(e[0], e[1], e[2], e[3]);
    }
    __syncthreads();
    TS(1);
    mbar_wait_safe(bars + B_WM, 0);
    if (w < 6 - NW0 - NW2 && elect_one()) tma2d_once(sb + R_WO + wg * 49152 + (NW0 + w) * 8192, tmw, fcol, rot_chunk(NW0 + w, rank) * 64, bars + B_STG + wg * 16);
    {
      float a[8];
#pragma unroll
      for (int j = 0; j < 8; j++) a[j] = 0.f;
#pragma unroll 2
      for (int i = 0; i < 2 * nwm; i++) {
        uint32_t u[4];
        lds128(u, sb + R_GA + i * 4096 + tid * 16);
        const float sc = scr[i * 32 + (tid >> 3)];
#pragma unroll
        for (int j = 0; j < 4; j++) { a[2 * j] += sc * bf_lo(u[j]); a[2 * j + 1] += sc * bf_hi(u[j]); }
      }
#pragma unroll
      for (int j = 0; j < 8; j++) { a[j] += __shfl_xor_sync(0xffffffffu, a[j], 8); a[j] += __shfl_xor_sync(0xffffffffu, a[j], 16); }
      if (lane < 8) {
        sts128(sb + R_VT + 1536 + warp * 256 + lane * 32, __float_as_uint(a[0]), __float_as_uint(a[1]), __float_as_uint(a[2]), __float_as_uint(a[3]));
        sts128(sb + R_VT + 1552 + warp * 256 + lane * 32, __float_as_uint(a[4]), __float_as_uint(a[5]), __float_as_uint(a[6]), __float_as_uint(a[7]));
      }
    }
    __syncthreads();
    TS(2);
    if (warp == 7) {
      float t0 = 0.f, t1 = 0.f;
#pragma unroll
      for (int i = 0; i < 8; i++) { float t[2]; lds64f(t, sb + R_VT + 1536 + i * 256 + lane * 8); t0 += t[0]; t1 += t[1]; }
      reinterpret_cast<float2*>(g_modp + rank * 2048 + head * 64)[lane] = make_float2(t0, t1);
      fence_gpu();
      __syncwarp();
      if (lane == 0) red_add_u32(&g_flags[FL_S1], 1);
      __syncwarp();
    }
    mbar_wait_safe(bars + B_X, 0);
#pragma unroll 1
    for (int r = 0; r < nrg; r++) {
      float f[32];
#pragma unroll
      for (int i = 0; i < 4; i++) {
        uint32_t u[4];
        lds128(u, sb + R_TAIL + (r * 8 + warp) * 2064 + i * 512 + lane * 16);
#pragma unroll
        for (int j = 0; j < 4; j++) { f[8 * i + 2 * j] = bf_lo(u[j]); f[8 * i + 2 * j + 1] = bf_hi(u[j]); }
      }
      float t = 0.f;
#pragma unroll
      for (int i = 0; i < 32; i++) t += f[i];
#pragma unroll
      for (int o = 1; o < 32; o <<= 1) t += __shfl_xor_sync(0xffffffffu, t, o);
      const float mean = t * (1.f / D_);
      t = 0.f;
#pragma unroll
      for (int i = 0; i < 32; i++) t = fmaf(f[i] - mean, f[i] - mean, t);
#pragma unroll
      for (int o = 1; o < 32; o <<= 1) t += __shfl_xor_sync(0xffffffffu, t, o);
      const float rstd = rsqrtf(t * (1.f / D_) + 1e-5f);
      if (lane == 0) sts64(sb + R_VT + 3584 + (r * 8 + warp) * 8, __float_as_uint(rstd), __float_as_uint(-mean * rstd));
    }
    TS(3);
    if (w < NW2 && elect_one()) tma2d_once(sb + R_WO + wg * 49152 + (6 - NW2 + w) * 8192, tmw, fcol, rot_chunk(6 - NW2 + w, rank) * 64, bars + B_STG + wg * 16);
    if (w < PF1 && elect_one()) tma2d_prefetch(tmw, fcol, rot_chunk(6 + w, rank) * 64);
    if (tid == 0) wait_flag(&g_flags[FL_S1], 96);
    __syncthreads();
    TS(4);
    {
      float4 p[6];
#pragma unroll
      for (int i = 0; i < 6; i++) p[i] = __ldcg(reinterpret_cast<const float4*>(g_modp + (i >> 1) * 2048) + 2 * tid + (i & 1));
      if (w < PF2 && elect_one()) tma2d_prefetch(tmw, fcol, (9 + w) * 64);
      sts128(sb + R_VT + 5120 + tid * 16, pack2(p[0].x + p[2].x + p[4].x, p[0].y + p[2].y + p[4].y), pack2(p[0].z + p[2].z + p[4].z, p[0].w + p[2].w + p[4].w),
             pack2(p[1].x + p[3].x + p[5].x, p[1].y + p[3].y + p[5].y), pack2(p[1].z + p[3].z + p[5].z, p[1].w + p[3].w + p[5].w));
    }
    __syncthreads();
#pragma unroll 2
    for (int it = 0; it < 4 * nrg; it++) {
      const int r = it >> 2, rg = cta + 96 * r, c = 16 * warp + (lane >> 3) + 4 * (it & 3);
      uint32_t a[4], b[4], u[4], o[4];
      float t[2];
      lds128(u, sb + R_TAIL + (r * 8 + (lane & 7)) * 2064 + c * 16);
      lds128(a, sb + R_VT + 5120 + c * 16); lds128(b, sb + R_VT + 7168 + c * 16);
      lds64f(t, sb + R_VT + 3584 + (r * 8 + (lane & 7)) * 8);
#pragma unroll
      for (int j = 0; j < 4; j++)
        o[j] = pack2(fmaf(fmaf(bf_lo(u[j]), t[0], t[1]), 1.f + bf_lo(b[j]), bf_lo(a[j])), fmaf(fmaf(bf_hi(u[j]), t[0], t[1]), 1.f + bf_hi(b[j]), bf_hi(a[j])));
      *reinterpret_cast<uint4*>(g_h + (size_t)(rg >> 2) * 65536 + (lane & 7) * 16 + (c & 7) * 128 +
                                (c < 96 ? (c >> 3) * 4096 + (rg & 3) * 1024 : 49152 + (rg & 3) * 4096 + ((c >> 3) - 12) * 1024)) =
          make_uint4(o[0], o[1], o[2], o[3]);
    }
    TS(5);
    __syncthreads();
    TS(6);
    if (w < PF3 && elect_one()) tma2d_once(sb + R_TAIL + warp * 8192, tmw, fcol, 768 + w * 64, bars + B_TAIL);
    if (warp == 3 && lane == 0) { fence_gpu(); red_add_u32(&g_flags[FL_S2], 1); }
    __syncwarp();

    const uint32_t a0 = opaque32(sb + R_WO + wg * 49152 + ((lane >> 4) * 8 + (lane & 7)) * 128 + (((2 * w + ((lane >> 3) & 1)) ^ (lane & 7)) << 4));
    mbar_wait_safe(bars + B_STG + wg * 16, 0);
    TS(7);
#pragma unroll
    for (int i = 0; i < 24; i++) ldsm4t(W[i], a0 + i * 2048);
    if (!S2_LATE && tid == 0) wait_flag(&g_flags[FL_S2], 96);
    __syncthreads();
    if (!S2_LATE) asm volatile("fence.proxy.async.global;" ::: "memory");
    if (elect_one()) {
      if (!S2_LATE && wg == 0) load_chunk(sb + R_GA + w * 4096, 0, 12 + w, bars + B_FA);
      if (w == 0) mbar_expect(bars + B_STG + wg * 16 + 8, 49152);
#pragma unroll 1
      for (int c = w; c < 6; c += 4) tma2d_once(sb + R_WO + wg * 49152 + c * 8192, tmw, fcol, rot_chunk(6 + c, rank) * 64, bars + B_STG + wg * 16 + 8);
      if (warp == 0) mbar_expect(bars + B_TAIL, 65536);
      if (w >= PF3) tma2d_once(sb + R_TAIL + warp * 8192, tmw, fcol, 768 + w * 64, bars + B_TAIL);
      if (wg == 1) mbar_expect(bars + B_XS + 8 * w, w == 2 ? 0 : arm_size(w, rank == 2));
#pragma unroll 1
      for (int i = warp; i < PF4; i += 8) tma2d_prefetch(&tmo, 16 * wo_tile(i, rank), head * 128);
    }
    TS(8);
    if (S2_LATE && tid == 0) wait_flag(&g_flags[FL_S2], 96);
    mbar_wait_safe(bars + B_STG + wg * 16 + 8, 0);
    TS(9);
#pragma unroll
    for (int i = 0; i < 24; i++) ldsm4t(W[24 + i], a0 + i * 2048);
    __syncthreads();
    if (S2_LATE) {
      asm volatile("fence.proxy.async.global;" ::: "memory");
      if (wg == 0 && elect_one()) load_chunk(sb + R_GA + w * 4096, 0, 12 + w, bars + B_FA);
    }
    if (elect_one()) {
      const int n = rank == 2 ? 22 : 21;
      if (warp == 0) mbar_expect(bars + B_WO, n * 4096);
#pragma unroll 1
      for (int i = warp; i < n; i += 8) tma2d(sb + R_WO + i * 4096, &tmo, 16 * wo_tile(i, rank), head * 128, bars + B_WO);
    }
    sts32(sb + R_P + warp * 768 + 640 + lane * 4, wg == 0 ? 0u : 0xff80ff80u);
    mbar_wait_safe(bars + B_TAIL, 0);
    if (GO_EARLY && cta == GO_EARLY - 1 && tid == 0) red_add_u32(&g_flags[FL_GO], 1);
    asm volatile("barrier.cluster.wait.aligned;\nbarrier.cluster.arrive.relaxed.aligned;\nbarrier.cluster.wait.aligned;" ::: "memory");
  }
  uint32_t rh[2];
  lds64(rh, bars + 248);
  rh[0] = __shfl_sync(0xffffffffu, rh[0], 0); rh[1] = __shfl_sync(0xffffffffu, rh[1], 0);
  if (wg == 0) r_main<0>(W, dsc, rh[1], rh[0], lane, w);
  else r_main<1>(W, dsc, rh[1], rh[0], lane, w);
}

template <int TA, bool FIRST> __device__ __forceinline__ void wg_ss256(float* d, uint64_t a, uint64_t b) {
  if (FIRST)
    asm volatile("wgmma.mma_async.sync.aligned.m64n256k16.f32.bf16.bf16 {%0,%1,%2,%3,%4,%5,%6,%7,%8,%9,%10,%11,%12,%13,%14,%15,%16,%17,%18,%19,%20,%21,%22,%23,%24,%25,%26,%27,%28,%29,%30,%31,%32,%33,%34,%35,%36,%37,%38,%39,%40,%41,%42,%43,%44,%45,%46,%47,%48,%49,%50,%51,%52,%53,%54,%55,%56,%57,%58,%59,%60,%61,%62,%63,%64,%65,%66,%67,%68,%69,%70,%71,%72,%73,%74,%75,%76,%77,%78,%79,%80,%81,%82,%83,%84,%85,%86,%87,%88,%89,%90,%91,%92,%93,%94,%95,%96,%97,%98,%99,%100,%101,%102,%103,%104,%105,%106,%107,%108,%109,%110,%111,%112,%113,%114,%115,%116,%117,%118,%119,%120,%121,%122,%123,%124,%125,%126,%127}, %128, %129, 0, 1, 1, %130, 1;"
               : "=f"(d[0]), "=f"(d[1]), "=f"(d[2]), "=f"(d[3]), "=f"(d[4]), "=f"(d[5]), "=f"(d[6]), "=f"(d[7]),
                 "=f"(d[8]), "=f"(d[9]), "=f"(d[10]), "=f"(d[11]), "=f"(d[12]), "=f"(d[13]), "=f"(d[14]), "=f"(d[15]),
                 "=f"(d[16]), "=f"(d[17]), "=f"(d[18]), "=f"(d[19]), "=f"(d[20]), "=f"(d[21]), "=f"(d[22]), "=f"(d[23]),
                 "=f"(d[24]), "=f"(d[25]), "=f"(d[26]), "=f"(d[27]), "=f"(d[28]), "=f"(d[29]), "=f"(d[30]), "=f"(d[31]),
                 "=f"(d[32]), "=f"(d[33]), "=f"(d[34]), "=f"(d[35]), "=f"(d[36]), "=f"(d[37]), "=f"(d[38]), "=f"(d[39]),
                 "=f"(d[40]), "=f"(d[41]), "=f"(d[42]), "=f"(d[43]), "=f"(d[44]), "=f"(d[45]), "=f"(d[46]), "=f"(d[47]),
                 "=f"(d[48]), "=f"(d[49]), "=f"(d[50]), "=f"(d[51]), "=f"(d[52]), "=f"(d[53]), "=f"(d[54]), "=f"(d[55]),
                 "=f"(d[56]), "=f"(d[57]), "=f"(d[58]), "=f"(d[59]), "=f"(d[60]), "=f"(d[61]), "=f"(d[62]), "=f"(d[63]),
                 "=f"(d[64]), "=f"(d[65]), "=f"(d[66]), "=f"(d[67]), "=f"(d[68]), "=f"(d[69]), "=f"(d[70]), "=f"(d[71]),
                 "=f"(d[72]), "=f"(d[73]), "=f"(d[74]), "=f"(d[75]), "=f"(d[76]), "=f"(d[77]), "=f"(d[78]), "=f"(d[79]),
                 "=f"(d[80]), "=f"(d[81]), "=f"(d[82]), "=f"(d[83]), "=f"(d[84]), "=f"(d[85]), "=f"(d[86]), "=f"(d[87]),
                 "=f"(d[88]), "=f"(d[89]), "=f"(d[90]), "=f"(d[91]), "=f"(d[92]), "=f"(d[93]), "=f"(d[94]), "=f"(d[95]),
                 "=f"(d[96]), "=f"(d[97]), "=f"(d[98]), "=f"(d[99]), "=f"(d[100]), "=f"(d[101]), "=f"(d[102]), "=f"(d[103]),
                 "=f"(d[104]), "=f"(d[105]), "=f"(d[106]), "=f"(d[107]), "=f"(d[108]), "=f"(d[109]), "=f"(d[110]), "=f"(d[111]),
                 "=f"(d[112]), "=f"(d[113]), "=f"(d[114]), "=f"(d[115]), "=f"(d[116]), "=f"(d[117]), "=f"(d[118]), "=f"(d[119]),
                 "=f"(d[120]), "=f"(d[121]), "=f"(d[122]), "=f"(d[123]), "=f"(d[124]), "=f"(d[125]), "=f"(d[126]), "=f"(d[127])
               : "l"(a), "l"(b), "n"(TA));
  else
    asm volatile("wgmma.mma_async.sync.aligned.m64n256k16.f32.bf16.bf16 {%0,%1,%2,%3,%4,%5,%6,%7,%8,%9,%10,%11,%12,%13,%14,%15,%16,%17,%18,%19,%20,%21,%22,%23,%24,%25,%26,%27,%28,%29,%30,%31,%32,%33,%34,%35,%36,%37,%38,%39,%40,%41,%42,%43,%44,%45,%46,%47,%48,%49,%50,%51,%52,%53,%54,%55,%56,%57,%58,%59,%60,%61,%62,%63,%64,%65,%66,%67,%68,%69,%70,%71,%72,%73,%74,%75,%76,%77,%78,%79,%80,%81,%82,%83,%84,%85,%86,%87,%88,%89,%90,%91,%92,%93,%94,%95,%96,%97,%98,%99,%100,%101,%102,%103,%104,%105,%106,%107,%108,%109,%110,%111,%112,%113,%114,%115,%116,%117,%118,%119,%120,%121,%122,%123,%124,%125,%126,%127}, %128, %129, 1, 1, 1, %130, 1;"
               : "+f"(d[0]), "+f"(d[1]), "+f"(d[2]), "+f"(d[3]), "+f"(d[4]), "+f"(d[5]), "+f"(d[6]), "+f"(d[7]),
                 "+f"(d[8]), "+f"(d[9]), "+f"(d[10]), "+f"(d[11]), "+f"(d[12]), "+f"(d[13]), "+f"(d[14]), "+f"(d[15]),
                 "+f"(d[16]), "+f"(d[17]), "+f"(d[18]), "+f"(d[19]), "+f"(d[20]), "+f"(d[21]), "+f"(d[22]), "+f"(d[23]),
                 "+f"(d[24]), "+f"(d[25]), "+f"(d[26]), "+f"(d[27]), "+f"(d[28]), "+f"(d[29]), "+f"(d[30]), "+f"(d[31]),
                 "+f"(d[32]), "+f"(d[33]), "+f"(d[34]), "+f"(d[35]), "+f"(d[36]), "+f"(d[37]), "+f"(d[38]), "+f"(d[39]),
                 "+f"(d[40]), "+f"(d[41]), "+f"(d[42]), "+f"(d[43]), "+f"(d[44]), "+f"(d[45]), "+f"(d[46]), "+f"(d[47]),
                 "+f"(d[48]), "+f"(d[49]), "+f"(d[50]), "+f"(d[51]), "+f"(d[52]), "+f"(d[53]), "+f"(d[54]), "+f"(d[55]),
                 "+f"(d[56]), "+f"(d[57]), "+f"(d[58]), "+f"(d[59]), "+f"(d[60]), "+f"(d[61]), "+f"(d[62]), "+f"(d[63]),
                 "+f"(d[64]), "+f"(d[65]), "+f"(d[66]), "+f"(d[67]), "+f"(d[68]), "+f"(d[69]), "+f"(d[70]), "+f"(d[71]),
                 "+f"(d[72]), "+f"(d[73]), "+f"(d[74]), "+f"(d[75]), "+f"(d[76]), "+f"(d[77]), "+f"(d[78]), "+f"(d[79]),
                 "+f"(d[80]), "+f"(d[81]), "+f"(d[82]), "+f"(d[83]), "+f"(d[84]), "+f"(d[85]), "+f"(d[86]), "+f"(d[87]),
                 "+f"(d[88]), "+f"(d[89]), "+f"(d[90]), "+f"(d[91]), "+f"(d[92]), "+f"(d[93]), "+f"(d[94]), "+f"(d[95]),
                 "+f"(d[96]), "+f"(d[97]), "+f"(d[98]), "+f"(d[99]), "+f"(d[100]), "+f"(d[101]), "+f"(d[102]), "+f"(d[103]),
                 "+f"(d[104]), "+f"(d[105]), "+f"(d[106]), "+f"(d[107]), "+f"(d[108]), "+f"(d[109]), "+f"(d[110]), "+f"(d[111]),
                 "+f"(d[112]), "+f"(d[113]), "+f"(d[114]), "+f"(d[115]), "+f"(d[116]), "+f"(d[117]), "+f"(d[118]), "+f"(d[119]),
                 "+f"(d[120]), "+f"(d[121]), "+f"(d[122]), "+f"(d[123]), "+f"(d[124]), "+f"(d[125]), "+f"(d[126]), "+f"(d[127])
               : "l"(a), "l"(b), "n"(TA));
}
template <int TA, bool FIRST> __device__ __forceinline__ void wg_ss128(float* d, uint64_t a, uint64_t b) {
  if (FIRST)
    asm volatile("wgmma.mma_async.sync.aligned.m64n128k16.f32.bf16.bf16 {%0,%1,%2,%3,%4,%5,%6,%7,%8,%9,%10,%11,%12,%13,%14,%15,%16,%17,%18,%19,%20,%21,%22,%23,%24,%25,%26,%27,%28,%29,%30,%31,%32,%33,%34,%35,%36,%37,%38,%39,%40,%41,%42,%43,%44,%45,%46,%47,%48,%49,%50,%51,%52,%53,%54,%55,%56,%57,%58,%59,%60,%61,%62,%63}, %64, %65, 0, 1, 1, %66, 1;"
               : "=f"(d[0]), "=f"(d[1]), "=f"(d[2]), "=f"(d[3]), "=f"(d[4]), "=f"(d[5]), "=f"(d[6]), "=f"(d[7]),
                 "=f"(d[8]), "=f"(d[9]), "=f"(d[10]), "=f"(d[11]), "=f"(d[12]), "=f"(d[13]), "=f"(d[14]), "=f"(d[15]),
                 "=f"(d[16]), "=f"(d[17]), "=f"(d[18]), "=f"(d[19]), "=f"(d[20]), "=f"(d[21]), "=f"(d[22]), "=f"(d[23]),
                 "=f"(d[24]), "=f"(d[25]), "=f"(d[26]), "=f"(d[27]), "=f"(d[28]), "=f"(d[29]), "=f"(d[30]), "=f"(d[31]),
                 "=f"(d[32]), "=f"(d[33]), "=f"(d[34]), "=f"(d[35]), "=f"(d[36]), "=f"(d[37]), "=f"(d[38]), "=f"(d[39]),
                 "=f"(d[40]), "=f"(d[41]), "=f"(d[42]), "=f"(d[43]), "=f"(d[44]), "=f"(d[45]), "=f"(d[46]), "=f"(d[47]),
                 "=f"(d[48]), "=f"(d[49]), "=f"(d[50]), "=f"(d[51]), "=f"(d[52]), "=f"(d[53]), "=f"(d[54]), "=f"(d[55]),
                 "=f"(d[56]), "=f"(d[57]), "=f"(d[58]), "=f"(d[59]), "=f"(d[60]), "=f"(d[61]), "=f"(d[62]), "=f"(d[63])
               : "l"(a), "l"(b), "n"(TA));
  else
    asm volatile("wgmma.mma_async.sync.aligned.m64n128k16.f32.bf16.bf16 {%0,%1,%2,%3,%4,%5,%6,%7,%8,%9,%10,%11,%12,%13,%14,%15,%16,%17,%18,%19,%20,%21,%22,%23,%24,%25,%26,%27,%28,%29,%30,%31,%32,%33,%34,%35,%36,%37,%38,%39,%40,%41,%42,%43,%44,%45,%46,%47,%48,%49,%50,%51,%52,%53,%54,%55,%56,%57,%58,%59,%60,%61,%62,%63}, %64, %65, 1, 1, 1, %66, 1;"
               : "+f"(d[0]), "+f"(d[1]), "+f"(d[2]), "+f"(d[3]), "+f"(d[4]), "+f"(d[5]), "+f"(d[6]), "+f"(d[7]),
                 "+f"(d[8]), "+f"(d[9]), "+f"(d[10]), "+f"(d[11]), "+f"(d[12]), "+f"(d[13]), "+f"(d[14]), "+f"(d[15]),
                 "+f"(d[16]), "+f"(d[17]), "+f"(d[18]), "+f"(d[19]), "+f"(d[20]), "+f"(d[21]), "+f"(d[22]), "+f"(d[23]),
                 "+f"(d[24]), "+f"(d[25]), "+f"(d[26]), "+f"(d[27]), "+f"(d[28]), "+f"(d[29]), "+f"(d[30]), "+f"(d[31]),
                 "+f"(d[32]), "+f"(d[33]), "+f"(d[34]), "+f"(d[35]), "+f"(d[36]), "+f"(d[37]), "+f"(d[38]), "+f"(d[39]),
                 "+f"(d[40]), "+f"(d[41]), "+f"(d[42]), "+f"(d[43]), "+f"(d[44]), "+f"(d[45]), "+f"(d[46]), "+f"(d[47]),
                 "+f"(d[48]), "+f"(d[49]), "+f"(d[50]), "+f"(d[51]), "+f"(d[52]), "+f"(d[53]), "+f"(d[54]), "+f"(d[55]),
                 "+f"(d[56]), "+f"(d[57]), "+f"(d[58]), "+f"(d[59]), "+f"(d[60]), "+f"(d[61]), "+f"(d[62]), "+f"(d[63])
               : "l"(a), "l"(b), "n"(TA));
}
template <int TA, bool FIRST> __device__ __forceinline__ void wg_ss64(float* d, uint64_t a, uint64_t b) {
  if (FIRST)
    asm volatile("wgmma.mma_async.sync.aligned.m64n64k16.f32.bf16.bf16 {%0,%1,%2,%3,%4,%5,%6,%7,%8,%9,%10,%11,%12,%13,%14,%15,%16,%17,%18,%19,%20,%21,%22,%23,%24,%25,%26,%27,%28,%29,%30,%31}, %32, %33, 0, 1, 1, %34, 1;"
               : "=f"(d[0]), "=f"(d[1]), "=f"(d[2]), "=f"(d[3]), "=f"(d[4]), "=f"(d[5]), "=f"(d[6]), "=f"(d[7]),
                 "=f"(d[8]), "=f"(d[9]), "=f"(d[10]), "=f"(d[11]), "=f"(d[12]), "=f"(d[13]), "=f"(d[14]), "=f"(d[15]),
                 "=f"(d[16]), "=f"(d[17]), "=f"(d[18]), "=f"(d[19]), "=f"(d[20]), "=f"(d[21]), "=f"(d[22]), "=f"(d[23]),
                 "=f"(d[24]), "=f"(d[25]), "=f"(d[26]), "=f"(d[27]), "=f"(d[28]), "=f"(d[29]), "=f"(d[30]), "=f"(d[31])
               : "l"(a), "l"(b), "n"(TA));
  else
    asm volatile("wgmma.mma_async.sync.aligned.m64n64k16.f32.bf16.bf16 {%0,%1,%2,%3,%4,%5,%6,%7,%8,%9,%10,%11,%12,%13,%14,%15,%16,%17,%18,%19,%20,%21,%22,%23,%24,%25,%26,%27,%28,%29,%30,%31}, %32, %33, 1, 1, 1, %34, 1;"
               : "+f"(d[0]), "+f"(d[1]), "+f"(d[2]), "+f"(d[3]), "+f"(d[4]), "+f"(d[5]), "+f"(d[6]), "+f"(d[7]),
                 "+f"(d[8]), "+f"(d[9]), "+f"(d[10]), "+f"(d[11]), "+f"(d[12]), "+f"(d[13]), "+f"(d[14]), "+f"(d[15]),
                 "+f"(d[16]), "+f"(d[17]), "+f"(d[18]), "+f"(d[19]), "+f"(d[20]), "+f"(d[21]), "+f"(d[22]), "+f"(d[23]),
                 "+f"(d[24]), "+f"(d[25]), "+f"(d[26]), "+f"(d[27]), "+f"(d[28]), "+f"(d[29]), "+f"(d[30]), "+f"(d[31])
               : "l"(a), "l"(b), "n"(TA));
}

constexpr int H_STAGE = 49152, H_NST = 4;
constexpr int H_STG = H_NST * H_STAGE;
constexpr int H_VEC = H_STG + 16384;
constexpr int H_BAR = H_VEC + 6144;
constexpr int H_SMEM = H_BAR + 256;
constexpr int HB_FULL = 0, HB_EMPTY = 32, HB_IFULL = 64, HB_IEMPTY = 80, HB_ITEM = 96, HB_INC = 104, HB_HAVE = 116, HB_NEXT = 160;
enum { IT_END = 0, IT_MOD = 1, IT_XT = 2, IT_OUT = 3, IT_UV = 4, IT_F1 = 5, IT_F2 = 6 };
constexpr int MAX_ITEMS = 1400;
#define D_MOD 4
#define D_UV 2
#define UV_WAIT 0
#define PF_MAPS 1
#define R_LATE 1
#define CH_FENCE 1
#define CH_FENCE1 1
#define N_UV1 20
#define FINE 1
#define B_EARLY 1
#define VEC_EARLY 1
#define HOLD 1
#define PEEK 4
#define ECL0 2
#define ECL1 6
constexpr uint32_t IT_GATHER = 0x80000000u;
__host__ __device__ __forceinline__ int split_tile(int type, int mt, int idx) { return ((type == IT_F2 ? 0 : mt >= 12 ? 4 : 8) + (mt & 3)) * 16 + idx; }
__device__ __forceinline__ int item_sz(uint32_t it) { return (it >> 13) & 3; }
struct HList { uint32_t n; uint32_t it[MAX_ITEMS]; };
__device__ __forceinline__ void item_deps(int type, int mt, int lane, int& f, uint32_t& target) {
  f = FL_GO; target = 1;
  if (type == IT_OUT) { f = lane == 0 ? FL_ATT + 8 * mt : lane == 1 ? FL_XT + 8 * mt : lane == 9 ? FL_MODA : FL_MOD; target = lane == 0 ? 64 : lane == 1 ? 2 : lane == 9 ? 8 : 16; }
  else if (type == IT_F1) { f = lane < 8 ? FL_OUT + 8 * mt + lane : FL_UV; target = lane < 8 ? 2 : 28; }
  else if (type == IT_F2) { f = lane < 8 ? FL_F1 + 8 * mt + lane : FL_MODB; target = 8; }
}
#define HT(i)

__device__ __forceinline__ uint32_t tile_lane(int warp, int lane) { return warp * 1024 + (lane >> 2) * 64 + (((lane & 3) ^ (lane >> 3)) << 4); }
__device__ __forceinline__ constexpr uint32_t tile_off(int c, int h) { return (c >> 1) * 16384 + (c & 1) * 8192 + h * 512; }

template <int BN, int TA, class PRE, class POST>
__device__ __forceinline__ void h_mainloop(float* acc, uint32_t sb, int nst, uint32_t& st, uint32_t& ph, int wg, bool leader, PRE pre, POST post) {
  constexpr int KS = BN == 64 ? 8 : 4;
  constexpr uint32_t BOFF = BN == 64 ? 32768 : 16384;
  const uint64_t da0 = TA ? mkdesc(sb + wg * 1024, 2048, 128, 0) : mkdesc(sb + wg * 4096, 16, 512, 2);
  auto release = [&](uint32_t s) { if (leader) mbar_arrive(sb + H_BAR + HB_EMPTY + s * 8); };
  const uint64_t db0 = mkdesc(sb + BOFF, 8192, 1024, 1);
  constexpr uint32_t kh = 512;
  uint32_t prev = 0;
  auto stage = [&](auto first) {
    constexpr bool FIRST = decltype(first)::value;
    mbar_wait(sb + H_BAR + HB_FULL + st * 8, ph);
    if (FIRST) HT(1);
    const uint64_t da = da0 + st * (H_STAGE >> 4), db = db0 + st * (H_STAGE >> 4);
    WG_FENCE();
#pragma unroll
    for (int k = 0; k < KS; k++) {
      const uint64_t a = da + (k >> 2) * 1024 + (TA ? (k & 3) * 256 : ((k >> 1) & 1) * kh + (k & 1) * 2), b = db + k * 128;
      if (FIRST && k == 0) { if (BN == 256) wg_ss256<TA, true>(acc, a, b); else if (BN == 128) wg_ss128<TA, true>(acc, a, b); else wg_ss64<TA, true>(acc, a, b); }
      else { if (BN == 256) wg_ss256<TA, false>(acc, a, b); else if (BN == 128) wg_ss128<TA, false>(acc, a, b); else wg_ss64<TA, false>(acc, a, b); }
    }
    WG_COMMIT();
  };
  stage(std::true_type());
  pre();
  prev = st;
  if (++st == H_NST) { st = 0; ph ^= 1; }
#pragma unroll 1
  for (int i = 1; i < nst; i++) {
    stage(std::false_type());
    WG_WAIT(1);
    release(prev);
    prev = st;
    if (++st == H_NST) { st = 0; ph ^= 1; }
  }
  post();
  WG_WAIT(0);
  HT(2);
  reg_fence<BN / 2>(acc);
  release(prev);
}

template <int BN, bool FINAL, class POST>
__device__ __forceinline__ void h_residual(uint32_t sb, uint32_t va, int mt, int n0, uint32_t& st, uint32_t& ph, int warp, int lane, __nv_bfloat16* out,
                                           POST post, int part = 0, int lgp = 0, bool gather = false) {
  const size_t toff = (size_t)(mt * 16 + (n0 >> 6)) * 16384 + tile_lane(warp, lane);
  uint4 r[BN / 16];
  auto load_r = [&]() {
#pragma unroll
    for (int i = 0; i < BN / 16; i++) r[i] = __ldcg(reinterpret_cast<const uint4*>(g_x1 + toff + tile_off(i >> 1, i & 1)));
  };
  const bool partial = BN == 64 && lgp > 0 && !gather;
  if (!R_LATE && !partial) load_r();
  float acc[BN / 2];
  h_mainloop<BN, FINAL ? 0 : 1>(acc, sb, ((FINAL ? 56 : 64) / (BN == 64 ? 2 : 1)) >> lgp, st, ph, warp >> 2, (warp & 3) == 0 && lane == 0,
                                [&]() { if (R_LATE && !partial) load_r(); }, post);
  if (BN == 64 && lgp > 0) {
    if (partial) {
      float4* ws = reinterpret_cast<float4*>(g_ws) + (size_t)split_tile(FINAL ? IT_F2 : IT_OUT, mt, n0 >> 6) * 8192 + part * 2048 + warp * 32 + lane;
#pragma unroll
      for (int i = 0; i < 8; i++) ws[i * 256] = make_float4(acc[4 * i], acc[4 * i + 1], acc[4 * i + 2], acc[4 * i + 3]);
      return;
    }
#pragma unroll 1
    for (int p = 1; p < (1 << lgp); p++) {
      mbar_wait(sb + H_BAR + HB_FULL + st * 8, ph);
#pragma unroll
      for (int i = 0; i < 8; i++) {
        float o[4];
        lds128f(o, sb + st * H_STAGE + i * 4096 + warp * 512 + lane * 16);
        acc[4 * i] += o[0]; acc[4 * i + 1] += o[1]; acc[4 * i + 2] += o[2]; acc[4 * i + 3] += o[3];
      }
      reg_fence<32>(acc);
      bar_sync<1, 256>();
      if ((warp & 3) == 0 && lane == 0) mbar_arrive(sb + H_BAR + HB_EMPTY + st * 8);
      if (++st == H_NST) { st = 0; ph ^= 1; }
    }
  }
  float sm[4] = {0.f, 0.f, 0.f, 0.f};
  const uint32_t stg = sb + H_STG + warp * 2048;
#pragma unroll
  for (int c = 0; c < BN / 32; c++) {
    uint32_t y[2][4] = {{r[2 * c].x, r[2 * c].y, r[2 * c].z, r[2 * c].w}, {r[2 * c + 1].x, r[2 * c + 1].y, r[2 * c + 1].z, r[2 * c + 1].w}}, z[2][4];
#pragma unroll
    for (int j = 0; j < 4; j++) {
      const uint32_t gt = lds32(va + c * 64 + j * 16 + (lane & 3) * 4);
      const uint32_t cb = FINAL ? 0 : lds32(va + 512 + c * 64 + j * 16 + (lane & 3) * 4);
#pragma unroll
      for (int h = 0; h < 2; h++) {
        const float* a = acc + c * 16 + j * 4 + h * 2;
        y[h][j] = pack2(fmaf(bf_lo(gt), a[0], bf_lo(y[h][j])), fmaf(bf_hi(gt), a[1], bf_hi(y[h][j])));
        if (!FINAL) {
          const float p = bf_lo(y[h][j]), q = bf_hi(y[h][j]);
          sm[2 * h] += p + q;
          sm[2 * h + 1] = fmaf(p, p, fmaf(q, q, sm[2 * h + 1]));
          z[h][j] = pack2(fmaf(p, bf_lo(cb), p), fmaf(q, bf_hi(cb), q));
        }
      }
    }
    if (!FINAL) {
#pragma unroll
      for (int h = 0; h < 2; h++) {
        const size_t o = toff + tile_off(c, h);
        *reinterpret_cast<uint4*>(g_x1 + o) = make_uint4(y[h][0], y[h][1], y[h][2], y[h][3]);
        *reinterpret_cast<uint4*>(g_h2 + o) = make_uint4(z[h][0], z[h][1], z[h][2], z[h][3]);
      }
    } else {
#pragma unroll
      for (int h = 0; h < 2; h++) stsm4(stg + (h * 8 + (lane & 7)) * 128 + ((((c & 1) * 4 + (lane >> 3)) ^ (lane & 7)) << 4), y[h]);
      if (c & 1) {
        __syncwarp();
#pragma unroll
        for (int j = 0; j < 4; j++) {
          const int rr = 4 * j + (lane >> 3);
          uint32_t v[4];
          lds128(v, stg + rr * 128 + (((lane & 7) ^ (rr & 7)) << 4));
          *reinterpret_cast<uint4*>(out + (size_t)(mt * 128 + warp * 16 + rr) * D_ + n0 + (c >> 1) * 64 + (lane & 7) * 8) = make_uint4(v[0], v[1], v[2], v[3]);
        }
        __syncwarp();
      }
    }
    if (CH_FENCE && c + 1 < BN / 32) sched_fence(lane, 100);
  }
  if (!FINAL) {
#pragma unroll
    for (int j = 0; j < 4; j++) { sm[j] += __shfl_xor_sync(0xffffffffu, sm[j], 1); sm[j] += __shfl_xor_sync(0xffffffffu, sm[j], 2); }
    const int t = lane & 3;
    const float sv = t == 0 ? sm[0] : t == 1 ? sm[1] : t == 2 ? sm[2] : sm[3];
    asm volatile("red.relaxed.gpu.global.add.f32 [%0], %1;" :: "l"(g_stat + (mt * 128 + warp * 16 + (t >> 1) * 8 + (lane >> 2)) * 2 + (t & 1)), "f"(sv) : "memory");
  }
}

__device__ __forceinline__ float silu_mul(float hg, float u) {
  float t; asm("tanh.approx.f32 %0, %1;" : "=f"(t) : "f"(hg));
  const float h = hg * u;
  return fmaf(h, t, h);
}

template <int BN>
__device__ __forceinline__ void h_swiglu(const float* acc, uint32_t va, int mt, int kb0, int warp, int lane) {
  uint8_t* ap = g_act + (size_t)(mt * 56 + kb0) * 16384 + tile_lane(warp, lane);
  float rs[2], nm[2], rh[2];
#pragma unroll
  for (int h = 0; h < 2; h++) {
    float t[2];
    lds64f(t, va + 2048 + (warp * 16 + h * 8 + (lane >> 2)) * 8);
    const float mean = t[0] * (1.f / D_);
    rs[h] = rsqrtf(fmaxf(t[1] * (1.f / D_) - mean * mean, 0.f) + 1e-5f);
    nm[h] = -mean * rs[h];
    rh[h] = 0.5f * rs[h];
  }
#pragma unroll
  for (int c = 0; c < BN / 64; c++) {
    uint32_t y[2][4];
#pragma unroll
    for (int j = 0; j < 4; j++) {
      const float* g = acc + 16 * c + 4 * j; const float* u = g + BN / 4;
      float p[4], q[4], o[4];
      lds128f(p, va + (4 * c + j) * 128 + (lane & 3) * 32); lds128f(q, va + (4 * c + j) * 128 + (lane & 3) * 32 + 16);
#pragma unroll
      for (int e = 0; e < 4; e++)
        o[e] = silu_mul(fmaf(rh[e >> 1], g[e], fmaf(nm[e >> 1], p[e & 1], p[2 + (e & 1)])), fmaf(rs[e >> 1], u[e], fmaf(nm[e >> 1], q[e & 1], q[2 + (e & 1)])));
      y[0][j] = pack2(o[0], o[1]); y[1][j] = pack2(o[2], o[3]);
    }
#pragma unroll
    for (int h = 0; h < 2; h++)
      *reinterpret_cast<uint4*>(ap + tile_off(c, h)) = make_uint4(y[h][0], y[h][1], y[h][2], y[h][3]);
    if (CH_FENCE1 && c + 1 < BN / 64) sched_fence(lane, 100);
  }
}

__global__ void __launch_bounds__(384, 1)
kernel_H(const __grid_constant__ CUtensorMap tmo, const __grid_constant__ CUtensorMap tm1, const __grid_constant__ CUtensorMap tm3,
         const __grid_constant__ CUtensorMap tm2, const __grid_constant__ CUtensorMap tmm, const __nv_bfloat16* __restrict__ x,
         const __nv_bfloat16* __restrict__ cvec, __nv_bfloat16* __restrict__ out, const __grid_constant__ HList list) {
  extern __shared__ __align__(1024) uint8_t smem[];
  constexpr uint32_t sb = 0x400, bars = sb + H_BAR;
  const int tid = threadIdx.x, lane = tid & 31;
  const int warp = __shfl_sync(0xffffffffu, tid >> 5, 0);
  if (tid == 0) {
    if (smem_u32(smem) != sb) __trap();
    for (int i = 0; i < H_NST; i++) { mbar_init(bars + HB_FULL + i * 8, 1); mbar_init(bars + HB_EMPTY + i * 8, 2); }
    for (int i = 0; i < 2; i++) { mbar_init(bars + HB_IFULL + i * 8, 1); mbar_init(bars + HB_IEMPTY + i * 8, 3); }
    mbar_init(bars + HB_NEXT, 1);
    fence_async_smem();
    if (PF_MAPS) {
      const CUtensorMap* maps[5] = {&tmm, &tm1, &tm3, &tmo, &tm2};
#pragma unroll
      for (int i = 0; i < 5; i++) asm volatile("prefetch.tensormap [%0];" :: "l"(maps[i]) : "memory");
    }
  }
  __syncthreads();
  if (warp >= 8) {
    asm volatile("setmaxnreg.dec.sync.aligned.u32 40;");
    if (warp == 8) {
      uint32_t st = 0, ph = 1;
#pragma unroll 1
      for (uint32_t n = 0;; n++) {
        mbar_wait(bars + HB_IFULL + (n & 1) * 8, (n >> 1) & 1);
        const uint32_t it = __shfl_sync(0xffffffffu, lds32(bars + HB_ITEM + (n & 1) * 4), 0);
        uint32_t have = __shfl_sync(0xffffffffu, lds32(bars + HB_HAVE + (n & 1) * 4), 0);
        if (elect_one()) mbar_arrive(bars + HB_IEMPTY + (n & 1) * 8);
        const int type = it & 7, mt = (it >> 3) & 15, idx = (it >> 7) & 63, sz = item_sz(it), part = (it >> 15) & 3, lgp = (it >> 17) & 3;
        if (type == IT_END) break;
        int f; uint32_t target, first = 0;
        item_deps(type, mt, opaque32(lane), f, target);
        if (type == IT_OUT) first = 3;
        const int gsh = type == IT_F1 ? 1 : type == IT_F2 ? 3 : 6;
        if (type >= IT_F1) first = FINE ? 1u << ((part * (56 >> lgp)) >> gsh) : type == IT_F1 ? 255u : 127u;
        auto need = [&](int g) {
          if (!((have >> g) & 1)) {
            if (lane == g) wait_flag2(&g_flags[f], target);
            __syncwarp();
            asm volatile("fence.proxy.async.global;" ::: "memory");
            have |= 1u << g;
          }
        };
        const bool has_a = type == IT_OUT || type >= IT_F1;
        if ((have & first) != first) {
          uint32_t c = 0;
          while (((have = __ballot_sync(0xffffffffu, ld_acquire(&g_flags[f]) >= target)) & first) != first) { if (++c > 20000000u) __trap(); __nanosleep(20); }
          asm volatile("fence.proxy.async.global;" ::: "memory");
        }
        if (type == IT_XT && elect_one()) mbar_arrive(bars + HB_NEXT);
        if (type != IT_XT) {
          const uint8_t* ap = type == IT_OUT ? g_att + (size_t)mt * 64 * 16384 : type == IT_F1 ? g_h2 + (size_t)mt * 16 * 16384 : g_act + (size_t)mt * 56 * 16384;
          const int nkb = (type == IT_OUT ? 64 : type == IT_F2 ? 56 : 16) >> lgp;
          const uint32_t abytes = has_a ? (sz == 2 ? 32768 : 16384) : 0, bytes = (sz == 0 ? 32768 : 16384) + abytes;
          const int dk = sz == 2 ? 1 : 0;
          const uint32_t late = type == IT_OUT ? 0x300 : type == IT_F1 ? 0x1ff : 0x100;
          const int kvec = !has_a || (lgp && !(it & IT_GATHER)) ? -1 : VEC_EARLY && (have & late) == late ? part * nkb + 1 + dk : (part + 1) * nkb - 1 - dk;
          const int knext = max(part * nkb, (part + 1) * nkb - ((sz == 0 ? ECL0 : ECL1) << dk));
#pragma unroll 1
          for (int kb = part * nkb; kb < (part + 1) * nkb; kb += 1 + dk) {
            const uint32_t d = sb + st * H_STAGE, fb = bars + HB_FULL + st * 8;
            mbar_wait(bars + HB_EMPTY + st * 8, ph);
            if (has_a) need(kb >> gsh);
            if (kb == kvec) {
              need(8);
              if (type == IT_OUT) need(9);
              if (elect_one()) {
                const bool f1 = type == IT_F1;
                const int c0 = f1 ? idx * (128 >> sz) : idx * (256 >> sz);
                const uint32_t v = sb + H_VEC + (n & 1) * 3072;
                const uint32_t n0 = (f1 ? 2048 : 512) >> sz, n1 = f1 ? 1024 : n0;
                asm volatile("mbarrier.expect_tx.relaxed.cta.shared::cta.b64 [%0], %1;" :: "r"(fb), "r"(n0 + n1) : "memory");
                bulk_g2s(v, f1 ? (const void*)(g_uv + c0 * 4) : (const void*)(g_mod + (type == IT_OUT ? 2 : 5) * D_ + c0), n0, fb);
                bulk_g2s(v + (f1 ? 2048 : 512), f1 ? (const void*)(g_stat + mt * 256) : (const void*)(g_mod + 4 * D_ + c0), n1, fb);
              }
            }
            if (elect_one()) {
              mbar_expect(fb, bytes);
              if (has_a) bulk_g2s(d, ap + (size_t)kb * 16384, abytes, fb);
              if (kb == knext) mbar_arrive(bars + HB_NEXT);
            }
            if (++st == H_NST) { st = 0; ph ^= 1; }
          }
          if (it & IT_GATHER) {
            const uint32_t i2 = opaque32(it), np = 1u << ((i2 >> 17) & 3);
            const int tile = split_tile(i2 & 7, (i2 >> 3) & 15, (i2 >> 7) & 63);
            if (lane == 0) wait_flag2(&g_flags[FL_SPL + tile], np - 1);
            __syncwarp();
            asm volatile("fence.proxy.async.global;" ::: "memory");
#pragma unroll 1
            for (uint32_t p = 1; p < np; p++) {
              const uint32_t fb = bars + HB_FULL + st * 8;
              mbar_wait(bars + HB_EMPTY + st * 8, ph);
              if (elect_one()) {
                mbar_expect(fb, 32768);
                bulk_g2s(sb + st * H_STAGE, g_ws + (size_t)tile * 32768 + (((i2 >> 15) & 3) ^ p) * 8192, 32768, fb);
              }
              if (++st == H_NST) { st = 0; ph ^= 1; }
            }
          }
        }
      }
    } else if (warp >= 10) {
      const int hb = warp - 10;
      uint32_t st = 0, ph = 1;
#pragma unroll 1
      for (uint32_t n = 0;; n++) {
        mbar_wait(bars + HB_IFULL + (n & 1) * 8, (n >> 1) & 1);
        const uint32_t it = __shfl_sync(0xffffffffu, lds32(bars + HB_ITEM + (n & 1) * 4), 0);
        const int type = it & 7, idx = (it >> 7) & 63, sz = item_sz(it), part = (it >> 15) & 3, lgp = (it >> 17) & 3;
        if (type == IT_END) break;
        if (elect_one()) mbar_arrive(bars + HB_IEMPTY + (n & 1) * 8);
        if (type == IT_XT) continue;
        const bool ffn1 = type == IT_F1 || type == IT_UV;
        const int nkb = (type == IT_OUT ? 64 : type == IT_F2 ? 56 : 16) >> lgp;
        const CUtensorMap* tb = type == IT_OUT ? &tmo : ffn1 ? &tm1 : type == IT_F2 ? &tm2 : &tmm;
        const CUtensorMap* tc = ffn1 ? &tm3 : tb;
        const int c0 = ffn1 ? idx * (128 >> sz) : idx * (256 >> sz) + (type == IT_MOD ? 2048 : 0), c2 = ffn1 ? c0 : c0 + 128;
        const int dk = sz == 2 ? 1 : 0;
        const CUtensorMap* t0 = hb == 1 && sz == 1 ? tc : tb;
        const int ca = hb == 0 || sz == 2 || (sz == 1 && ffn1) ? c0 : c0 + 64;
        const uint32_t off = (sz == 2 ? 32768 : 16384) + hb * 8192;
        const uint32_t cold = type == IT_MOD ? D_MOD : type == IT_UV ? D_UV : H_NST;
        if (type == IT_MOD || type == IT_UV) {
          if (lane == 0) wait_flag2(&g_flags[UV_WAIT && type == IT_UV ? FL_MOD : FL_GO], UV_WAIT && type == IT_UV ? UV_WAIT : 1);
          __syncwarp();
        }
#pragma unroll 1
        for (int kb = part * nkb; kb < (part + 1) * nkb; kb += 1 + dk) {
          const uint32_t d = sb + st * H_STAGE + off, fb = bars + HB_FULL + st * 8;
          mbar_wait(bars + HB_EMPTY + st * 8, ph);
          if (cold < H_NST) mbar_wait(bars + HB_FULL + ((st - cold) & 3) * 8, st >= cold ? ph ^ 1 : ph);
          if (elect_one()) {
            tma5d(d, t0, ca, kb + hb * dk, fb);
            if (sz == 0) tma5d(d + 16384, tc, c2 + hb * 64, kb, fb);
          }
          if (++st == H_NST) { st = 0; ph ^= 1; }
        }
        if (it & IT_GATHER) {
#pragma unroll 1
          for (int p = 1; p < (1 << lgp); p++) {
            mbar_wait(bars + HB_EMPTY + st * 8, ph);
            if (++st == H_NST) { st = 0; ph ^= 1; }
          }
        }
      }
    } else if (warp == 9) {
      uint32_t have;
      auto claim = [&]() {
        uint32_t q = 0;
        if (lane == 0) q = atomicAdd(&g_flags[FL_HEAD], 1);
        q = __shfl_sync(0xffffffffu, q, 0);
        const uint32_t it = q < list.n ? list.it[q] : 0;
        int f; uint32_t target;
        item_deps(it & 7, (it >> 3) & 15, lane, f, target);
        have = __ballot_sync(0xffffffffu, ld_acquire(&g_flags[f]) >= target);
        asm volatile("fence.proxy.async.global;" ::: "memory");
        return it | (q << 19);
      };
      auto hand_out = [&](uint32_t n, uint32_t it) {
        mbar_wait(bars + HB_IEMPTY + (n & 1) * 8, ((n >> 1) & 1) ^ 1);
        if (elect_one()) {
          sts32(bars + HB_ITEM + (n & 1) * 4, it);
          sts32(bars + HB_HAVE + (n & 1) * 4, have);
          mbar_arrive(bars + HB_IFULL + (n & 1) * 8);
        }
      };
      uint32_t next = claim();
      hand_out(0, next);
#pragma unroll 1
      for (uint32_t n = 0;; n++) {
        const uint32_t itq = next;
        const int type = itq & 7, mt = (itq >> 3) & 15;
        if (type == IT_END) break;
        mbar_wait(bars + HB_NEXT, n & 1);
        next = claim();
        const bool split = (itq >> 17) & 3, gath = itq & IT_GATHER;
        const bool hold = split && (gath ? (type == IT_OUT ? HOLD & 2 : false) : type == IT_OUT ? HOLD & 1 : HOLD & 4);
        if (!hold) hand_out(n + 1, next);
        if (n & 1) bar_sync<3, 288>(); else bar_sync<2, 288>();
        if (lane == 0) {
          const uint32_t inc = lds32(bars + HB_INC + (n & 1) * 4);
          if (inc) {
            fence_gpu();
            const int idx = (itq >> 7) & 63, sz = item_sz(itq);
            const int mv = (idx >> sz) >> 2;
            uint32_t* fl = &g_flags[type == IT_MOD ? (mv == 0 ? FL_MODA : mv == 3 ? FL_MODB : FL_MOD) : type == IT_UV ? FL_UV : type == IT_XT ? FL_XT + 8 * mt
                                    : type == IT_OUT ? FL_OUT + 8 * mt + ((2 * idx) >> sz) : FL_F1 + 8 * mt + (idx >> (2 + sz))];
            if (((itq >> 17) & 3) && !(itq & IT_GATHER)) fl = &g_flags[FL_SPL + split_tile(type, mt, idx)];
            red_add_u32(fl, inc);
            if (type == IT_OUT && sz == 0) red_add_u32(fl + 1, inc);
          }
        }
        __syncwarp();
        if (hold) hand_out(n + 1, next);
      }
      asm volatile("griddepcontrol.wait;" ::: "memory");
      uint32_t k = 0;
      if (lane == 0) { fence_gpu(); k = atomicAdd(&g_flags[FL_EXIT], 1); }
      k = __shfl_sync(0xffffffffu, k, 0);
      if (k == gridDim.x - 1) {
        fence_gpu();
        for (int i = lane; i < 1024; i += 32) g_flags[i] = 0;
      }
    }
  } else {
    asm volatile("setmaxnreg.inc.sync.aligned.u32 232;");
    const int wg = warp >> 2;
    const bool leader = (tid & 127) == 0;
    uint32_t st = 0, ph = 0;
    uint32_t nxt = 0;
#pragma unroll 1
    for (uint32_t n = 0;; n++) {
      uint32_t itq = nxt;
      if (itq == 0) {
        mbar_wait(bars + HB_IFULL + (n & 1) * 8, (n >> 1) & 1);
        itq = lds32(bars + HB_ITEM + (n & 1) * 4);
      }
      itq = __shfl_sync(0xffffffffu, itq, 0);
      nxt = 0;
      auto peek = [&]() {
        if (PEEK && mbar_test(bars + HB_IFULL + ((n + 1) & 1) * 8, ((n + 1) >> 1) & 1)) nxt = lds32(bars + HB_ITEM + ((n + 1) & 1) * 4);
      };
      auto finish = [&](uint32_t inc) {
        if (tid == 0) sts32(bars + HB_INC + (n & 1) * 4, inc);
        if (n & 1) bar_arrive<3, 288>(); else bar_arrive<2, 288>();
      };
      auto again = [&](int level, uint32_t inc) {
        if (PEEK < level) return false;
        nxt = __shfl_sync(0xffffffffu, nxt, 0);
        if (((nxt ^ itq) & 0x6007) != 0) return false;
        finish(inc);
        n++;
        itq = nxt;
        nxt = 0;
        HT(0);
        return true;
      };
      const int type = itq & 7, mt = (itq >> 3) & 15, idx = (itq >> 7) & 63, sz = item_sz(itq);
      uint32_t inc = type == IT_OUT ? (sz == 2 ? 1 : 2) : type == IT_F1 || type == IT_MOD ? 2 >> sz : type != IT_F2;
#define VA (sb + H_VEC + (n & 1) * 3072)
#define MT ((itq >> 3) & 15)
#define IDX ((itq >> 7) & 63)
#define SPLIT (itq >> 15) & 3, (itq >> 17) & 3, (itq & IT_GATHER) != 0
      if (type == IT_END) break;
      HT(0);
      if (type == IT_OUT) {
        if (sz == 0) h_residual<256, false>(sb, VA, mt, idx * 256, st, ph, warp, lane, out, peek);
        else if (sz == 1) { do h_residual<128, false>(sb, VA, MT, IDX * 128, st, ph, warp, lane, out, peek); while (again(5, 2)); }
        else { do h_residual<64, false>(sb, VA, MT, IDX * 64, st, ph, warp, lane, out, peek, SPLIT); while (again(5, 1)); }
      } else if (type == IT_F2) {
        if (sz == 0) h_residual<256, true>(sb, VA, mt, idx * 256, st, ph, warp, lane, out, peek);
        else if (sz == 1) { do h_residual<128, true>(sb, VA, MT, IDX * 128, st, ph, warp, lane, out, peek); while (again(4, 0)); }
        else {
          do {
            h_residual<64, true>(sb, VA, MT, IDX * 64, st, ph, warp, lane, out, peek, SPLIT);
            inc = ((itq >> 17) & 3) && !(itq & IT_GATHER);
          } while (again(4, inc));
        }
      } else if (type == IT_XT) {
        const int rg = idx * 8 + warp;
        const uint32_t* xp = reinterpret_cast<const uint32_t*>(x + (size_t)(mt * 128 + rg * 8 + (lane >> 2)) * D_) + (lane & 3);
        uint8_t* tp = g_x1 + (size_t)mt * 262144 + rg * 512 + tile_lane(0, lane);
        if (lane < 16) g_stat[(mt * 128 + rg * 8) * 2 + lane] = 0.f;
#pragma unroll 1
        for (int b = 0; b < 2; b++) {
          uint32_t v[64];
#pragma unroll
          for (int i = 0; i < 64; i++) v[i] = __ldg(xp + 256 * b + 4 * i);
#pragma unroll
          for (int i = 0; i < 16; i++)
            *reinterpret_cast<uint4*>(tp + tile_off(16 * b + i, 0)) = make_uint4(v[4 * i], v[4 * i + 1], v[4 * i + 2], v[4 * i + 3]);
        }
      } else if (type == IT_F1) {
        if (sz == 1) {
          do {
            float acc[64];
            h_mainloop<128, 0>(acc, sb, 16, st, ph, wg, leader, []() {}, peek);
            h_swiglu<128>(acc, VA, MT, IDX, warp, lane);
          } while (again(3, 1));
        } else {
          do {
            float acc[128];
            h_mainloop<256, 0>(acc, sb, 16, st, ph, wg, leader, []() {}, peek);
            h_swiglu<256>(acc, VA, MT, IDX * 2, warp, lane);
          } while (again(2, 2));
        }
      } else {
        if (type == IT_UV && tid == 0) wait_flag2(&g_flags[FL_MOD], 16);
        bar_sync<1, 256>();
        {
          const uint32_t* src = reinterpret_cast<const uint32_t*>(type == IT_UV ? g_mod + (wg == 0 ? 4 : 3) * D_ : cvec) + ((tid & 127) >> 2) * 16 + (tid & 3);
          uint32_t v[4];
#pragma unroll
          for (int j = 0; j < 4; j++) v[j] = __ldcg(src + 4 * j);
          const uint32_t p = sb + H_STG + ((tid & 127) >> 2) * 512 + (tid & 3) * 16;
          if (type == IT_MOD) {
#pragma unroll 1
            for (int j = 0; j < 4; j++) {
              const float c0 = bf_lo(v[0]), c1 = bf_hi(v[0]);
              v[0] = v[1]; v[1] = v[2]; v[2] = v[3];
              v[3] = pack2(c0 / (1.f + __expf(-c0)), c1 / (1.f + __expf(-c1)));
            }
          }
          if (type == IT_UV && wg == 0) sts128(p, 0x3f803f80u, 0x3f803f80u, 0x3f803f80u, 0x3f803f80u);
          if (type == IT_UV || wg == 0) sts128(type == IT_MOD ? p : wg == 0 ? p + 64 : (p ^ 16) + 128, v[0], v[1], v[2], v[3]);
        }
        fence_async_smem();
        bar_sync<1, 256>();
        float acc[8] = {0.f, 0.f, 0.f, 0.f, 0.f, 0.f, 0.f, 0.f};
        const uint64_t dw = mkdesc(sb + 16384 + wg * (16384 >> sz), 8192, 1024, 1), dv = mkdesc(sb + H_STG, 16, 0, 2);
#pragma unroll 1
        for (int i = 0; i < 16; i++) {
          mbar_wait(bars + HB_FULL + st * 8, ph);
          if (i == 0) HT(1);
          WG_FENCE();
#pragma unroll
          for (int k = 0; k < 4; k++) {
            const uint64_t a = dw + st * (H_STAGE >> 4) + k * 128, b = dv + i * 64 + (k >> 1) * 32 + (k & 1) * 2;
            wg_ss8(acc, a, b); wg_ss8(acc + 4, a + (sz ? 0 : 512), b);
          }
          WG_COMMIT();
          WG_WAIT(0);
          if (leader) mbar_arrive(bars + HB_EMPTY + st * 8);
          if (++st == H_NST) { st = 0; ph ^= 1; }
        }
        HT(2);
        reg_fence<8>(acc);
        const int t = lane & 3, c = (warp & 3) * 16 + (lane >> 2);
#pragma unroll
        for (int j = 0; j < 4; j++) {
          const int cj = c + (j >> 1) * 64 + (j & 1) * 8;
          if (type == IT_MOD) { if (t == 0 && (j < 2 || !sz)) g_mod[2048 + ((idx * 256 + wg * 128) >> sz) + cj] = __float2bfloat16(acc[2 * j]); }
          else if (t < 2) g_uv[idx * 512 + (cj >> 1) * 8 + wg * 4 + t * 2 + (cj & 1)] = (wg == 0 ? 0.5f : 1.f) * (t == 0 ? acc[2 * j] + acc[2 * j + 1] : acc[2 * j]);
        }
      }
      finish(inc);
    }
  }
}

const uint32_t h_items[] = {
  2, 130, 10, 138, 18, 146, 26, 154, 34, 162, 42, 170, 50, 178, 58, 186, 66, 194, 74, 202, 82, 210, 90, 218,
  98, 226, 106, 234, 114, 242, 122, 250, 1, 129, 257, 385, 513, 641, 769, 897, 1025, 1153, 1281, 1409, 4, 132, 260, 388,
  516, 644, 772, 900, 1028, 1156, 1284, 1412, 1540, 1668, 1796, 1924, 2052, 2180, 2308, 16387, 2436, 16515, 16643, 16771, 16899, 17027, 17155, 17283,
  17411, 17539, 17667, 17795, 17923, 18051, 18179, 18307, 2564, 2692, 2820, 2948, 3076, 3204, 3332, 1537, 3460, 1665, 1793, 1921, 16395, 16523, 16651, 16779,
  16907, 17035, 17163, 17291, 17419, 17547, 17675, 17803, 17931, 18059, 18187, 18315, 8211, 8339, 8467, 8595, 8723, 5, 133, 261, 389, 517, 645, 773,
  901, 1029, 1157, 1285, 1413, 1541, 1669, 1797, 1925, 2053, 2181, 2309, 2437, 8851, 8979, 9107, 2565, 2693, 2821, 2949, 3077, 3205, 3333, 3461,
  13, 141, 269, 781, 909, 1037, 1165, 1293, 1421, 1549, 1677, 1805, 1933, 2061, 2189, 2317, 2445, 397, 8219, 525, 8347, 653, 8475, 2573,
  2701, 2829, 8603, 2957, 3085, 8731, 3213, 3341, 17691, 3469, 8198, 8326, 8454, 8582, 17819, 2837, 8710, 8838, 17947, 8966, 18075, 9094, 3093, 18203,
  21, 3221, 18331, 16419, 3349, 16547, 16675, 3477, 16803, 1173, 16931, 1301, 17059, 1429, 2965, 1557, 17187, 1685, 17315, 2197, 17443, 1813, 17571, 2325,
  17699, 1941, 149, 2453, 277, 2069, 405, 2581, 533, 2709, 661, 29, 789, 157, 917, 285, 1045, 413, 17827, 541, 17955, 669, 18083, 797,
  18211, 925, 18339, 1053, 14, 1181, 142, 1309, 270, 1437, 398, 1565, 1693, 1821, 8235, 8363, 8491, 8619, 8747, 8875, 1949, 9003, 9131, 2077,
  2205, 2333, 3229, 2461, 3357, 2589, 3485, 2717, 8243, 2845, 8371, 2973, 8499, 3101, 8627, 8755, 8883, 9011, 9139, 37, 165, 293, 421, 549,
  677, 805, 933, 1061, 1189, 1317, 1445, 1573, 1701, 1829, 1957, 8251, 8379, 8507, 8635, 8763, 8891, 9019, 9147, 2085, 2213, 2341, 2469, 2597,
  2725, 2853, 2981, 3109, 3237, 3365, 3493, 45, 173, 301, 429, 557, 685, 813, 941, 1069, 1453, 1197, 1581, 1325, 9027, 1709, 1837, 1965,
  8259, 8387, 8515, 8643, 8771, 8899, 693, 9155, 2093, 2221, 2349, 2477, 2605, 2733, 2861, 2989, 3117, 3245, 9163, 2101, 2229, 3373, 3501, 53,
  181, 309, 437, 565, 821, 949, 1077, 1205, 1333, 1461, 1589, 1717, 1845, 1973, 8267, 8395, 8523, 8651, 8779, 8907, 9035, 2357, 2485, 2613,
  2741, 2869, 2997, 3125, 3253, 3381, 3509, 61, 189, 317, 445, 573, 701, 829, 957, 1085, 1213, 1341, 1469, 1597, 1725, 2493, 8275, 1853,
  8403, 1981, 8531, 2109, 8659, 2237, 8787, 2365, 8915, 9043, 9171, 2621, 2749, 2877, 3005, 3133, 3261, 3389, 3517, 1733, 69, 453, 197, 1861,
  325, 581, 709, 837, 1477, 965, 1605, 1093, 1989, 1221, 2117, 1349, 12869, 12997, 2245, 2501, 8283, 8411, 8539, 2629, 8667, 2757, 8795, 2885,
  8923, 9179, 3269, 3397, 1229, 3525, 973, 77, 205, 333, 461, 589, 1357, 717, 845, 1101, 3013, 9051, 3141, 1485, 1613, 1741, 1869, 1997,
  8675, 8291, 8803, 8419, 8931, 8547, 9059, 341, 3277, 85, 22, 469, 3405, 597, 3533, 725, 853, 981, 1109, 1237, 1365, 1493, 9187, 2125,
  2253, 2893, 2381, 2509, 3021, 213, 2637, 3149, 2765, 1621, 1749, 1877, 2005, 2133, 2261, 8427, 8299, 2389, 8555, 2517, 8683, 2645, 8811, 2773,
  8939, 2901, 9067, 3029, 9195, 150, 278, 406, 30, 158, 430, 286, 414, 38, 46, 166, 174, 294, 302, 422, 54, 182, 310, 438,
  8307, 8435, 8563, 8691, 8819, 8947, 9075, 9203, 278651, 311419, 344187, 376955, 278779, 311547, 344315, 377083, 180987, 312315, 148347, 345083, 181115, 148731, 181499, 148859,
  3157, 62, 148987, 149243, 278907, 3285, 190, 318, 149115, 311675, 148219, 344443, 279547, 181627, 1757, 377211, 181755, 181883, 1885, 147963, 2013, 180731, 2141, 2269,
  2397, 101, 2525, 182011, 148091, 180859, 3165, 149371, 182139, 280571, 313339, 346107, 279675, 377851, 378875, 312443, 345211, 377979, 446, 2653, 2781, 2909, 3037, 3293,
  3421, 3549, 3413, 733, 229, 989, 741, 1117, 1245, 869, 997, 1373, 1125, 1501, 1253, 1509, 3541, 93, 1629, 221, 349, 477, 1381, 605,
  357, 485, 861, 613, 1637, 1893, 2021, 2149, 2277, 2405, 2533, 2661, 2789, 12269, 2917, 3045, 12397, 3173, 12525, 3301, 12653, 3429, 12781, 12909,
  3557, 13037, 8301, 8429, 13165, 13293, 1765, 8557, 8685, 13421, 13549, 8813, 13677, 9069, 13805, 9197, 13933, 8941, 14061, 9325, 9453, 14189, 14317, 9581,
  9709, 14445, 14573, 9837, 10861, 10989, 11117, 11245, 11373, 11501, 11629, 9965, 14701, 14829, 10093, 10221, 14957, 15213, 15341, 10605, 10733, 15085, 11757, 10349,
  8573, 11885, 10477, 8701, 12013, 2549, 12141, 2677, 8317, 2805, 2933, 8262, 8390, 8518, 8646, 8774, 9030, 9158, 8902, 9038, 9166, 8270, 8398, 8526,
  8654, 8782, 3061, 8910, 3189, 3317, 117, 245, 373, 501, 629, 757, 3445, 3573, 1269, 1397, 1525, 8445, 8829, 8957, 9085, 9213, 9341, 9469,
  9597, 9725, 9853, 10621, 9981, 10109, 10749, 11645, 10237, 11773, 12029, 10365, 11901, 12157, 12285, 10493, 885, 12413, 1653, 1781, 1013, 1909, 1141, 12541,
  2037, 12669, 2165, 12797, 2293, 12925, 2421, 13053, 13181, 13309, 13565, 13437, 13693, 13821, 10877, 11005, 11133, 11517, 13949, 14077, 14205, 14333, 14461, 14589,
  14717, 14845, 14973, 8278, 8406, 8534, 15101, 8662, 15229, 8790, 15357, 9174, 8918, 11261, 8286, 9046, 8542, 11389, 8414, 8670, 8798, 8926, 9054, 9182,
  147558, 180326, 147686, 180454, 147814, 180582, 16870, 16998, 17126, 17254, 17382, 17510, 17638, 17766, 17894, 18022, 18150, 18278, 18406, 16494, 16622, 16750, 16878, 17006,
  17134, 17390, 17518, 17646, 17774, 17902, 18030, 18158, 17262, 18414, 18286, 16894, 17022, 17150, 17278, 17534, 17662, 17790, 18046, 18174, 278774, 16510, 16638, 311542,
  16766, 18302, 344310, 18430, 147574, 17918, 377078, 17406, 180342, 147830, 180598, 148470, 181238, 182006, 149366, 182134, 148598, 181366, 148726, 148854, 181494, 181622, 147958, 180726,
  148086, 180854, 148214, 180982, 148342, 181110, 148982, 181750, 149110, 181878, 149238, 149494, 182262,
};
void build_list(HList& l) {
  l.n = sizeof(h_items) / sizeof(h_items[0]);
  for (uint32_t i = 0; i < l.n; i++) l.it[i] = h_items[i];
}

typedef CUresult (*EncodeFn)(CUtensorMap*, CUtensorMapDataType, cuuint32_t, void*, const cuuint64_t*, const cuuint64_t*,
                             const cuuint32_t*, const cuuint32_t*, CUtensorMapInterleave, CUtensorMapSwizzle,
                             CUtensorMapL2promotion, CUtensorMapFloatOOBfill);

#define PROMO_W CU_TENSOR_MAP_L2_PROMOTION_L2_128B
#define PROMO_O CU_TENSOR_MAP_L2_PROMOTION_L2_128B
#define PROMO_M CU_TENSOR_MAP_L2_PROMOTION_L2_128B
#define PROMO_H CU_TENSOR_MAP_L2_PROMOTION_L2_128B
void make_map(EncodeFn fn, CUtensorMap* m, const void* p, uint64_t cols, uint64_t rows, uint32_t bc, uint32_t br, CUtensorMapSwizzle sw,
              CUtensorMapL2promotion promo) {
  cuuint64_t dims[2] = {cols, rows};
  cuuint64_t strides[1] = {cols * 2};
  cuuint32_t box[2] = {bc, br};
  cuuint32_t es[2] = {1, 1};
  fn(m, CU_TENSOR_MAP_DATA_TYPE_BFLOAT16, 2, const_cast<void*>(p), dims, strides, box, es, CU_TENSOR_MAP_INTERLEAVE_NONE, sw,
     promo, CU_TENSOR_MAP_FLOAT_OOB_FILL_NONE);
}

void make_map_perm(EncodeFn fn, CUtensorMap* m, const void* p, uint64_t cols, uint64_t rows, bool perm) {
  cuuint64_t dims[5] = {cols, 2, 4, 4, rows / 32};
  cuuint64_t strides[4] = {cols * 2, cols * 2 * (perm ? 8 : 2), cols * 2 * (perm ? 2 : 8), cols * 2 * 32};
  cuuint32_t box[5] = {64, 2, 4, 4, 2};
  cuuint32_t es[5] = {1, 1, 1, 1, 1};
  fn(m, CU_TENSOR_MAP_DATA_TYPE_BFLOAT16, 5, const_cast<void*>(p), dims, strides, box, es, CU_TENSOR_MAP_INTERLEAVE_NONE,
     CU_TENSOR_MAP_SWIZZLE_128B, PROMO_H, CU_TENSOR_MAP_FLOAT_OOB_FILL_NONE);
}

}

extern "C" void kernel_launch(void* const* d_in, const int* in_sizes, int n_in, void* d_out, int out_size) {
  const __nv_bfloat16* x = (const __nv_bfloat16*)d_in[0];
  const __nv_bfloat16* mem0 = (const __nv_bfloat16*)d_in[1];
  const __nv_bfloat16* cvec = (const __nv_bfloat16*)d_in[11];
  static EncodeFn enc = nullptr;
  if (!enc) {
    cudaDriverEntryPointQueryResult qr;
    void* fp = nullptr;
    cudaGetDriverEntryPoint("cuTensorMapEncodeTiled", &fp, cudaEnableDefault, &qr);
    enc = (EncodeFn)fp;
    cudaFuncSetAttribute(kernel_R, cudaFuncAttributeMaxDynamicSharedMemorySize, R_SMEM);
    cudaFuncSetAttribute(kernel_H, cudaFuncAttributeMaxDynamicSharedMemorySize, H_SMEM);
  }
  CUtensorMap tmq, tmk, tmv, tmo, tmm;
  make_map(enc, &tmm, d_in[12], 6144, 1024, 64, 64, CU_TENSOR_MAP_SWIZZLE_NONE, PROMO_M);
  make_map(enc, &tmq, d_in[2], 4096, 1024, 64, 64, CU_TENSOR_MAP_SWIZZLE_128B, PROMO_W);
  make_map(enc, &tmk, d_in[3], 4096, 1024, 64, 64, CU_TENSOR_MAP_SWIZZLE_128B, PROMO_W);
  make_map(enc, &tmv, d_in[4], 4096, 1024, 64, 64, CU_TENSOR_MAP_SWIZZLE_128B, PROMO_W);
  make_map(enc, &tmo, d_in[5], 1024, 4096, 16, 128, CU_TENSOR_MAP_SWIZZLE_32B, PROMO_O);
  RDesc dsc;
  for (int k = 0; k < 32; k++) {
    dsc.tok[k] = mkdesc(0x400 + (k < 16 ? R_GA : R_GB) + ((k & 15) >> 2) * 4096 + (k & 3) * 256, 128, 1024, 0);
    dsc.tail_a[k] = mkdesc(0x400 + R_TAIL + k * 2048, 1024, 1024, 1);
    if (k < 16) dsc.tail_b[k] = mkdesc(0x400 + R_GA + k * 256, 128, 4096, 0);
  }
  kernel_R<<<96, 256, R_SMEM, cudaStreamPerThread>>>(tmq, tmk, tmv, tmo, tmm, x, mem0, cvec, dsc);

  CUtensorMap ho, h1, h3, h2, hm;
  make_map_perm(enc, &ho, d_in[5], 1024, 4096, false);
  make_map_perm(enc, &h1, d_in[8], F_, 1024, true);
  make_map_perm(enc, &h3, d_in[9], F_, 1024, true);
  make_map_perm(enc, &h2, d_in[10], 1024, F_, true);
  make_map_perm(enc, &hm, d_in[12], 6144, 1024, true);
  HList list;
  build_list(list);
  {
    bool seen[12 * 16] = {};
    for (int i = (int)list.n - 1; i >= 0; i--) {
      const uint32_t it = list.it[i];
      if ((it >> 17) & 3) {
        const int t = split_tile(it & 7, (it >> 3) & 15, (it >> 7) & 63);
        if (!seen[t]) list.it[i] |= IT_GATHER;
        seen[t] = true;
      }
    }
  }
  cudaLaunchConfig_t cfg = {};
#define H_GRID 132
  cfg.gridDim = dim3(H_GRID); cfg.blockDim = dim3(384); cfg.dynamicSmemBytes = H_SMEM; cfg.stream = cudaStreamPerThread;
  cudaLaunchAttribute at[1];
  at[0].id = cudaLaunchAttributeProgrammaticStreamSerialization;
  at[0].val.programmaticStreamSerializationAllowed = 1;
  cfg.attrs = at;
  cfg.numAttrs = 1;
  cudaLaunchKernelEx(&cfg, kernel_H, ho, h1, h3, h2, hm, x, cvec, (__nv_bfloat16*)d_out, list);
}
```
